```python
import torch

def _softmax(x, axis=-1):
    return torch.softmax(x, dim=axis)
def _gelu(x):
    return torch.nn.functional.gelu(x, approximate="tanh")
def _silu(x):
    return torch.nn.functional.silu(x)
def _sigmoid(x):
    return torch.sigmoid(x)
def _layernorm(x, axis=-1, eps=1e-5):
    m = x.mean(dim=axis, keepdim=True)
    v = x.var(dim=axis, keepdim=True, unbiased=False)
    return (x - m) / torch.sqrt(v + eps)
def _scatter_add(tgt, idx, src, axis=0):
    return tgt.clone().index_add_(axis, idx, src)
def _segment_sum(src, seg, n):
    out = torch.zeros((n,) + src.shape[1:], dtype=src.dtype)
    return out.index_add_(0, seg, src)
def _pad(x, pw):
    flat = tuple(v for pair in reversed(pw) for v in pair)
    return torch.nn.functional.pad(x, flat)

kernel_name = 'parallel_sum__linear_attn_block__moe_arch_mod__prompt'

def setup_inputs():

    _w = (lambda a: (lambda t: t.to(torch.bfloat16) if t.is_floating_point() else t)(torch.as_tensor(a)))
    def _A_setup():
        B, S, D = 1, 2048, 1024
        return {
            "x": _w((lambda *s: torch.randn(*s, dtype=torch.bfloat16) * 0.05)(B, S, D)),
            "wqkv": _w((lambda *s: torch.randn(*s, dtype=torch.bfloat16) * 0.4)(D, 3 * D)),
            "wo": _w((lambda *s: torch.randn(*s, dtype=torch.bfloat16) * 0.2)(D, D)),
        }
    _A_in = _A_setup()

    def _B_setup():
        B, S, D, F, C = 1, 2048, 1024, 3584, 8
        return {
            "x": _w((lambda *s: torch.randn(*s, dtype=torch.bfloat16) * 0.05)(B, S, D)),
            "w_r": _w((lambda *s: torch.randn(*s, dtype=torch.bfloat16) * 0.05)(D)),
            "w_gate": _w((lambda *s: torch.randn(*s, dtype=torch.bfloat16) * 0.05)(D, F)),
            "w_up": _w((lambda *s: torch.randn(*s, dtype=torch.bfloat16) * 0.05)(D, F)),
            "w_down": _w((lambda *s: torch.randn(*s, dtype=torch.bfloat16) * 0.05)(F, D)),
        }
    _B_in = _B_setup()

    return {
        "A_x": _A_in["x"],
        "A_wqkv": _A_in["wqkv"],
        "A_wo": _A_in["wo"],
        "B_x": _B_in["x"],
        "B_w_r": _B_in["w_r"],
        "B_w_gate": _B_in["w_gate"],
        "B_w_up": _B_in["w_up"],
        "B_w_down": _B_in["w_down"],
    }

def reference(A_x, A_wqkv, A_wo, B_x, B_w_r, B_w_gate, B_w_up, B_w_down):
    def _A_ref(x, wqkv, wo):
        B, S, D = x.shape
        H = 32; Dh = D // H
        qkv = (lambda x, *d: x.permute(*d))((x @ wqkv).reshape(B, S, 3, H, Dh), 2, 0, 3, 1, 4)
        q, k, v = qkv[0], qkv[1], qkv[2]
        phi = lambda t: torch.where(t > 0, t + 1, torch.exp(t)) + 1e-6
        pq, pk = phi(q), phi(k)
        kv = torch.einsum("bhsd,bhse->bhde", pk, v)
        z = torch.einsum("bhsd->bhd", pk)
        num = torch.einsum("bhqd,bhde->bhqe", pq, kv)
        den = torch.einsum("bhqd,bhd->bhq", pq, z)[..., None] + 1e-6
        o = num / den
        return (lambda x, *d: x.permute(*d))(o, 0, 2, 1, 3).reshape(B, S, D) @ wo

    def _B_ref(x, w_r, w_gate, w_up, w_down):
        B, S, D = x.shape
        C = 8
        r = x @ w_r
        idx = torch.argsort(-r, axis=-1)[:, :C]
        idx_e = (lambda x, n, axis: torch.repeat_interleave(x, n, dim=axis))(idx.reshape(B, C, 1), D, axis=2)
        x_sel = (lambda x, i, axis: torch.take_along_dim(x, i, dim=axis))(x, idx_e, axis=1)
        g = _silu(x_sel @ w_gate)
        u = x_sel @ w_up
        y = (g * u) @ w_down
        r_sel = _sigmoid((lambda x, i, axis: torch.take_along_dim(x, i, dim=axis))(r, idx, axis=1))
        y = y * r_sel.reshape(B, C, 1)
        b_off = (torch.arange(B) * S).reshape(B, 1)
        flat_idx = (idx + b_off).reshape(B * C)
        zero = (x * 0.0).reshape(B * S, D)
        upd = _scatter_add(zero, flat_idx, y.reshape(B * C, D), axis=0)
        return x + upd.reshape(B, S, D)

    x = A_x
    xn = _layernorm(x, axis=-1)
    return x + _A_ref(xn, A_wqkv, A_wo) + _B_ref(xn, B_w_r, B_w_gate, B_w_up, B_w_down)
```

```cpp
#include <cuda_runtime.h>
#include <cuda.h>
#include <cuda_bf16.h>
#include <stdint.h>

namespace {

template <int TA, int TB> __device__ __forceinline__ void wgmma_ss_n128(float (&d)[64], uint64_t da, uint64_t db) {
  asm volatile("wgmma.mma_async.sync.aligned.m64n128k16.f32.bf16.bf16 "
  "{%0,%1,%2,%3,%4,%5,%6,%7,%8,%9,%10,%11,%12,%13,%14,%15,%16,%17,%18,%19,%20,%21,%22,%23,%24,%25,%26,%27,%28,%29,%30,%31,%32,%33,%34,%35,%36,%37,%38,%39,%40,%41,%42,%43,%44,%45,%46,%47,%48,%49,%50,%51,%52,%53,%54,%55,%56,%57,%58,%59,%60,%61,%62,%63}, "
  "%64, %65, 1, 1, 1, %66, %67;"
  : "+f"(d[0]),"+f"(d[1]),"+f"(d[2]),"+f"(d[3]),"+f"(d[4]),"+f"(d[5]),"+f"(d[6]),"+f"(d[7]),"+f"(d[8]),"+f"(d[9]),"+f"(d[10]),"+f"(d[11]),"+f"(d[12]),"+f"(d[13]),"+f"(d[14]),"+f"(d[15]),"+f"(d[16]),"+f"(d[17]),"+f"(d[18]),"+f"(d[19]),"+f"(d[20]),"+f"(d[21]),"+f"(d[22]),"+f"(d[23]),"+f"(d[24]),"+f"(d[25]),"+f"(d[26]),"+f"(d[27]),"+f"(d[28]),"+f"(d[29]),"+f"(d[30]),"+f"(d[31]),"+f"(d[32]),"+f"(d[33]),"+f"(d[34]),"+f"(d[35]),"+f"(d[36]),"+f"(d[37]),"+f"(d[38]),"+f"(d[39]),"+f"(d[40]),"+f"(d[41]),"+f"(d[42]),"+f"(d[43]),"+f"(d[44]),"+f"(d[45]),"+f"(d[46]),"+f"(d[47]),"+f"(d[48]),"+f"(d[49]),"+f"(d[50]),"+f"(d[51]),"+f"(d[52]),"+f"(d[53]),"+f"(d[54]),"+f"(d[55]),"+f"(d[56]),"+f"(d[57]),"+f"(d[58]),"+f"(d[59]),"+f"(d[60]),"+f"(d[61]),"+f"(d[62]),"+f"(d[63])
  : "l"(da), "l"(db), "n"(TA), "n"(TB));
}
template <int TB> __device__ __forceinline__ void wgmma_rs_n72(float (&d)[36], uint32_t a0, uint32_t a1, uint32_t a2, uint32_t a3, uint64_t db) {
  asm volatile("wgmma.mma_async.sync.aligned.m64n72k16.f32.bf16.bf16 "
  "{%0,%1,%2,%3,%4,%5,%6,%7,%8,%9,%10,%11,%12,%13,%14,%15,%16,%17,%18,%19,%20,%21,%22,%23,%24,%25,%26,%27,%28,%29,%30,%31,%32,%33,%34,%35}, "
  "{%36,%37,%38,%39}, %40, 1, 1, 1, %41;"
  : "+f"(d[0]),"+f"(d[1]),"+f"(d[2]),"+f"(d[3]),"+f"(d[4]),"+f"(d[5]),"+f"(d[6]),"+f"(d[7]),"+f"(d[8]),"+f"(d[9]),"+f"(d[10]),"+f"(d[11]),"+f"(d[12]),"+f"(d[13]),"+f"(d[14]),"+f"(d[15]),"+f"(d[16]),"+f"(d[17]),"+f"(d[18]),"+f"(d[19]),"+f"(d[20]),"+f"(d[21]),"+f"(d[22]),"+f"(d[23]),"+f"(d[24]),"+f"(d[25]),"+f"(d[26]),"+f"(d[27]),"+f"(d[28]),"+f"(d[29]),"+f"(d[30]),"+f"(d[31]),"+f"(d[32]),"+f"(d[33]),"+f"(d[34]),"+f"(d[35])
  : "r"(a0), "r"(a1), "r"(a2), "r"(a3), "l"(db), "n"(TB));
}
template <int TB> __device__ __forceinline__ void wgmma_rz_n72(float (&d)[36], uint32_t a0, uint32_t a1, uint32_t a2, uint32_t a3, uint64_t db) {
  asm volatile("wgmma.mma_async.sync.aligned.m64n72k16.f32.bf16.bf16 "
  "{%0,%1,%2,%3,%4,%5,%6,%7,%8,%9,%10,%11,%12,%13,%14,%15,%16,%17,%18,%19,%20,%21,%22,%23,%24,%25,%26,%27,%28,%29,%30,%31,%32,%33,%34,%35}, "
  "{%36,%37,%38,%39}, %40, 0, 1, 1, %41;"
  : "=f"(d[0]),"=f"(d[1]),"=f"(d[2]),"=f"(d[3]),"=f"(d[4]),"=f"(d[5]),"=f"(d[6]),"=f"(d[7]),"=f"(d[8]),"=f"(d[9]),"=f"(d[10]),"=f"(d[11]),"=f"(d[12]),"=f"(d[13]),"=f"(d[14]),"=f"(d[15]),"=f"(d[16]),"=f"(d[17]),"=f"(d[18]),"=f"(d[19]),"=f"(d[20]),"=f"(d[21]),"=f"(d[22]),"=f"(d[23]),"=f"(d[24]),"=f"(d[25]),"=f"(d[26]),"=f"(d[27]),"=f"(d[28]),"=f"(d[29]),"=f"(d[30]),"=f"(d[31]),"=f"(d[32]),"=f"(d[33]),"=f"(d[34]),"=f"(d[35])
  : "r"(a0), "r"(a1), "r"(a2), "r"(a3), "l"(db), "n"(TB));
}
template <int TB> __device__ __forceinline__ void wgmma_rs_n40(float (&d)[20], uint32_t a0, uint32_t a1, uint32_t a2, uint32_t a3, uint64_t db) {
  asm volatile("wgmma.mma_async.sync.aligned.m64n40k16.f32.bf16.bf16 "
  "{%0,%1,%2,%3,%4,%5,%6,%7,%8,%9,%10,%11,%12,%13,%14,%15,%16,%17,%18,%19}, "
  "{%20,%21,%22,%23}, %24, 1, 1, 1, %25;"
  : "+f"(d[0]),"+f"(d[1]),"+f"(d[2]),"+f"(d[3]),"+f"(d[4]),"+f"(d[5]),"+f"(d[6]),"+f"(d[7]),"+f"(d[8]),"+f"(d[9]),"+f"(d[10]),"+f"(d[11]),"+f"(d[12]),"+f"(d[13]),"+f"(d[14]),"+f"(d[15]),"+f"(d[16]),"+f"(d[17]),"+f"(d[18]),"+f"(d[19])
  : "r"(a0), "r"(a1), "r"(a2), "r"(a3), "l"(db), "n"(TB));
}
template <int TB> __device__ __forceinline__ void wgmma_rz_n40(float (&d)[20], uint32_t a0, uint32_t a1, uint32_t a2, uint32_t a3, uint64_t db) {
  asm volatile("wgmma.mma_async.sync.aligned.m64n40k16.f32.bf16.bf16 "
  "{%0,%1,%2,%3,%4,%5,%6,%7,%8,%9,%10,%11,%12,%13,%14,%15,%16,%17,%18,%19}, "
  "{%20,%21,%22,%23}, %24, 0, 1, 1, %25;"
  : "=f"(d[0]),"=f"(d[1]),"=f"(d[2]),"=f"(d[3]),"=f"(d[4]),"=f"(d[5]),"=f"(d[6]),"=f"(d[7]),"=f"(d[8]),"=f"(d[9]),"=f"(d[10]),"=f"(d[11]),"=f"(d[12]),"=f"(d[13]),"=f"(d[14]),"=f"(d[15]),"=f"(d[16]),"=f"(d[17]),"=f"(d[18]),"=f"(d[19])
  : "r"(a0), "r"(a1), "r"(a2), "r"(a3), "l"(db), "n"(TB));
}
template <int TB> __device__ __forceinline__ void wgmma_rs_n128(float (&d)[64], uint32_t a0, uint32_t a1, uint32_t a2, uint32_t a3, uint64_t db) {
  asm volatile("wgmma.mma_async.sync.aligned.m64n128k16.f32.bf16.bf16 "
  "{%0,%1,%2,%3,%4,%5,%6,%7,%8,%9,%10,%11,%12,%13,%14,%15,%16,%17,%18,%19,%20,%21,%22,%23,%24,%25,%26,%27,%28,%29,%30,%31,%32,%33,%34,%35,%36,%37,%38,%39,%40,%41,%42,%43,%44,%45,%46,%47,%48,%49,%50,%51,%52,%53,%54,%55,%56,%57,%58,%59,%60,%61,%62,%63}, "
  "{%64,%65,%66,%67}, %68, 1, 1, 1, %69;"
  : "+f"(d[0]),"+f"(d[1]),"+f"(d[2]),"+f"(d[3]),"+f"(d[4]),"+f"(d[5]),"+f"(d[6]),"+f"(d[7]),"+f"(d[8]),"+f"(d[9]),"+f"(d[10]),"+f"(d[11]),"+f"(d[12]),"+f"(d[13]),"+f"(d[14]),"+f"(d[15]),"+f"(d[16]),"+f"(d[17]),"+f"(d[18]),"+f"(d[19]),"+f"(d[20]),"+f"(d[21]),"+f"(d[22]),"+f"(d[23]),"+f"(d[24]),"+f"(d[25]),"+f"(d[26]),"+f"(d[27]),"+f"(d[28]),"+f"(d[29]),"+f"(d[30]),"+f"(d[31]),"+f"(d[32]),"+f"(d[33]),"+f"(d[34]),"+f"(d[35]),"+f"(d[36]),"+f"(d[37]),"+f"(d[38]),"+f"(d[39]),"+f"(d[40]),"+f"(d[41]),"+f"(d[42]),"+f"(d[43]),"+f"(d[44]),"+f"(d[45]),"+f"(d[46]),"+f"(d[47]),"+f"(d[48]),"+f"(d[49]),"+f"(d[50]),"+f"(d[51]),"+f"(d[52]),"+f"(d[53]),"+f"(d[54]),"+f"(d[55]),"+f"(d[56]),"+f"(d[57]),"+f"(d[58]),"+f"(d[59]),"+f"(d[60]),"+f"(d[61]),"+f"(d[62]),"+f"(d[63])
  : "r"(a0), "r"(a1), "r"(a2), "r"(a3), "l"(db), "n"(TB));
}
template <int TA, int TB> __device__ __forceinline__ void wgmma_ss_n8(float (&d)[4], uint64_t da, uint64_t db) {
  asm volatile("wgmma.mma_async.sync.aligned.m64n8k16.f32.bf16.bf16 "
  "{%0,%1,%2,%3}, "
  "%4, %5, 1, 1, 1, %6, %7;"
  : "+f"(d[0]),"+f"(d[1]),"+f"(d[2]),"+f"(d[3])
  : "l"(da), "l"(db), "n"(TA), "n"(TB));
}
template <int TA, int TB> __device__ __forceinline__ void wgmma_ss_n16(float (&d)[8], uint64_t da, uint64_t db) {
  asm volatile("wgmma.mma_async.sync.aligned.m64n16k16.f32.bf16.bf16 "
  "{%0,%1,%2,%3,%4,%5,%6,%7}, "
  "%8, %9, 1, 1, 1, %10, %11;"
  : "+f"(d[0]),"+f"(d[1]),"+f"(d[2]),"+f"(d[3]),"+f"(d[4]),"+f"(d[5]),"+f"(d[6]),"+f"(d[7])
  : "l"(da), "l"(db), "n"(TA), "n"(TB));
}

constexpr int SEQ = 2048, DM = 1024, FF = 3584;
constexpr int NCTA = 128, NSVC = 4;
constexpr int NUNIT = 112;
constexpr uint32_t SLOT = 16384;
constexpr uint32_t MISC = 14 * SLOT;
constexpr uint32_t SMEM_BYTES = MISC + 3072;
constexpr uint32_t M_MOE = 0;
constexpr uint32_t M_BAR = 2048;
constexpr uint32_t M_DUM = 2048 + 1020;
constexpr uint32_t M_IDX = 2048 + 688;
constexpr uint32_t M_KEY = 2048 + 960;
constexpr uint32_t M_TL = 2048 + 720;
#define NQ 5
constexpr int NF = 16 - NQ, NR = NQ == 5 ? 4 : 3;
constexpr int B_FXQ = 0, B_FKV = 3, B_AST = 6, B_MOE = 7, B_MF = 8  , B_CQ = 12, B_XS = 13, B_DF = 14, B_ZOK = 15, B_FWO = 21  , B_FQ = B_FWO - NQ,
              B_UP = 37, B_FIN = 38, B_KVB = 39, B_ME = 40  , B_HF = 44, B_AF = 45  , B_AR = 50  , B_GO = 52,
              B_FAUX = 53, B_EAUX = 54, B_T0 = 55, B_DE = 56, B_EA = 57  , B_VAL = 62  ,
              B_E = 67  , B_STG = 70, B_EQ = 71  , B_EO = 76  , NBAR = 83, B_KV4 = 83, B_MS = 84;
constexpr uint32_t MT = 9216, A_ONES = 12 * SLOT + 3 * MT, A_CS = A_ONES + 2048, A_ST = A_CS + 1536;
constexpr int S_V0 = 11, S_V1 = 7;
constexpr int C_B = 0, C_DONE = 32, NCNT = 2;
constexpr uint32_t QX_SLOTS = NQ == 5 ? 0x43102u : 0x354021u;
constexpr uint32_t QW_SLOTS = 0xB76A98u;
constexpr uint32_t qx(int k) { return (QX_SLOTS >> (4 * k)) & 15u; }
constexpr uint32_t qw(int k) { return (QW_SLOTS >> (4 * k)) & 15u; }
constexpr uint32_t S_KVB = 8, S_D0 = NQ == 5 ? 5 : 1, S_D1 = NQ == 5 ? 11 : 2;
constexpr int WQ0 = NQ == 5 ? 1 : 3;
constexpr uint32_t wo_slot_c(int i) { return i >= 9 ? wo_slot_c(i - 9) : (i == 7 ? S_D0 : (i == 8 ? S_D1 : (((i & 1) || i + WQ0 == 1) ? qx((i + WQ0) >> 1) : qw((i + WQ0) >> 1)))); }
constexpr uint64_t wo_slots() { uint64_t t = 0; for (int i = 0; i < 16; i++) t |= (uint64_t)wo_slot_c(i) << (4 * i); return t; }
constexpr uint64_t WO_SLOTS = wo_slots();
constexpr uint32_t A_SLOTS = 0xDC000u | (S_KVB << 8) | (qw(NQ - 1) << 4) | qx(NQ - 1);
constexpr uint32_t SX14 = qx(NQ - 2), SX15 = qx(NQ - 1), SXQ0 = qx(0);
#define WOD 2
#define PLC 3
#define PFG1 10
#define PFNS1 150
#define PFG0 3
#define RS0 0
#define WPF 1
#define POLLNS 150
#define SVNS 100
#define MPROMO CU_TENSOR_MAP_L2_PROMOTION_L2_128B
#define MW0 0
#define PFILL 0
#define H2W (NQ - 3)
#define TOPW 1000
#define PFT 0
#define SV0 2
#define SV0A 14
#define SV0B 22
#define ASTE 2
#define PFS 1
#define PFTAB 0x0012222220000ull
#define HW 0
#define DPF 1
#define PROBE 0x28
#define OS1 1
#define YW 0
#define OS2 3
#define NOVAL 0
#define NDIR 1
#define I0 (2 + NDIR)
#define DW 0
#define OSP 1
#define NA 5
#define STAG 4
#define GOE 0
#define SVP 99
#define KEY1 0
#define HYB 0
#define DV 0
#define DVJ 4
#define DVK 10
#define FW 0
#define E1E 0
#define GATE 0
#define SVD 0
#define XPROMO CU_TENSOR_MAP_L2_PROMOTION_L2_128B
#define MC0 3
#define MX 0
#define OUTV 1
#define BW0 2
#define QL 1
#define NP 0
#define FINCP 0
#define DNS 0
#define WOK 99
#define WOD1 2
#define SVT 64
#define MRED 1
#define MRW 0
#define H2D 400
#define MRD 0
#define STP 0
#define TPNS 50
#define DLP 0
#define MFIN 0
#define MFD 300
#define SF 1
#define PH MFIN
#define RSL 0
#define PFW 3000
#define KVE 1
#define P2NS 0
#define OS3 4
#define PLP 2
#define FINJ 9
#define PFD 0
#define PFG 3
#define PFNS2 150
#define PFNS 250
#define MAP 2
#define RSNS 60
#define SVS 6
#define PRODLATE 0
#define MC 7
#define QE 0
#define TMP 1
#define TMPW 4
#define DS 14
#define SH 0
#define VR 4
#define KEEP 1
#define KP 4
#define KC 1
#define MS 0
constexpr int CON_REGS = 224, MOE_REGS = 40, PROD_REGS = 24;
constexpr uint32_t SPIN_MAX = 2000000;
constexpr uint32_t SENT = 0xFFFFFFFFu;

struct __align__(128) Scratch {
  uint4 o[NCTA * 2048];
  uint4 part[NCTA * 544];
  uint4 fin[8 * 640];
  float2 stats[SEQ];
  uint32_t key[SEQ];
  uint32_t cs[3 * DM];
  uint4 y[NCTA * 128];
  uint32_t h[56 * 256];
  uint32_t top[128];
  uint32_t cnt[NCNT * 32];
};
__device__ Scratch G;
#define TLS(th, i)
#define TLG(i)
#define TLDUMP()

__device__ __forceinline__ bool elect_one() {
  uint32_t p;
  asm volatile("{\n.reg .pred P;\nelect.sync _|P, 0xffffffff;\nselp.b32 %0, 1, 0, P;\n}" : "=r"(p));
  return p;
}
__device__ __forceinline__ void mbar_init(uint32_t b, uint32_t c) { asm volatile("mbarrier.init.shared::cta.b64 [%0], %1;" ::"r"(b), "r"(c) : "memory"); }
__device__ __forceinline__ void mbar_expect_tx(uint32_t b, uint32_t bytes) { asm volatile("mbarrier.arrive.expect_tx.shared::cta.b64 _, [%0], %1;" ::"r"(b), "r"(bytes) : "memory"); }
__device__ __forceinline__ void mbar_arrive(uint32_t b) { asm volatile("mbarrier.arrive.shared::cta.b64 _, [%0];" ::"r"(b) : "memory"); }
__device__ __forceinline__ void mbar_wait_b(uint32_t b, uint32_t parity) {
  asm volatile(
      "{\n.reg .pred p;\n.reg .u32 cnt;\nmov.u32 cnt, 0;\n"
      "LW:\nmbarrier.try_wait.parity.shared::cta.b64 p, [%0], %1;\n@p bra LD;\n"
      "add.u32 cnt, cnt, 1;\nsetp.lt.u32 p, cnt, 4000000;\n@p bra LW;\ntrap;\nLD:\n}" ::"r"(b), "r"(parity) : "memory");
}
__device__ __forceinline__ void mbar_wait(uint32_t b, uint32_t parity) {
  asm volatile("{\n.reg .pred p;\nLW:\nmbarrier.try_wait.parity.shared::cta.b64 p, [%0], %1;\n@!p bra LW;\n}" ::"r"(b), "r"(parity) : "memory");
}
__device__ __forceinline__ bool mbar_test(uint32_t b, uint32_t parity) {
  uint32_t r;
  asm volatile("{\n.reg .pred p;\nmbarrier.test_wait.parity.shared::cta.b64 p, [%1], %2;\nselp.b32 %0, 1, 0, p;\n}" : "=r"(r) : "r"(b), "r"(parity) : "memory");
  return r;
}
__device__ __forceinline__ uint32_t ev_arrive(uint32_t a) { uint32_t r; asm volatile("atom.shared.add.u32 %0, [%1], 1;" : "=r"(r) : "r"(a) : "memory"); return r; }
__device__ __forceinline__ void tma2d(uint32_t dst, const CUtensorMap* m, int c0, int c1, uint32_t bar) {
  asm volatile("cp.async.bulk.tensor.2d.shared::cluster.global.mbarrier::complete_tx::bytes [%0], [%1, {%3, %4}], [%2];" ::"r"(dst), "l"(m), "r"(bar), "r"(c0), "r"(c1) : "memory");
}
__device__ __forceinline__ void tma3d(uint32_t dst, const CUtensorMap* m, int c1, int c2, uint32_t bar) {
  asm volatile("cp.async.bulk.tensor.3d.shared::cluster.global.mbarrier::complete_tx::bytes [%0], [%1, {%3, %4, %5}], [%2];" ::"r"(dst), "l"(m), "r"(bar), "r"(0), "r"(c1), "r"(c2) : "memory");
}
__device__ __forceinline__ void tma3d_mc(uint32_t dst, const CUtensorMap* m, int c1, int c2, uint32_t bar) {
  asm volatile("cp.async.bulk.tensor.3d.shared::cluster.global.mbarrier::complete_tx::bytes.multicast::cluster [%0], [%1, {%3, %4, %5}], [%2], %6;" ::"r"(dst), "l"(m), "r"(bar), "r"(0), "r"(c1), "r"(c2), "h"((uint16_t)3) : "memory");
}
__device__ __forceinline__ void tma5d(uint32_t dst, const CUtensorMap* m, int c2, int c4, uint32_t bar, bool mc) {
  if (mc) asm volatile("cp.async.bulk.tensor.5d.shared::cluster.global.mbarrier::complete_tx::bytes.multicast::cluster [%0], [%1, {%3, %3, %4, %3, %5}], [%2], %6;" ::"r"(dst), "l"(m), "r"(bar), "r"(0), "r"(c2), "r"(c4), "h"((uint16_t)3) : "memory");
  else asm volatile("cp.async.bulk.tensor.5d.shared::cluster.global.mbarrier::complete_tx::bytes [%0], [%1, {%3, %3, %4, %3, %5}], [%2];" ::"r"(dst), "l"(m), "r"(bar), "r"(0), "r"(c2), "r"(c4) : "memory");
}
__device__ __forceinline__ void mbar_arrive_cta(uint32_t b, uint32_t cta) {
  asm volatile("{\n.reg .b32 ra;\nmapa.shared::cluster.u32 ra, %0, %1;\nmbarrier.arrive.shared::cluster.b64 _, [ra];\n}" ::"r"(b), "r"(cta) : "memory");
}
constexpr uint64_t POL_FIRST = 0x12F0000000000000ull;
__device__ __forceinline__ void tma2d_ef(uint32_t dst, const CUtensorMap* m, int c0, int c1, uint32_t bar) {
  asm volatile("cp.async.bulk.tensor.2d.shared::cluster.global.mbarrier::complete_tx::bytes.L2::cache_hint [%0], [%1, {%3, %4}], [%2], %5;" ::"r"(dst), "l"(m), "r"(bar), "r"(c0), "r"(c1), "l"(POL_FIRST) : "memory");
}
__device__ __forceinline__ void bulk_ld(uint32_t dst, const void* src, uint32_t bytes, uint32_t bar) {
  asm volatile("cp.async.bulk.shared::cluster.global.mbarrier::complete_tx::bytes [%0], [%1], %2, [%3];" ::"r"(dst), "l"(src), "r"(bytes), "r"(bar) : "memory");
}
__device__ __forceinline__ void bulk_pf(const void* src, uint32_t bytes) { asm volatile("cp.async.bulk.prefetch.L2.global [%0], %1;" ::"l"(src), "r"(bytes) : "memory"); }
__device__ __forceinline__ void tma2d_pf(const CUtensorMap* m, int c0, int c1) {
  asm volatile("cp.async.bulk.prefetch.tensor.2d.L2.global [%0, {%1, %2}];" ::"l"(m), "r"(c0), "r"(c1) : "memory");
}
__device__ __forceinline__ void map_pf(const CUtensorMap* m) { asm volatile("prefetch.tensormap [%0];" ::"l"(m) : "memory"); }
__device__ __forceinline__ void line_pf(const void* p) { asm volatile("prefetch.global.L2 [%0];" ::"l"(p)); }
__device__ __forceinline__ void pf128(uint32_t dummy, const void* src) { asm volatile("cp.async.ca.shared.global.L2::128B [%0], [%1], 4;" ::"r"(dummy), "l"(src) : "memory"); }
__device__ __forceinline__ void pf256(uint32_t dummy, const void* src) { asm volatile("cp.async.ca.shared.global.L2::256B [%0], [%1], 4;" ::"r"(dummy), "l"(src) : "memory"); }
__device__ __forceinline__ void cp16x2(uint32_t dst, const void* src) {
  asm volatile("cp.async.cg.shared.global [%0], [%1], 16;\ncp.async.cg.shared.global [%0+4096], [%1+512], 16;" ::"r"(dst), "l"(src) : "memory");
}
constexpr uint32_t HI_SW128 = 0x40000000u | (1024 >> 4), HI_SW64 = 0x80000000u | (512 >> 4), HI_NOSW = 512 >> 4;
__device__ __forceinline__ uint64_t mkdesc(uint32_t lo, uint32_t hi) { uint64_t d; asm("mov.b64 %0, {%1, %2};" : "=l"(d) : "r"(lo), "r"(hi)); return d; }
__device__ __forceinline__ void wg_fence() { asm volatile("wgmma.fence.sync.aligned;" ::: "memory"); }
__device__ __forceinline__ void wg_commit() { asm volatile("wgmma.commit_group.sync.aligned;" ::: "memory"); }
template <int N> __device__ __forceinline__ void wg_wait() { asm volatile("wgmma.wait_group.sync.aligned %0;" ::"n"(N) : "memory"); }
template <int N> __device__ __forceinline__ void reg_fence(float (&a)[N]) {
#pragma unroll
  for (int i = 0; i < N; i++) asm volatile("" : "+f"(a[i])::"memory");
}
template <int ID, int N> __device__ __forceinline__ void bar_sync() { asm volatile("bar.sync %0, %1;" ::"n"(ID), "n"(N) : "memory"); }
__device__ __forceinline__ void fence_async_smem() { asm volatile("fence.proxy.async.shared::cta;" ::: "memory"); }
__device__ __forceinline__ void fence_async_gmem() { asm volatile("fence.proxy.async.global;" ::: "memory"); }
__device__ __forceinline__ uint32_t pack_bf16(float lo, float hi) { uint32_t r; asm("cvt.rn.bf16x2.f32 %0, %1, %2;" : "=r"(r) : "f"(hi), "f"(lo)); return r; }
__device__ __forceinline__ float bf_lo(uint32_t v) { return __uint_as_float(v << 16); }
__device__ __forceinline__ float bf_hi(uint32_t v) { return __uint_as_float(v & 0xFFFF0000u); }
__device__ __forceinline__ float bf_round(float v) { return bf_lo(pack_bf16(v, v)); }
__device__ __forceinline__ uint32_t bf_sub2(uint32_t a, uint32_t b) { uint32_t r; asm("sub.rn.bf16x2 %0, %1, %2;" : "=r"(r) : "r"(a), "r"(b)); return r; }
__device__ __forceinline__ float rcp(float v) { float r; asm("rcp.approx.ftz.f32 %0, %1;" : "=f"(r) : "f"(v)); return r; }
__device__ __forceinline__ float ex2(float v) { float r; asm("ex2.approx.ftz.f32 %0, %1;" : "=f"(r) : "f"(v)); return r; }
__device__ __forceinline__ float sigmoid(float v) { return rcp(1.f + ex2(v * -1.4426950408889634f)); }
__device__ __forceinline__ void stsm4(uint32_t a, uint32_t r0, uint32_t r1, uint32_t r2, uint32_t r3) {
  asm volatile("stmatrix.sync.aligned.m8n8.x4.shared.b16 [%0], {%1,%2,%3,%4};" ::"r"(a), "r"(r0), "r"(r1), "r"(r2), "r"(r3) : "memory");
}
__device__ __forceinline__ void stsm4t(uint32_t a, uint32_t r0, uint32_t r1, uint32_t r2, uint32_t r3) {
  asm volatile("stmatrix.sync.aligned.m8n8.x4.trans.shared.b16 [%0], {%1,%2,%3,%4};" ::"r"(a), "r"(r0), "r"(r1), "r"(r2), "r"(r3) : "memory");
}
__device__ __forceinline__ void ldsm4(uint32_t a, uint32_t& r0, uint32_t& r1, uint32_t& r2, uint32_t& r3) {
  asm volatile("ldmatrix.sync.aligned.m8n8.x4.shared.b16 {%0,%1,%2,%3}, [%4];" : "=r"(r0), "=r"(r1), "=r"(r2), "=r"(r3) : "r"(a) : "memory");
}
__device__ __forceinline__ uint32_t movmat(uint32_t a) { uint32_t d; asm volatile("movmatrix.sync.aligned.m8n8.trans.b16 %0, %1;" : "=r"(d) : "r"(a)); return d; }
__device__ __forceinline__ void sts_h(uint32_t a, float v) { asm volatile("st.shared.u16 [%0], %1;" ::"r"(a), "h"((uint16_t)pack_bf16(v, v)) : "memory"); }
__device__ __forceinline__ float2 lds_f2(uint32_t a) { float2 v; asm volatile("ld.shared.v2.f32 {%0,%1}, [%2];" : "=f"(v.x), "=f"(v.y) : "r"(a)); return v; }
__device__ __forceinline__ float lds_f(uint32_t a) { float v; asm volatile("ld.shared.f32 %0, [%1];" : "=f"(v) : "r"(a)); return v; }
__device__ __forceinline__ float4 lds_f4(uint32_t a) { float4 v; asm volatile("ld.shared.v4.f32 {%0,%1,%2,%3}, [%4];" : "=f"(v.x), "=f"(v.y), "=f"(v.z), "=f"(v.w) : "r"(a)); return v; }
__device__ __forceinline__ uint32_t lds_u(uint32_t a) { uint32_t v; asm volatile("ld.shared.u32 %0, [%1];" : "=r"(v) : "r"(a) : "memory"); return v; }
__device__ __forceinline__ uint4 lds_u4(uint32_t a) { uint4 v; asm volatile("ld.shared.v4.u32 {%0,%1,%2,%3}, [%4];" : "=r"(v.x), "=r"(v.y), "=r"(v.z), "=r"(v.w) : "r"(a) : "memory"); return v; }
__device__ __forceinline__ void sts_u(uint32_t a, uint32_t v) { asm volatile("st.shared.u32 [%0], %1;" ::"r"(a), "r"(v) : "memory"); }
__device__ __forceinline__ void sts_u4(uint32_t a, uint4 v) { asm volatile("st.shared.v4.u32 [%0], {%1,%2,%3,%4};" ::"r"(a), "r"(v.x), "r"(v.y), "r"(v.z), "r"(v.w) : "memory"); }
__device__ __forceinline__ uint4 ldx4(const void* p) { uint4 v; asm volatile("ld.relaxed.gpu.global.v4.u32 {%0,%1,%2,%3}, [%4];" : "=r"(v.x), "=r"(v.y), "=r"(v.z), "=r"(v.w) : "l"(p) : "memory"); return v; }
__device__ __forceinline__ uint2 ldx2(const void* p) { uint2 v; asm volatile("ld.relaxed.gpu.global.v2.u32 {%0,%1}, [%2];" : "=r"(v.x), "=r"(v.y) : "l"(p) : "memory"); return v; }
__device__ __forceinline__ uint32_t ldx1(const void* p) { uint32_t v; asm volatile("ld.relaxed.gpu.global.u32 %0, [%1];" : "=r"(v) : "l"(p) : "memory"); return v; }
__device__ __forceinline__ void stx4(void* p, uint32_t a, uint32_t b, uint32_t c, uint32_t d) { asm volatile("st.relaxed.gpu.global.v4.u32 [%0], {%1,%2,%3,%4};" ::"l"(p), "r"(a), "r"(b), "r"(c), "r"(d) : "memory"); }
__device__ __forceinline__ void stx2(void* p, uint32_t a, uint32_t b) { asm volatile("st.relaxed.gpu.global.v2.u32 [%0], {%1,%2};" ::"l"(p), "r"(a), "r"(b) : "memory"); }
__device__ __forceinline__ void stx1(void* p, uint32_t a) { asm volatile("st.relaxed.gpu.global.u32 [%0], %1;" ::"l"(p), "r"(a) : "memory"); }
__device__ __forceinline__ uint32_t umax4(uint4 v) { return max(max(v.x, v.y), max(v.z, v.w)); }
__device__ __forceinline__ uint32_t f2x(float f) { return min(__float_as_uint(f), 0xFFFFFFFEu); }
__device__ __forceinline__ void red4(float* p, float a, float b, float c, float d) { asm volatile("red.relaxed.gpu.global.add.v4.f32 [%0], {%1,%2,%3,%4};" ::"l"(p), "f"(a), "f"(b), "f"(c), "f"(d) : "memory"); }
__device__ __forceinline__ void cnt_arrive(int c) { asm volatile("red.release.gpu.global.add.u32 [%0], 1;" ::"l"(&G.cnt[c]) : "memory"); }
__device__ __forceinline__ void cnt_wait(int c, uint32_t target) {
#pragma unroll 1
  for (uint32_t it = 0; it < SPIN_MAX; it++) {
    uint32_t v;
    asm volatile("ld.acquire.gpu.global.u32 %0, [%1];" : "=r"(v) : "l"(&G.cnt[c]) : "memory");
    if (v >= target) break;
    __nanosleep(POLLNS);
  }
}
__device__ __forceinline__ void cnt_done() {
  uint32_t t;
  asm volatile("atom.acq_rel.gpu.global.add.u32 %0, [%1], 1;" : "=r"(t) : "l"(&G.cnt[C_DONE]) : "memory");
  if (t == NCTA + NSVC - 1) {
#pragma unroll 1
    for (int i = 0; i < NCNT; i++) G.cnt[i * 32] = 0;
  }
}
__device__ __forceinline__ float phi(float u, float rs, float rl) {
  float a = fmaf(u, rs, 1.000001f), e = ex2(u * rl), r;
  asm("add.sat.f32 %0, %1, 0f358637BD;" : "=f"(e) : "f"(e));
  asm("max.NaN.f32 %0, %1, %2;" : "=f"(r) : "f"(a), "f"(e));
  return r;
}

__device__ __forceinline__ int kstep1(int e, int hg) { return e < 14 ? (e < 2 * hg ? e : e + 2) : 2 * hg + e - 14; }
__device__ __forceinline__ int slab(int n, int hg) { return n + (((n + 7 - hg) * 37) >> 8); }
__host__ __device__ constexpr uint32_t d_off(int i) { return i < 3 ? 12 * SLOT + (NR == 4 ? i : (i == 2 ? 0 : i + 1)) * MT : (i < 5 ? S_D0 * SLOT + (i - 3) * 8192 : S_D1 * SLOT + (i - 5) * 8192); }
__host__ __device__ constexpr uint32_t h_off(int i) { return i < 3 ? 12 * SLOT + i * MT + 8192 : (i < 5 ? A_ONES + (i - 3) * 1024 : MISC + M_MOE + (i - 5) * 1024); }
__device__ __forceinline__ uint32_t m_off(int r) { return r < 3 ? 12 * SLOT + r * MT : 5 * SLOT; }
__device__ __forceinline__ int x_slot(int e, int s) { return NQ == 5 ? (e < 14 ? s : e - 11) : (e < 13 ? s : 3 + s); }
__device__ __forceinline__ uint32_t wo_slot(int i) { return (uint32_t)(WO_SLOTS >> (4 * i)) & 15u; }

__global__ void __launch_bounds__(512, 1)
fused_kernel(const __nv_bfloat16* __restrict__ x, const __nv_bfloat16* __restrict__ wqkv, const __nv_bfloat16* __restrict__ wo,
             const __nv_bfloat16* __restrict__ wr, const __nv_bfloat16* __restrict__ wd, const int by_sm,
             const __grid_constant__ CUtensorMap tmX, const __grid_constant__ CUtensorMap tmW,
             const __grid_constant__ CUtensorMap tmWo, const __grid_constant__ CUtensorMap tmOut,
             const __grid_constant__ CUtensorMap tmG, const __grid_constant__ CUtensorMap tmU,
             const __grid_constant__ CUtensorMap tmD, const __grid_constant__ CUtensorMap tmR,
             const __grid_constant__ CUtensorMap tmWp) {
  if (TMP && threadIdx.x == 32 * TMPW) { map_pf(&tmX); map_pf(&tmW); }
  extern __shared__ __align__(1024) uint8_t smem_raw[];
  const uint32_t sb = (uint32_t)__cvta_generic_to_shared(smem_raw);
  const uint32_t bars = sb + MISC + M_BAR;
  uint32_t smid;
  asm("mov.u32 %0, %%smid;" : "=r"(smid));
  const int tpc = smid >> 1;
  int cl = tpc + max(((tpc - 25) * 37) >> 8, 0);
  cl = tpc < 60 ? cl : cl - 1;
  cl = tpc < 62 ? cl : (tpc - 58) * 8;
  const int u = by_sm ? 2 * cl + (blockIdx.x & 1) : blockIdx.x;
  const int hg = (u >> 4) & 7, tb = u & 15;
  const int b = tb * 8 + hg;
  const int lane = threadIdx.x & 31;
  const int warp = __shfl_sync(~0u, threadIdx.x >> 5, 0);
  const int ltid = threadIdx.x;
  const int g = lane >> 2, t = lane & 3;
  const uint32_t d0 = (sb & 0x3FFFF) >> 4;
#define BAR(i) (bars + 8 * (i))
  TLS(0, 0);

  const int rank = u & 1;
  auto load_entry = [&](int e, int s) {
    const int k0 = kstep1(e, hg) * 64;
    mbar_expect_tx(BAR(B_FXQ + s), e < NF ? 2 * SLOT : SLOT);
    mbar_expect_tx(BAR(B_FKV + s), 2 * SLOT);
    tma2d(sb + x_slot(e, s) * SLOT, &tmX, k0, tb * 128, BAR(B_FXQ + s));
    if (e < MC0 || !(MC & 1)) {
      if (e < NF) tma3d(sb + (3 + s) * SLOT, &tmW, k0, 2 * hg, BAR(B_FXQ + s));
      tma3d(sb + (6 + 2 * s) * SLOT, &tmW, k0, 16 + 2 * hg, BAR(B_FKV + s));
      tma3d(sb + (7 + 2 * s) * SLOT, &tmW, k0, 32 + 2 * hg, BAR(B_FKV + s));
    } else {
      if (e < NF && (e & 1) == rank) tma3d_mc(sb + (3 + s) * SLOT, &tmW, k0, 2 * hg, BAR(B_FXQ + s));
      tma3d_mc(sb + (6 + 2 * s + rank) * SLOT, &tmW, k0, 16 + 16 * rank + 2 * hg, BAR(B_FKV + s));
    }
  };
  if (warp == FW && u < NCTA) {
    if (elect_one()) {
      mbar_init(BAR(B_FXQ), 1); mbar_init(BAR(B_FKV), 1);
      load_entry(0, 0);
      asm volatile("fence.mbarrier_init.release.cluster;" ::: "memory");
      TLS(FW * 32, 61);
    }
    __syncwarp();
  }
  if (u >= NCTA) {
    const int j = u - NCTA;
    if (warp == 8 && elect_one()) {
#pragma unroll
      for (int i = 0; i < 13; i++) mbar_init(BAR(i), 1);
    }
    if (ltid < 64) sts_u4(sb + MISC + ltid * 16, make_uint4(0x3F803F80u, 0x3F803F80u, 0x3F803F80u, 0x3F803F80u));
    fence_async_smem();
    __syncthreads();
    if (warp < 4) {
      int s = 0, p = 0;
#pragma unroll 1
      for (int pass = 0; pass < 3; pass++) {
        float acc[4][4];
#pragma unroll
        for (int c = 0; c < 4; c++) acc[c][0] = acc[c][1] = acc[c][2] = acc[c][3] = 0.f;
#pragma unroll 1
        for (int k = 0; k < 16; k++) {
          mbar_wait(BAR(s), p);
          wg_fence();
#pragma unroll
          for (int c = 0; c < 4; c++)
#pragma unroll
            for (int kk = 0; kk < 4; kk++)
              wgmma_ss_n8<1, 0>(acc[c], mkdesc((d0 + s * 2048 + c * 512 + kk * 128) | (512u << 16), HI_SW128), mkdesc((d0 + (MISC >> 4)) | (1u << 16), HI_SW128));
          wg_commit();
          wg_wait<0>();
          if (ltid == 0) mbar_arrive(BAR(6 + s));
          if (++s == SVS) { s = 0; p ^= 1; }
        }
        uint32_t* pc = G.cs + (pass < 2 ? DM + pass * DM : 0) + j * 256 + warp * 16 + g;
#pragma unroll
        for (int c = 0; c < 4; c++) {
          reg_fence(acc[c]);
          const uint32_t v = __float_as_uint((t & 1) ? acc[c][2] : acc[c][0]);
          if (t < 2) stx1(pc + c * 64 + t * 8, v ? v : 0x80000000u);
        }
        TLS(0, 1 + pass);
      }
    } else if (warp >= 8 && j == 0) {
      const int wq = warp - 8;
      const uint32_t top = sb + MISC + 1024;
#pragma unroll 1
      for (uint32_t it = 0; it < SPIN_MAX; it++) {
        const uint4 v0 = ldx4(G.key + wq * 256 + lane * 4), v1 = ldx4(G.key + wq * 256 + 128 + lane * 4);
        uint32_t ok;
        asm volatile("{\n.reg .pred p, q;\nsetp.ne.u32 p, %1, 0;\nbar.red.and.pred q, 2, 256, p;\nselp.b32 %0, 1, 0, q;\n}" : "=r"(ok) : "r"((v0.x & v0.y & v0.z & v0.w & v1.x & v1.y & v1.z & v1.w) >> 27) : "memory");
        ok = __any_sync(~0u, ok);
        if (!ok && it) continue;
        TLS(256, 4);
        uint32_t np = 0u - (1u << 28), mine = 0;
#pragma unroll 1
        for (int r = 0; r < 8; r++) {
          const uint32_t m0 = __viaddmax_u32(v0.x, np, v0.y + np), m1 = __viaddmax_u32(v0.z, np, v0.w + np), m2 = __viaddmax_u32(v1.x, np, v1.y + np), m3 = __viaddmax_u32(v1.z, np, v1.w + np);
          np -= __reduce_max_sync(~0u, max(max(m0, m1), max(m2, m3)));
          if (g == r) mine = 0u - np;
        }
        if (t == 0) sts_u(top + (wq * 8 + g) * 4, mine);
        bar_sync<2, 256>();
        TLS(256, 5);
        int rk = 0;
#pragma unroll
        for (int i = 0; i < 4; i++) {
          const uint4 o = lds_u4(top + t * 64 + i * 16);
          rk += (o.x > mine) + (o.y > mine) + (o.z > mine) + (o.w > mine);
        }
        rk += __shfl_xor_sync(~0u, rk, 1);
        rk += __shfl_xor_sync(~0u, rk, 2);
        if (ok) { if (rk < 8) stx1(G.top + t * 32 + rk, mine); break; }
        __nanosleep(2500);
      }
      TLS(256, 7);
    } else if (warp == 4) {
      int s = 0, p = 1;
      if (SVD) __nanosleep(SVD);
#pragma unroll 1
      for (int i = 0; i < 48; i++) {
        mbar_wait(BAR(6 + s), p);
        if (j == 0 && i >= SV0A && i < SV0B) mbar_wait(BAR(s >= SV0 ? s - SV0 : s - SV0 + SVS), s >= SV0 ? p ^ 1 : p);
        if (elect_one()) {
          mbar_expect_tx(BAR(s), 2 * SLOT);
          const int ch = (i < 32 ? 16 + (i & 16) : 0) + j * 4, k0 = (i & 15) * 64;
          tma3d(sb + s * 2 * SLOT, &tmW, k0, ch, BAR(s));
          tma3d(sb + s * 2 * SLOT + SLOT, &tmW, k0, ch + 2, BAR(s));
        }
        if (++s == SVS) { s = 0; p ^= 1; }
      }
    }
    if (ltid == 0) cnt_wait(C_DONE, NCTA);
    __syncthreads();
    const uint4 zero = make_uint4(0, 0, 0, 0);
    if (ltid < 128) reinterpret_cast<uint4*>(G.key)[j * 128 + ltid] = zero;
    else if (ltid < 320) reinterpret_cast<uint4*>(G.cs)[j * 192 + ltid - 128] = zero;
    else if (ltid < 322) reinterpret_cast<uint4*>(G.top)[j * 8 + ltid - 320] = zero;
    if (ltid == 0) { cnt_done(); TLDUMP(); }
    return;
  }

  if (warp == 12) {
    if (elect_one()) {
#pragma unroll
      for (int i = 1; i < 7; i++) if (i != B_FKV) mbar_init(BAR(i), 1);
      if (E1E) load_entry(1, 1);
      asm volatile("fence.mbarrier_init.release.cluster;" ::: "memory");
    }
  } else if (warp >= 13) {
    if (elect_one()) {
      if (warp == 15) {
#pragma unroll
        for (int i = B_FAUX; i < NBAR; i++) mbar_init(BAR(i), i < B_E || !MC ? 2 : 4);
        mbar_init(BAR(B_KV4), 4); mbar_init(BAR(B_MS), 2);
      } else {
#pragma unroll
        for (int i = 0; i < 23; i++) mbar_init(BAR((warp == 13 ? 7 : 30) + i), 1);
      }
      asm volatile("fence.mbarrier_init.release.cluster;" ::: "memory");
    }
  }
  __syncthreads();
  if (MC) asm volatile("barrier.cluster.arrive.relaxed.aligned;" ::: "memory");

  const bool unit = u < NUNIT;
  const int dcol = (u & 15) * 64, drow = (u >> 4) * 448;
  if (warp >= 12) {
    asm volatile("setmaxnreg.dec.sync.aligned.u32 %0;" ::"n"(PROD_REGS));
    if (MC && warp != 12) asm volatile("barrier.cluster.wait.aligned;" ::: "memory");
    if (warp == 12) {
      int s = 1 + E1E, p = 1, pn = 3;
#pragma unroll 1
      for (int e = 1 + E1E; e < 16; e++) {
        if (MC && e == MC0) asm volatile("barrier.cluster.wait.aligned;" ::: "memory");
        if (e == GATE) mbar_wait(BAR(B_FXQ), 0);
        mbar_wait(BAR(B_E + s), p);
        if (elect_one()) {
          load_entry(e, s);
          if (NR == 4 && e == 11) mbar_arrive(BAR(B_ME + 3));
          if (e == ASTE) {
            mbar_expect_tx(BAR(B_AST), 2 * SLOT + 2048);
            bulk_ld(sb + 12 * SLOT, x + (size_t)b * 16 * DM, 2 * SLOT, BAR(B_AST));
            bulk_ld(sb + MISC + M_MOE, wr, 2048, BAR(B_AST));
          } else if (e >= 3) {
            if (e < 6) bulk_pf(wqkv + (size_t)((e - 2) * 256 + 2 * b) * 3 * DM, 2 * 3 * DM * 2);
            if (e < 7) bulk_pf(wo + (size_t)((e - 3) * 256 + 2 * b) * DM, 2 * DM * 2);
            if (NUNIT) {
#pragma unroll 1
              for (int i = (PFTAB >> (4 * (e - 3))) & 15; i > 0; i--, pn++) {
                if (pn >= 16) { if (!(MX & 8)) tma2d_pf(&tmD, dcol, drow + (pn - 16) * 64); }
                else if (unit && !(MX & 2)) tma2d_pf(rank ? &tmU : &tmG, (u >> 1) * 64, pn * 64);
              }
            }
          }
        }
        if (++s == 3) { s = 0; p ^= 1; }
      }
#pragma unroll 1
      for (int k = 0; k < NQ; k++) {
        if (k == 0) mbar_wait(BAR(B_E + 1), 0);
        if (k == 2) mbar_wait(BAR(B_E + 2), 0);
        if (k == 3) mbar_wait(BAR(B_E + 0), 1);
        if (k == 4) mbar_wait(BAR(B_STG), 0);
        if (elect_one()) {
          const int k0 = kstep1(NF + k, hg) * 64;
          mbar_expect_tx(BAR(B_FQ + k), SLOT);
          if (!(MC & 2)) tma3d(sb + ((QW_SLOTS >> (4 * k)) & 15u) * SLOT, &tmW, k0, 2 * hg, BAR(B_FQ + k));
          else if ((k & 1) == rank) tma3d_mc(sb + ((QW_SLOTS >> (4 * k)) & 15u) * SLOT, &tmW, k0, 2 * hg, BAR(B_FQ + k));
        }
      }
#pragma unroll 1
      for (int i = 0; i < 16; i++) {
        mbar_wait(i < 7 ? BAR(B_EQ + ((i + WQ0) >> 1)) : (i < 9 ? BAR(B_DE) : BAR(B_EO + i - 9)), 0);
        if (i == WOK) mbar_wait(BAR(B_KVB), 0);
        mbar_wait(BAR(B_FWO + i - (i < WOK ? WOD1 : WOD)), 0);
        if (elect_one()) {
          mbar_expect_tx(BAR(B_FWO + i), SLOT);
#pragma unroll
          for (int hf = 0; hf < ((MC & 4) ? 1 : 2); hf++) {
            const int n = 2 * i + ((MC & 4) ? rank : hf), m = slab(n - 4, hg), hd = n < 4 ? 4 * hg + n : 4 * (m & 7) + (m >> 3);
            if (i < 2 + NDIR) tma5d(sb + wo_slot(i) * SLOT + (n & 1) * 8192, &tmWp, hd * 4, 2 * hg, BAR(B_FWO + i), MC & 4);
            else if (MC & 4) tma3d_mc(sb + wo_slot(i) * SLOT + rank * 8192, &tmWo, hd * 32, 2 * hg, BAR(B_FWO + i));
            else tma3d(sb + wo_slot(i) * SLOT + hf * 8192, &tmWo, hd * 32, 2 * hg, BAR(B_FWO + i));
          }
        }
      }
    } else if (warp == 13) {
      if (elect_one()) {
        map_pf(rank ? &tmU : &tmG); map_pf(&tmR); map_pf(&tmD); map_pf(&tmWo); map_pf(&tmWp); map_pf(&tmOut);
      }
      bar_sync<6, 64>();
      if (elect_one()) {
        cnt_wait(C_B, NCTA);
        fence_async_gmem();
        mbar_expect_tx(BAR(B_FAUX), 1024);
        bulk_ld(sb + A_ST, G.stats + tb * 128, 1024, BAR(B_FAUX));
      }
      __syncwarp();
      TLS(416, 68);
#pragma unroll 1
      for (int m = 1; m < 4; m++) {
        const int part = m == 3 ? 0 : m;
        uint4 c;
#pragma unroll 1
        for (uint32_t it = 0; it < SPIN_MAX; it++) {
          c = ldx4(G.cs + part * DM + hg * 128 + lane * 4);
          if (__all_sync(~0u, min(min(c.x, c.y), min(c.z, c.w)))) break;
          __nanosleep(POLLNS);
        }
        sts_u4(sb + A_CS + part * 512 + lane * 16, c);
        __syncwarp();
        if (m > 1 && lane == 0) mbar_arrive(BAR(m == 2 ? B_FAUX : B_CQ));
        TLS(416, 71 + m);
      }
      mbar_wait(BAR(B_XS), 1);
      if (elect_one()) asm volatile("red.relaxed.gpu.global.add.u32 [%0], 1;" ::"l"(&G.cnt[C_DONE]) : "memory");
    } else if (warp == 14) {
      const uint4 sent = make_uint4(SENT, SENT, SENT, SENT);
      uint4* ro = G.o + (tb * 32 + hg) * 512 + lane;
      uint4* rp = G.part + b * 544 + lane;
      if (RSL) bar_sync<5, 160>(); else mbar_wait(BAR(B_AST), 0);
#pragma unroll 1
      for (int i = RS0; i < 40; i++) {
        uint4* q = i < 32 ? ro + (i >> 3) * 4096 + (i & 7) * 64 : rp + (i - 32) * 64;
        q[0] = sent; q[32] = sent;
        __nanosleep(RSNS);
      }
      rp[512] = sent;
#pragma unroll
      for (int i = 0; i < 4; i++) G.y[u * 128 + i * 32 + lane] = sent;
      if (unit) reinterpret_cast<uint4*>(G.h)[u * 32 + lane] = sent;
      G.fin[hg * 640 + tb * 40 + lane] = sent;
      if (lane < 8) G.fin[hg * 640 + tb * 40 + 32 + lane] = sent;
      if (!RSL) bar_sync<5, 160>();
      __syncwarp();
      TLS(448, 67);
      if (lane == 0) cnt_arrive(C_B);
      __syncwarp();
      TLS(448, 32);
      asm volatile("bar.arrive 6, 64;" ::: "memory");
    } else {
      const uint32_t stg = sb + 12 * SLOT;
      auto load_a = [&](int n, int r) {
        mbar_expect_tx(BAR(B_MF + r), (MX & 2) ? 1024 : MT);
        if (!(MX & 2)) tma2d_ef(sb + m_off(r), rank ? &tmU : &tmG, (u >> 1) * 64, n * 64, BAR(B_MF + r));
      };
      mbar_wait(BAR(B_XS), 0);
      if (unit) {
#pragma unroll 1
        for (int i = 0; i < 3; i++) {
          if (elect_one()) load_a(i, i);
          __nanosleep(PFILL);
        }
      }
      uint32_t key;
#pragma unroll 1
      for (uint32_t it = 0; it < SPIN_MAX; it++) {
        key = ldx1(G.top + ((u >> 1) & 3) * 32 + (lane & 7));
        if (__all_sync(~0u, key)) break;
        __nanosleep(TPNS);
      }
      TLS(480, 66);
      if (lane < 8) sts_u(sb + MISC + M_IDX + lane * 4, key);
      __syncwarp();
      if (lane == 0) mbar_arrive(BAR(B_XS));
      if (unit) {
        int tok[8];
#pragma unroll
        for (int i = 0; i < 8; i++) tok[i] = ~__shfl_sync(~0u, key, i) & 2047;
        int r = 0, p = 0;
#pragma unroll 1
        for (int n = 0; n < 16; n++) {
          if (n >= 3) mbar_wait(BAR(B_ME + r), r == 3 ? p : p ^ 1);
          if (elect_one()) {
            if (n >= 3) load_a(n, r);
#pragma unroll
            for (int i = 0; i < 8; i++) tma2d(sb + m_off(r) + 8192 + i * 128, &tmR, n * 64, tok[i], BAR(B_MF + r));
          }
          if (++r == NR) { r = 0; p ^= 1; }
        }
      }
      if (NUNIT) {
        if (lane == 0) mbar_expect_tx(BAR(B_DF), (MX & 8) ? 0 : 7 * 8192);
#pragma unroll 1
        for (int i = 0; i < 7; i++) {
          if (NR == 4) {
            if (i >= 3) mbar_wait(i < 5 ? BAR(B_ME + 3) : BAR(B_STG), 0);
            else if (unit) mbar_wait(BAR(B_ME + i), 1);
          } else {
            if (i >= 3) mbar_wait(BAR(B_EQ + ((i - 3) >> 1)), 0);
            else if (unit) mbar_wait(BAR(B_ME + (i == 2 ? 0 : i + 1)), i == 2);
          }
          if (!(MX & 8) && elect_one()) tma2d_ef(sb + d_off(i), &tmD, dcol, drow + i * 64, BAR(B_DF));
          if (DNS) __nanosleep(DNS);
        }
      }
    }
    if (warp == 14) {
      if (DPF && NUNIT && !(MX & 8)) {
        mbar_wait(DS ? BAR(B_MS) : (DPF == 1 ? BAR(B_FQ) : BAR(B_T0)), 0);
#pragma unroll 1
        for (int pf = 0; pf < 7; pf++) { pf256(sb + MISC + M_DUM, wd + (size_t)(drow + pf * 64 + rank * 32 + lane) * DM + (dcol & ~127)); __nanosleep(PFNS2); }
      }
      const uint32_t* src = reinterpret_cast<const uint32_t*>(G.part + ((lane >> 3) * 32 + hg) * 544 + 512) + tb * 8 + (lane & 7);
      mbar_wait(BAR(B_EQ + MRW), 0);
      if (MRD) __nanosleep(MRD);
      uint32_t z0, z1, z2, z3;
#pragma unroll 1
      for (uint32_t it = 0; it < SPIN_MAX; it++) {
        z0 = ldx1(src); z1 = ldx1(src + 8 * 2176); z2 = ldx1(src + 16 * 2176); z3 = ldx1(src + 24 * 2176);
        if (!__any_sync(~0u, max(max(z0, z1), max(z2, z3)) == SENT)) break;
      }
      if (MRED == 2 && elect_one()) mbar_arrive(BAR(B_ZOK));
      float zz = (__uint_as_float(z0) + __uint_as_float(z1)) + (__uint_as_float(z2) + __uint_as_float(z3));
      zz += __shfl_xor_sync(~0u, zz, 8);
      zz += __shfl_xor_sync(~0u, zz, 16);
      stx1(reinterpret_cast<uint32_t*>(G.fin + hg * 640) + (tb >> 2) * 640 + 512 + ((tb >> 1) & 1) * 64 + (lane & 1) * 32 + (tb & 1) * 16 + ((lane & 7) >> 1) * 4 + (lane >> 3),
           pack_bf16(zz, zz));
      TLS(448, 12);
    }
    if (!MFIN && (warp == 13 || warp == 14)) {
      mbar_wait(BAR(B_EQ + H2W), 0);
      if (H2D) __nanosleep(H2D);
#pragma unroll 1
      for (uint32_t it = 0; it < SPIN_MAX; it++) {
        if (warp == 14 && elect_one()) { mbar_expect_tx(BAR(B_FIN), 10240); bulk_ld(sb + S_KVB * SLOT, G.fin + hg * 640, 10240, BAR(B_FIN)); }
        mbar_wait(BAR(B_FIN), it & 1);
        uint32_t m = 0;
#pragma unroll
        for (int i = 0; i < 10; i++) m = max(m, lds_u(sb + S_KVB * SLOT + (i * 64 + ltid - 416) * 16 + (g >> 1) * 4));
        uint32_t bad;
        asm volatile("{\n.reg .pred p, q;\nsetp.eq.u32 p, %1, 0xFFFFFFFF;\nbar.red.or.pred q, 7, 64, p;\nselp.b32 %0, 1, 0, q;\n}" : "=r"(bad) : "r"(m) : "memory");
        if (!__any_sync(~0u, bad)) break;
      }
      if (warp == 14 && elect_one()) mbar_arrive(BAR(B_KVB));
      TLS(448, 14);
    }
    if (PH && (warp == 13 || warp == 14)) {
      bar_sync<3, 192>();
      mbar_wait(BAR(B_STG), 0);
#pragma unroll 1
      for (uint32_t it = 0; NUNIT && it < SPIN_MAX; it++) {
        if (elect_one()) {
          const uint32_t* ph = G.h + (u >> 4) * 7 * 256;
          if (warp == 13) { mbar_expect_tx(BAR(B_HF), 7168); bulk_ld(sb + h_off(3), ph + 768, 2048, BAR(B_HF)); bulk_ld(sb + h_off(5), ph + 1280, 2048, BAR(B_HF)); }
          else { bulk_ld(sb + h_off(0), ph, 1024, BAR(B_HF)); bulk_ld(sb + h_off(1), ph + 256, 1024, BAR(B_HF)); bulk_ld(sb + h_off(2), ph + 512, 1024, BAR(B_HF)); }
        }
        mbar_wait(BAR(B_HF), it & 1);
        uint32_t m = 0;
#pragma unroll
        for (int i = 0; i < 7; i++) m = max(m, lds_u(sb + h_off(i) + (ltid - 416) * 16 + (g >> 1) * 4));
        uint32_t bad;
        asm volatile("{\n.reg .pred p, q;\nsetp.eq.u32 p, %1, 0xFFFFFFFF;\nbar.red.or.pred q, 7, 64, p;\nselp.b32 %0, 1, 0, q;\n}" : "=r"(bad) : "r"(m) : "memory");
        if (!__any_sync(~0u, bad)) break;
        __nanosleep(POLLNS);
      }
      if (warp == 14 && elect_one()) mbar_arrive(BAR(B_KVB));
    }
    __syncwarp();
    if (warp >= 13) {
      const char* og = reinterpret_cast<const char*>(G.o + tb * 16384);
      auto probe = [&](uint32_t m) {
        const char* p = og + m * 8192u + (lane & 15) * 512 + 496;
#pragma unroll 1
        for (uint32_t it = 0; it < SPIN_MAX; it++)
          if (!__any_sync(~0u, ldx1(p) == SENT)) break;
      };
      if (warp == 15) {
        int r = 0, p = 1;
        mbar_wait(BAR(B_EAUX), 0);
#pragma unroll 1
        for (int i = I0; i < 16; i++) {
          const uint32_t dst = sb + ((A_SLOTS >> (4 * r)) & 15u) * SLOT, m0 = slab(2 * i - 4, hg), m1 = slab(2 * i - 3, hg);
          if (i == I0 + 3) mbar_wait(BAR(B_DE), 0);
          mbar_wait(BAR(B_EA + r), p);
          if ((PROBE >> i) & 1) probe(lane < 16 ? m0 : m1);
          if (elect_one()) {
            mbar_expect_tx(BAR(B_AF + r), SLOT);
            bulk_ld(dst, og + m0 * 8192u, 8192, BAR(B_AF + r)); bulk_ld(dst + 8192, og + m1 * 8192u, 8192, BAR(B_AF + r));
          }
          if (++r == NA) { r = 0; p ^= 1; }
        }
      } else {
        const uint32_t lo = lane * 32 + g * 4, hb = sb + (warp - 13) * 8192;
        uint32_t ph = 0;
        int r = 0, p = 0;
#pragma unroll 1
        for (int i = I0; i < 16; i++) {
          const uint32_t mine = hb + ((A_SLOTS >> (4 * r)) & 15u) * SLOT;
          auto bad = [&]() {
            uint32_t v[8];
#pragma unroll
            for (int j = 0; j < 8; j++) v[j] = lds_u(mine + lo + j * 1024);
            return __any_sync(~0u, max(max(max(v[0], v[1]), max(v[2], v[3])), max(max(v[4], v[5]), max(v[6], v[7]))) == SENT);
          };
          mbar_wait(BAR(B_AF + r), p);
          if (!NOVAL && bad()) {
            const uint32_t m = slab(2 * i - 17 + warp, hg);
#pragma unroll 1
            for (uint32_t it = 0; it < 64; it++) {
              probe(m);
              if (elect_one()) { mbar_expect_tx(BAR(B_AR + warp - 13), 8192); bulk_ld(mine, og + m * 8192u, 8192, BAR(B_AR + warp - 13)); }
              mbar_wait(BAR(B_AR + warp - 13), ph);
              ph ^= 1;
              if (!bad()) break;
            }
          }
          if (elect_one()) mbar_arrive(BAR(B_VAL + r));
          if (++r == NA) { r = 0; p ^= 1; }
        }
      }
    }
  } else if (warp >= 8) {
    asm volatile("setmaxnreg.dec.sync.aligned.u32 %0;" ::"n"(MOE_REGS));
    if (MC) asm volatile("barrier.cluster.wait.aligned;" ::: "memory");
    const int aw = warp - 8;
    const uint32_t mbuf = sb + MISC + M_MOE, stg = sb + 12 * SLOT;
    mbar_wait(BAR(B_AST), 0);
    TLS(288, 64);
    {
      float v[16];
#pragma unroll
      for (int r = 0; r < 16; r++) v[r] = 0.f;
      const uint32_t base = stg + aw * 4 * 2048 + lane * 8;
#pragma unroll 1
      for (int c = 0; c < 8; c++) {
        const float2 w2 = lds_f2(mbuf + c * 256 + lane * 8);
        const float w[4] = {bf_lo(__float_as_uint(w2.x)), bf_hi(__float_as_uint(w2.x)), bf_lo(__float_as_uint(w2.y)), bf_hi(__float_as_uint(w2.y))};
        v[12] += (w[0] + w[1]) + (w[2] + w[3]);
#pragma unroll
        for (int r = 0; r < 4; r++) {
          const float2 x2 = lds_f2(base + r * 2048 + c * 256);
#pragma unroll
          for (int e = 0; e < 2; e++) {
            const uint32_t xx = __float_as_uint(e ? x2.y : x2.x);
            const float lo = bf_lo(xx), hi = bf_hi(xx);
            v[r] += lo; v[4 + r] = fmaf(lo, lo, v[4 + r]); v[8 + r] = fmaf(lo, w[2 * e], v[8 + r]);
            v[r] += hi; v[4 + r] = fmaf(hi, hi, v[4 + r]); v[8 + r] = fmaf(hi, w[2 * e + 1], v[8 + r]);
          }
        }
      }
#pragma unroll
      for (int l = 0; l < 4; l++) {
        const int n = 8 >> l;
        const bool up = lane & (2 * n);
#pragma unroll
        for (int r = 0; r < 8; r++) {
          if (r < n) { const float a = v[r], c = v[n + r]; v[r] = (up ? c : a) + __shfl_xor_sync(~0u, up ? a : c, 2 * n); }
        }
      }
      v[0] += __shfl_xor_sync(~0u, v[0], 1);
      const float sx = __shfl_sync(~0u, v[0], 2 * t), sq = __shfl_sync(~0u, v[0], 8 + 2 * t), sw = __shfl_sync(~0u, v[0], 16 + 2 * t), ws = __shfl_sync(~0u, v[0], 24);
      if (lane < 4) {
        const int row = b * 16 + aw * 4 + lane;
        const float mean = sx * (1.f / DM);
        const float var = fmaxf(fmaf(-mean, mean, sq * (1.f / DM)), 0.f);
        float sd;
        asm("sqrt.approx.ftz.f32 %0, %1;" : "=f"(sd) : "f"(bf_round(bf_round(var) + 1e-5f)));
        const float rstd = rcp(bf_round(sd));
        const float mb = bf_round(mean);
        uint32_t rb = pack_bf16(fmaf(-mb, ws, sw) * rstd, 0.f) & 0xFFFFu;
        rb = (rb & 0x8000u) ? (~rb & 0xFFFFu) : (rb | 0x8000u);
        const uint32_t key = (1u << 27) | (rb << 11) | (uint32_t)(2047 - row);
        if (KEY1) sts_u(sb + MISC + M_KEY + (aw * 4 + lane) * 4, key); else stx1(G.key + row, key);
        G.stats[row] = make_float2(mb, rstd);
      }
    }
    bar_sync<2, 128>();
    if (KEY1 && ltid < 272) stx1(G.key + b * 16 + lane, lds_u(sb + MISC + M_KEY + lane * 4));
    TLS(288, 65);
    sts_u4(sb + A_ONES + (ltid - 256) * 16, make_uint4(0x3F803F80u, 0x3F803F80u, 0x3F803F80u, 0x3F803F80u));
    fence_async_smem();
    asm volatile("bar.arrive 5, 160;" ::: "memory");
    if (ltid == 256) { if (unit && rank == 0) mbar_expect_tx(BAR(B_UP), 2048); mbar_arrive(BAR(B_XS)); }
    bar_sync<2, 128>();
    mbar_wait(BAR(B_XS), 1);
    TLS(288, 70);
    if (NUNIT) {
      if (unit) {
        int r = 0, p = 0;
        uint32_t rel = 0;
        float acc[8];
        uint2 s0, s1;
#pragma unroll
        for (int i = 0; i < 8; i++) acc[i] = 0.f;
        if (MS == 16) mbar_wait(BAR(B_T0), 0); else if (MS) mbar_wait(BAR(B_MS), 0);
#pragma unroll 1
        for (int n = 0; n < 16; n++) {
          if (n == 15) {
            mbar_wait(BAR(B_FAUX), 0);
            s0 = ldx2(G.stats + (~lds_u(sb + MISC + M_IDX + t * 8) & 2047)); s1 = ldx2(G.stats + (~lds_u(sb + MISC + M_IDX + t * 8 + 4) & 2047));
          }
          mbar_wait(BAR(B_MF + r), p);
          if (!(n & 3)) TLS(288, 56 + (n >> 2));
          const uint32_t mo = m_off(r) >> 4, da = (d0 + mo) | (512u << 16), db = (d0 + mo + 512) | (1u << 16);
          const uint32_t hb = 0x40000000u | ((A_ONES >> 4) - 512 - mo);
          wg_fence();
#pragma unroll
          for (int kk = 0; kk < ((MX & 1) ? 1 : 4); kk++) wgmma_ss_n16<1, 0>(acc, mkdesc(da + kk * 128, HI_SW128), mkdesc(db + kk * 2, hb));
          wg_commit();
          wg_wait<1>();
          if (n > 0 && !rel && ltid == 256) mbar_arrive(BAR(B_ME + (r == 0 ? NR - 1 : r - 1)));
          rel = 0;
          const int r0 = r;
          if (++r == NR) { r = 0; p ^= 1; }
        }
        wg_wait<0>();
        reg_fence(acc);
        {
          if (!MW0 && !rel && ltid == 256) mbar_arrive(BAR(B_ME + 15 % NR));
          TLS(288, 71);
          const float v0 = bf_round(fmaf(-__uint_as_float(s0.x), acc[4], acc[0]) * __uint_as_float(s0.y));
          const float v1 = bf_round(fmaf(-__uint_as_float(s1.x), acc[4], acc[1]) * __uint_as_float(s1.y));
          const float v2 = bf_round(fmaf(-__uint_as_float(s0.x), acc[6], acc[2]) * __uint_as_float(s0.y));
          const float v3 = bf_round(fmaf(-__uint_as_float(s1.x), acc[6], acc[3]) * __uint_as_float(s1.y));
          if (rank) {
            asm volatile("{\n.reg .b32 ra, rb;\nmapa.shared::cluster.u32 ra, %0, 0;\nmapa.shared::cluster.u32 rb, %1, 0;\n"
                         "st.async.weak.shared::cluster.mbarrier::complete_tx::bytes.v4.f32 [ra], {%2, %3, %4, %5}, [rb];\n}"
                         ::"r"(mbuf + (ltid - 256) * 16), "r"(BAR(B_UP)), "f"(v0), "f"(v1), "f"(v2), "f"(v3) : "memory");
          } else {
            const float g0 = bf_round(v0 * sigmoid(v0)), g1 = bf_round(v1 * sigmoid(v1)), g2 = bf_round(v2 * sigmoid(v2)), g3 = bf_round(v3 * sigmoid(v3));
            mbar_wait(BAR(B_UP), 0);
            const uint4 uu = lds_u4(mbuf + (ltid - 256) * 16);
            const uint32_t h0 = movmat(pack_bf16(g0 * __uint_as_float(uu.x), g1 * __uint_as_float(uu.y)));
            const uint32_t h1 = movmat(pack_bf16(g2 * __uint_as_float(uu.z), g3 * __uint_as_float(uu.w)));
            uint32_t* ph = G.h + (u >> 1) * 256 + g * 32 + t;
            stx1(ph + ((2 * aw) ^ g) * 4, h0); stx1(ph + ((2 * aw + 1) ^ g) * 4, h1);
          }
          TLS(288, 60);
        }
      }
    }
    if (PH) asm volatile("bar.arrive 3, 192;" ::: "memory");
    {
      const int wd_ = ltid & 63;
      const uint32_t* src = reinterpret_cast<const uint32_t*>(G.part + hg * 544 + (aw >> 1) * 256 + tb * 16) + wd_;
      mbar_wait(MRED == 2 ? BAR(B_ZOK) : BAR(B_EQ + MRW), 0);
      if (MRD) __nanosleep(MRD);
      TLS(256, 48);
      uint32_t v[16];
#pragma unroll 1
      for (uint32_t it = 0; it < SPIN_MAX; it++) {
        uint32_t m = 0;
#pragma unroll
        for (int i = 0; i < 16; i++) v[i] = ldx1(src + i * 8 * 2176);
#pragma unroll
        for (int i = 0; i < 16; i++) m = max(m, v[i]);
        if (!__any_sync(~0u, m == SENT)) break;
      }
      TLS(256, 55);
      float lo[4], hi[4];
#pragma unroll
      for (int i = 0; i < 4; i++) {
        lo[i] = (bf_lo(v[4 * i]) + bf_lo(v[4 * i + 1])) + (bf_lo(v[4 * i + 2]) + bf_lo(v[4 * i + 3]));
        hi[i] = (bf_hi(v[4 * i]) + bf_hi(v[4 * i + 1])) + (bf_hi(v[4 * i + 2]) + bf_hi(v[4 * i + 3]));
      }
      stx1(reinterpret_cast<uint32_t*>(G.fin + hg * 640) + (tb >> 2) * 640 + ((tb >> 1) & 1) * 64 + (tb & 1) * 16 + (aw >> 1) * 32 + ((wd_ >> 2) & 3) * 128 + (wd_ >> 4) * 4 + (wd_ & 3),
           pack_bf16((lo[0] + lo[1]) + (lo[2] + lo[3]), (hi[0] + hi[1]) + (hi[2] + hi[3])));
      TLS(256, 5);
    }
    if (NUNIT) {
      mbar_wait(BAR(B_STG), 0);
      bar_sync<2, 128>();
      if (HW) __nanosleep(HW);
#pragma unroll 1
      for (uint32_t it = 0; it < SPIN_MAX; it++) {
        if (elect_one()) {
          const uint32_t* ph = G.h + (u >> 4) * 7 * 256;
          if (aw == 3) { mbar_expect_tx(BAR(B_HF), 7168); bulk_ld(sb + h_off(3), ph + 768, 2048, BAR(B_HF)); bulk_ld(sb + h_off(5), ph + 1280, 2048, BAR(B_HF)); }
          else bulk_ld(stg + aw * MT + 8192, ph + aw * 256, 1024, BAR(B_HF));
        }
        mbar_wait(BAR(B_HF), it & 1);
        const uint32_t o = (ltid & 63) * 16 + (g >> 1) * 4, o2 = o + (aw >> 1) * 1024;
        const uint32_t m = max(max(lds_u(sb + h_off(0) + (aw >> 1) * MT + o), lds_u(sb + h_off(2) + o)), max(lds_u(sb + h_off(3) + o2), lds_u(sb + h_off(5) + o2)));
        uint32_t bad;
        asm volatile("{\n.reg .pred p, q;\nsetp.eq.u32 p, %1, 0xFFFFFFFF;\nbar.red.or.pred q, 2, 128, p;\nselp.b32 %0, 1, 0, q;\n}" : "=r"(bad) : "r"(m) : "memory");
        if (!__any_sync(~0u, bad)) break;
        __nanosleep(POLLNS);
      }
      TLS(288, 62);
      float acc[4] = {0.f, 0.f, 0.f, 0.f};
      mbar_wait(BAR(B_DF), 0);
      TLS(288, 63);
#pragma unroll 1
      for (int i = 0; i < 7; i++) {
        const uint32_t da = (d0 + (d_off(i) >> 4)) | (512u << 16), db = (d0 + (h_off(i) >> 4)) | (1u << 16);
        wg_fence();
#pragma unroll
        for (int kk = 0; kk < ((MX & 4) ? 1 : 4); kk++) wgmma_ss_n8<1, 0>(acc, mkdesc(da + kk * 128, HI_SW128), mkdesc(db + kk * 2, HI_SW128));
        wg_commit();
      }
      wg_wait<0>();
      reg_fence(acc);
      if (ltid < 258) { if (MC) mbar_arrive_cta(BAR(B_DE), ltid & 1); else mbar_arrive(BAR(B_DE)); }
      {
        uint32_t* py = reinterpret_cast<uint32_t*>(G.y) + u * 512 + t * 128 + aw * 16 + g;
        stx1(py, f2x(acc[0])); stx1(py + 64, f2x(acc[1])); stx1(py + 8, f2x(acc[2])); stx1(py + 72, f2x(acc[3]));
      }
      TLS(288, 69);
      const uint32_t key = lds_u(sb + MISC + M_IDX + (lane & 7) * 4);
      uint32_t rb = (key >> 11) & 0xFFFFu;
      rb = (rb & 0x8000u) ? (rb & 0x7FFFu) : (~rb & 0xFFFFu);
      const float sg = bf_round(sigmoid(__uint_as_float(rb << 16)));
      uint32_t hits = __ballot_sync(~0u, ((~key >> 7) & 15) == tb) & 255u;
      const uint32_t* py = reinterpret_cast<const uint32_t*>(G.y) + (2 * hg + (aw >> 1)) * 512 + (ltid & 63);
      if (hits) {
        sts_u4(mbuf + (ltid - 256) * 16, make_uint4(0, 0, 0, 0));
        bar_sync<2, 128>();
        if (YW >= 0) mbar_wait(BAR(B_EO + YW), 0); else if (YW == -2) mbar_wait(BAR(B_EAUX), 0);
      }
#pragma unroll 1
      while (hits) {
        const int n0 = __ffs(hits) - 1;
        hits &= hits - 1;
        const int n1 = hits ? __ffs(hits) - 1 : n0;
        hits &= hits - 1;
        uint32_t v[16];
#pragma unroll 1
        for (uint32_t it = 0; it < SPIN_MAX; it++) {
          uint32_t m = 0;
#pragma unroll
          for (int i = 0; i < 8; i++) { v[i] = ldx1(py + n0 * 64 + i * 8192); v[8 + i] = ldx1(py + n1 * 64 + i * 8192); }
#pragma unroll
          for (int i = 0; i < 16; i++) m = max(m, v[i]);
          if (!__any_sync(~0u, m == SENT)) break;
          __nanosleep(POLLNS);
        }
#pragma unroll
        for (int e = 0; e < 2; e++) {
          const uint32_t* w8 = v + 8 * e;
          const float y = ((__uint_as_float(w8[0]) + __uint_as_float(w8[1])) + (__uint_as_float(w8[2]) + __uint_as_float(w8[3]))) +
                          ((__uint_as_float(w8[4]) + __uint_as_float(w8[5])) + (__uint_as_float(w8[6]) + __uint_as_float(w8[7])));
          const int n = e ? n1 : n0;
          sts_h(mbuf + (aw >> 1) * 1024 + n * 128 + ((((ltid >> 3) & 7) ^ n) << 4) + (lane & 7) * 2, bf_round(y) * __shfl_sync(~0u, sg, n));
        }
      }
    }
    if (!NUNIT && ltid < 258) mbar_arrive(BAR(B_DE));
    fence_async_smem();
    bar_sync<2, 128>();
    TLS(288, 33);
    if (ltid == 288) mbar_arrive(BAR(B_MOE));
  } else {
    asm volatile("setmaxnreg.inc.sync.aligned.u32 %0;" ::"n"(CON_REGS));
    if (MC) asm volatile("barrier.cluster.wait.aligned;" ::: "memory");
    const int w = warp >> 2, wq = warp & 3, tid = ltid;
    const bool lead = (tid & 127) == 0;
    const uint32_t dA = (d0 + w * 512) | (1u << 16);
    const uint32_t dB = d0 | (512u << 16);
    auto release = [&](int bar) { if (lead) mbar_arrive(BAR(bar)); };
    auto release2 = [&](int bar) {
      if (MC) { if ((tid & 127) < 2) mbar_arrive_cta(BAR(bar), tid & 1); } else release(bar);
    };
    float aq[64], ak[64], av[64];
#pragma unroll
    for (int i = 0; i < 64; i++) aq[i] = ak[i] = av[i] = 0.f;
    auto q_step = [&](uint32_t bar, int p, uint32_t xs, uint32_t qs) {
      mbar_wait_b(bar, p);
      wg_fence();
#pragma unroll
      for (int kk = 0; kk < 4; kk++)
        wgmma_ss_n128<0, 1>(aq, mkdesc(dA + xs * 1024 + kk * 2, HI_SW128), mkdesc(dB + qs * 1024 + kk * 128, HI_SW128));
      wg_commit();
    };
    const uint32_t dT = dB + w * 512, dX = d0 | (1u << 16);
    auto t_step = [&](float (&a)[64], uint32_t ws, uint32_t xs) {
      wg_fence();
#pragma unroll
      for (int kk = 0; kk < 4; kk++)
        wgmma_ss_n128<1, 0>(a, mkdesc(dT + ws * 1024 + kk * 128, HI_SW128), mkdesc(dX + xs * 1024 + kk * 2, HI_SW128));
      wg_commit();
    };
    {
      int s = 0, p = 0, sp = 2;
#pragma unroll 1
      for (int e = 0; e < NF; e++) {
        TLS(0, 16 + e);
        if (((MS && MS < NF) || (DS && DS < NF)) && e == (MS ? MS : DS)) release(B_MS);
        q_step(BAR(B_FXQ + s), p, s, 3 + s);
        wg_wait<1>();
        if (e > 0) release2(B_E + sp);
        mbar_wait(BAR(B_FKV + s), p);
        t_step(ak, 6 + 2 * s, s); t_step(av, 7 + 2 * s, s);
        sp = s;
        if (++s == 3) { s = 0; p ^= 1; }
      }
#pragma unroll 1
      for (int e = NF; e < 16; e++) {
        TLS(0, 16 + e);
        if (((MS >= NF && MS < 16) || DS >= NF) && e == (MS ? MS : DS)) release(B_MS);
        mbar_wait(BAR(B_FXQ + s), p);
        mbar_wait(BAR(B_FKV + s), p);
        t_step(ak, 6 + 2 * s, x_slot(e, s));
        wg_wait<1>();
        release2(B_E + sp);
        t_step(av, 7 + 2 * s, x_slot(e, s));
        sp = s;
        if (++s == 3) { s = 0; p ^= 1; }
      }
    }
    const uint32_t aux = sb;
    mbar_wait(BAR(B_FAUX), 0);
    const int row0 = w * 64 + wq * 16 + g;
    const float ck0 = lds_f(aux + A_CS + 512 + row0 * 4), ck1 = lds_f(aux + A_CS + 512 + (row0 + 8) * 4);
    const float cv0 = lds_f(aux + A_CS + 1024 + row0 * 4), cv1 = lds_f(aux + A_CS + 1024 + (row0 + 8) * 4);
    const uint32_t moff = (uint32_t)(w * 64 + wq * 16 + (lane & 15)) * 128 + (((lane >> 4) ^ (lane & 7)) << 4);
    const uint32_t sta = aux + A_ST + t * 16;
    float kvp[36];
    uint32_t xr[32];
    {
      uint32_t pa[32];
      float4 st[16];
      auto ld = [&](int j) { st[j] = lds_f4(sta + j * 64); };
      auto k_blk = [&](int c) {
#pragma unroll
        for (int i = 0; i < 2; i++) {
          const float4 u = st[2 * c + i];
          const float l0 = u.y * 1.4426950408889634f, l1 = u.w * 1.4426950408889634f;
          const float* a = ak + 8 * c + 4 * i;
          pa[4 * c + 2 * i] = pack_bf16(phi(fmaf(-u.x, ck0, a[0]), u.y, l0), phi(fmaf(-u.z, ck0, a[1]), u.w, l1));
          pa[4 * c + 2 * i + 1] = pack_bf16(phi(fmaf(-u.x, ck1, a[2]), u.y, l0), phi(fmaf(-u.z, ck1, a[3]), u.w, l1));
        }
      };
      const uint32_t voff = sb + w * 8192 + (uint32_t)(8 * (lane >> 4) + (lane & 7)) * 128 + (((2 * wq + ((lane >> 3) & 1)) ^ (lane & 7)) << 4);
      auto v_blk = [&](int c) {
        uint32_t r[4];
#pragma unroll
        for (int i = 0; i < 2; i++) {
          const float4 u = st[2 * c + i];
          const float* a = av + 8 * c + 4 * i;
          r[2 * i] = pack_bf16(fmaf(-u.x, cv0, a[0]) * u.y, fmaf(-u.z, cv0, a[1]) * u.w);
          r[2 * i + 1] = pack_bf16(fmaf(-u.x, cv1, a[2]) * u.y, fmaf(-u.z, cv1, a[3]) * u.w);
        }
        stsm4t(voff + (c < 4 ? S_V0 : S_V1) * SLOT + (c & 3) * 2048, r[0], r[1], r[2], r[3]);
      };
      auto kv_mma = [&](int c) {
        const uint32_t bo = (c < 4 ? S_V0 : S_V1) * 1024 + w * 512 + (c & 3) * 128;
        const uint64_t bb = mkdesc((d0 + bo) | (((A_ONES >> 4) - bo) << 16), HI_SW128);
        if (c == (SH ? 8 - SH : 0)) wgmma_rz_n72<1>(kvp, pa[4 * c], pa[4 * c + 1], pa[4 * c + 2], pa[4 * c + 3], bb);
        else wgmma_rs_n72<1>(kvp, pa[4 * c], pa[4 * c + 1], pa[4 * c + 2], pa[4 * c + 3], bb);
      };
      ld(0); ld(1);
      if (SH) {
        wg_wait<1>();
        reg_fence(ak);
        TLS(0, 2);
        if (SH == 2) k_blk(6);
        k_blk(7);
        ld(0); ld(1);
      }
      wg_wait<0>();
      if (!SH) { reg_fence(ak); TLS(0, 2); }
      reg_fence(av);
      release2(B_E);
      release(B_T0);
      TLS(0, 3);
      ld(2); ld(3); v_blk(0); ld(4); ld(5); v_blk(1); k_blk(0);
      ld(6); ld(7); v_blk(2); ld(8); ld(9); v_blk(3); k_blk(1);
      ld(10); ld(11); v_blk(4); ld(12); ld(13); v_blk(5); k_blk(2);
      ld(14); ld(15); v_blk(6); v_blk(7); k_blk(3);
      fence_async_smem();
      asm volatile("bar.sync %0, 128;" ::"r"(3 + w) : "memory");
      wg_fence();
      if (SH == 2) kv_mma(6);
      if (SH) kv_mma(7);
      kv_mma(0); kv_mma(1); kv_mma(2); kv_mma(3);
      wg_commit();
#pragma unroll
      for (int c = 4; c < 8 - SH; c++) {
        k_blk(c);
        if (KC == 1 || (c & 1) || c == 7 - SH) {
          wg_fence();
          if (KC != 1 && (c & 1)) kv_mma(c - 1);
          kv_mma(c);
          wg_commit();
        }
      }
#pragma unroll
      for (int j = 0; j < 16; j += 2) ldsm4(sb + (j < 8 ? SX14 : SX15) * SLOT + (moff ^ ((j & 7) << 4)), xr[2 * j], xr[2 * j + 1], xr[2 * j + 2], xr[2 * j + 3]);
      if (QE) { q_step(BAR(B_FQ), 0, SXQ0, QW_SLOTS & 15u); wg_wait<1>(); } else wg_wait<0>();
      reg_fence(kvp);
      auto hand_back = [&]() { release2(B_STG); __syncwarp(); };
      if (!SF) hand_back();
      TLS(0, 4);
      uint4* pp = G.part + b * 544;
      uint32_t pk[8];
#pragma unroll
      for (int j = 0; j < 8; j++) pk[j] = wq >= 2 ? pack_bf16(kvp[16 + 2 * j], kvp[17 + 2 * j]) : pack_bf16(kvp[2 * j], kvp[2 * j + 1]);
      stx4(pp + tid, pk[0], pk[2], pk[4], pk[6]);
      stx4(pp + 256 + tid, pk[1], pk[3], pk[5], pk[7]);
      if (t == 0) stx2(reinterpret_cast<uint2*>(pp + 512) + (tid >> 2), f2x(kvp[32]), f2x(kvp[34]));
      if (SF == 1) hand_back();
      if (!QE) q_step(BAR(B_FQ), 0, SXQ0, QW_SLOTS & 15u);
      if (SF == 2) hand_back();
      const int wd_ = wq * 16 + (lane & 15);
      const uint32_t* src = reinterpret_cast<const uint32_t*>(G.part + ((lane >> 4) * 64 + hg) * 544 + w * 256 + tb * 16) + wd_;
      uint32_t* fin = reinterpret_cast<uint32_t*>(G.fin + hg * 640) + (tb >> 2) * 640 + ((tb >> 1) & 1) * 64 + (tb & 1) * 16 + w * 32 + ((wd_ >> 2) & 3) * 128 + wq * 4 + (wd_ & 3);
      uint32_t v[8];
      auto part_load = [&]() {
#pragma unroll
        for (int i = 0; i < 8; i++) v[i] = ldx1(src + i * 8 * 2176);
      };
#pragma unroll
      for (int k = 1; k < NQ; k++) {
        q_step(BAR(B_FQ + k), 0, (QX_SLOTS >> (4 * k)) & 15u, (QW_SLOTS >> (4 * k)) & 15u);
        TLS(0, 48 + k);
        if (!MRED && k == PLP) part_load();
        if (!MRED && k == PLC) {
#pragma unroll 1
          for (uint32_t it = 0; it < SPIN_MAX; it++) {
            if (!__any_sync(~0u, max(max(max(v[0], v[1]), max(v[2], v[3])), max(max(v[4], v[5]), max(v[6], v[7]))) == SENT)) break;
            part_load();
          }
          float lo = ((bf_lo(v[0]) + bf_lo(v[1])) + (bf_lo(v[2]) + bf_lo(v[3]))) + ((bf_lo(v[4]) + bf_lo(v[5])) + (bf_lo(v[6]) + bf_lo(v[7])));
          float hi = ((bf_hi(v[0]) + bf_hi(v[1])) + (bf_hi(v[2]) + bf_hi(v[3]))) + ((bf_hi(v[4]) + bf_hi(v[5])) + (bf_hi(v[6]) + bf_hi(v[7])));
          lo += __shfl_xor_sync(~0u, lo, 16); hi += __shfl_xor_sync(~0u, hi, 16);
          if (lane < 16) stx1(fin, pack_bf16(lo, hi));
          TLS(0, 5);
        }
        wg_wait<1>();
        release2(B_EQ + k - 1);
      }
      TLS(0, 13);
      mbar_wait(BAR(B_CQ), 0);
    }
    wg_wait<0>();
    reg_fence(aq);
    TLS(0, 15);
    const float2 st0 = lds_f2(aux + A_ST + row0 * 8), st1 = lds_f2(aux + A_ST + (row0 + 8) * 8);
    const float nm0 = -st0.x, nm1 = -st1.x, rs0 = st0.y, rs1 = st1.y;
    const float rl0 = rs0 * 1.4426950408889634f, rl1 = rs1 * 1.4426950408889634f;
    uint32_t pq[32];
#pragma unroll
    for (int j = 0; j < 16; j++) {
      const float2 c = lds_f2(aux + A_CS + (j * 8 + 2 * t) * 4);
      const float* a = aq + 4 * j;
      pq[2 * j] = pack_bf16(phi(fmaf(nm0, c.x, a[0]), rs0, rl0), phi(fmaf(nm0, c.y, a[1]), rs0, rl0));
      pq[2 * j + 1] = pack_bf16(phi(fmaf(nm1, c.x, a[2]), rs1, rl1), phi(fmaf(nm1, c.y, a[3]), rs1, rl1));
    }
    TLS(0, 6);
    mbar_wait_b(BAR(MFIN ? B_KV4 : B_KVB), 0);
    TLS(0, 7);
    uint32_t of[32];
    float ao[64];
    uint4* mine = G.o + (tb * 32 + hg) * 512 + warp * 64 + g * 4 + (t ^ (g >> 1));
    const uint32_t dW = d0 | (256u << 16);
    auto o_store = [&](int h) {
#pragma unroll
      for (int c = 0; c < 2; c++) stx4(mine + h * 4096 + c * 32, of[8 * h + c], of[8 * h + 2 + c], of[8 * h + 4 + c], of[8 * h + 6 + c]);
    };
    auto out_step = [&](uint32_t slot, const uint32_t* a) {
      const uint32_t d = dW + slot * 1024;
      wg_fence();
#pragma unroll
      for (int kk = 0; kk < 4; kk++) wgmma_rs_n128<1>(ao, a[4 * kk], a[4 * kk + 1], a[4 * kk + 2], a[4 * kk + 3], mkdesc(d + (kk >> 1) * 512 + (kk & 1) * 128, HI_SW128));
      wg_commit();
    };
    {
      float oa[4][20];
      const uint32_t dK = (d0 + S_KVB * 1024) | (8u << 16);
      wg_fence();
#pragma unroll
      for (int h = 0; h < 4; h++) {
        wgmma_rz_n40<1>(oa[h], pq[8 * h], pq[8 * h + 1], pq[8 * h + 2], pq[8 * h + 3], mkdesc(dK + h * 160, HI_NOSW));
        wgmma_rs_n40<1>(oa[h], pq[8 * h + 4], pq[8 * h + 5], pq[8 * h + 6], pq[8 * h + 7], mkdesc(dK + h * 160 + 16, HI_NOSW));
        if (h == 0 || h == 3) wg_commit();
      }
      auto norm = [&](int h) {
        const float r0 = rcp(oa[h][16] + 1e-6f), r1 = rcp(oa[h][18] + 1e-6f);
#pragma unroll
        for (int j = 0; j < 4; j++) {
          of[8 * h + 2 * j] = pack_bf16(oa[h][4 * j] * r0, oa[h][4 * j + 1] * r0);
          of[8 * h + 2 * j + 1] = pack_bf16(oa[h][4 * j + 2] * r1, oa[h][4 * j + 3] * r1);
        }
      };
      wg_wait<1>();
      reg_fence(oa[0]);
      norm(0);
      o_store(0);
      TLS(0, 8);
      auto resid = [&]() {
        const float c0 = 1.f + rs0, c1 = 1.f + rs1, e0 = nm0 * rs0, e1 = nm1 * rs1;
#pragma unroll
        for (int j = 0; j < 16; j++) {
          ao[4 * j + 0] = fmaf(bf_lo(xr[2 * j]), c0, e0); ao[4 * j + 1] = fmaf(bf_hi(xr[2 * j]), c0, e0);
          ao[4 * j + 2] = fmaf(bf_lo(xr[2 * j + 1]), c1, e1); ao[4 * j + 3] = fmaf(bf_hi(xr[2 * j + 1]), c1, e1);
        }
      };
      wg_wait<0>();
      reg_fence(oa[1]); reg_fence(oa[2]); reg_fence(oa[3]);
      release(B_EAUX);
      norm(1);
      if (OS1 == 3) o_store(1);
      if (NP == 0) { norm(2); norm(3); }
      mbar_wait_b(BAR(B_FWO), 0);
      resid();
      out_step(WO_SLOTS & 15u, of);
      if (NP == 1) { norm(2); norm(3); }
    }
    if (OS1 == 0) o_store(1);
    mbar_wait(BAR(B_FWO + 1), 0);
    out_step((WO_SLOTS >> 4) & 15u, of + 16);
    if (OS1 == 1) o_store(1);
    {
      uint4 v[NDIR][4];
      auto ld = [&](int k) {
        const uint4* p0 = mine + (slab(2 * k, hg) - hg) * 512;
        const uint4* p1 = mine + (slab(2 * k + 1, hg) - hg) * 512;
        v[k][0] = ldx4(p0); v[k][1] = ldx4(p0 + 32); v[k][2] = ldx4(p1); v[k][3] = ldx4(p1 + 32);
      };
      if (DW) __nanosleep(DW);
#pragma unroll
      for (int k = 0; k < NDIR; k++) ld(k);
      if (OS1 == 2) o_store(1);
#pragma unroll
      for (int k = 0; k < NDIR; k++) {
#pragma unroll 1
        for (uint32_t it = 0; it < SPIN_MAX; it++) {
          if (!__any_sync(~0u, max(max(v[k][0].x, v[k][1].x), max(v[k][2].x, v[k][3].x)) == SENT)) break;
#pragma unroll
          for (int j = k; j < NDIR; j++) ld(j);
        }
        const uint32_t a[16] = {v[k][0].x, v[k][1].x, v[k][0].y, v[k][1].y, v[k][0].z, v[k][1].z, v[k][0].w, v[k][1].w,
                                v[k][2].x, v[k][3].x, v[k][2].y, v[k][3].y, v[k][2].z, v[k][3].z, v[k][2].w, v[k][3].w};
        mbar_wait(BAR(B_FWO + 2 + k), 0);
        TLS(0, 34 + k);
        out_step((WO_SLOTS >> (8 + 4 * k)) & 15u, a);
        if (k) { wg_wait<1>(); release2(B_EO); }
      }
      o_store(2);
    }
    {
      const uint32_t dO = (d0 + w * 256) | (1u << 16);
      auto step = [&](int i, int r, int p, uint32_t as, uint32_t ws) {
        mbar_wait(BAR(B_FWO + i), 0);
        mbar_wait(BAR(B_VAL + r), p);
        TLS(0, 32 + i);
        const uint32_t da = dO + as * 1024, db = dW + ws * 1024;
        wg_fence();
#pragma unroll
        for (int kk = 0; kk < 4; kk++)
          wgmma_ss_n128<0, 1>(ao, mkdesc(da + (kk >> 1) * 512 + (kk & 1) * 2, HI_SW64), mkdesc(db + (kk >> 1) * 512 + (kk & 1) * 128, HI_SW128));
        wg_commit();
      };
      uint64_t tbl = WO_SLOTS >> (4 * I0);
      int r = 0, p = 0, rp = 0;
#pragma unroll 1
      for (int i = I0; i < 12; i++) {
        step(i, r, p, (A_SLOTS >> (4 * r)) & 15u, (uint32_t)tbl & 15u);
        tbl >>= 4;
#pragma unroll
        for (int c = 0; c < 2; c++)
          if (i == OS3 + c) stx4(mine + 3 * 4096 + c * 32, of[24 + c], of[26 + c], of[28 + c], of[30 + c]);
        wg_wait<1>();
        if (i > I0) release(B_EA + rp);
        rp = r;
        if (++r == NA) { r = 0; p ^= 1; }
        if (i >= 3 && i <= 9) release2(B_EO + i - 3);
      }
#pragma unroll
      for (int i = 12; i < 16; i++) {
        if (i == 16 - STAG && w == 1) mbar_wait(BAR(B_GO), 0);
        step(i, (i - I0) % NA, ((i - I0) / NA) & 1, (A_SLOTS >> (4 * ((i - I0) % NA))) & 15u, (uint32_t)(WO_SLOTS >> (4 * i)) & 15u);
        if (STAG && i == 15 - GOE && tid == 0) mbar_arrive(BAR(B_GO));
      }
    }
    mbar_wait(BAR(B_MOE), 0);
    {
      const float2 kk = lds_f2(sb + MISC + M_IDX + t * 8);
      const int k0 = (int)(~__float_as_uint(kk.x) & 2047u) - tb * 128, k1 = (int)(~__float_as_uint(kk.y) & 2047u) - tb * 128;
      if (NUNIT && __any_sync(~0u, (k0 >> 6) == w || (k1 >> 6) == w)) {
        const uint32_t a0 = (k0 == row0 ? 0x3F80u : 0u) | (k1 == row0 ? 0x3F800000u : 0u);
        const uint32_t a1 = (k0 == row0 + 8 ? 0x3F80u : 0u) | (k1 == row0 + 8 ? 0x3F800000u : 0u);
        wg_fence();
        wgmma_rs_n128<1>(ao, a0, a1, 0u, 0u, mkdesc((d0 + ((MISC + M_MOE) >> 4)) | (64u << 16), 0x40000000u));
        wg_commit();
      }
    }
    wg_wait<0>();
    reg_fence(ao);
    TLS(0, 10);
    const uint32_t ost = sb + (w ? S_D1 : S_D0) * SLOT + wq * 4096;
#pragma unroll
    for (int h = 0; h < 2; h++) {
#pragma unroll
      for (int j = 8 * h; j < 8 * h + 8; j += 2)
        stsm4(ost + h * 2048 + ((moff & 2047) ^ ((j & 7) << 4)), pack_bf16(ao[4 * j], ao[4 * j + 1]), pack_bf16(ao[4 * j + 2], ao[4 * j + 3]),
              pack_bf16(ao[4 * j + 4], ao[4 * j + 5]), pack_bf16(ao[4 * j + 6], ao[4 * j + 7]));
      if (OUTV == 2 || h) {
        fence_async_smem();
        __syncwarp();
        if (elect_one()) {
#pragma unroll
          for (int c = (OUTV == 2 ? h : 0); c <= h; c++)
            asm volatile("cp.async.bulk.tensor.2d.global.shared::cta.bulk_group [%0, {%2, %3}], [%1];" ::"l"(&tmOut), "r"(ost + c * 2048), "r"(hg * 128 + c * 64), "r"(tb * 128 + warp * 16) : "memory");
          if (h) asm volatile("cp.async.bulk.commit_group;\ncp.async.bulk.wait_group.read 0;" ::: "memory");
        }
        __syncwarp();
      }
    }
    TLS(0, 11);
    TLS(128, 9);
  }
}

typedef CUresult (*EncFn)(CUtensorMap*, CUtensorMapDataType, cuuint32_t, void*, const cuuint64_t*, const cuuint64_t*, const cuuint32_t*,
                          const cuuint32_t*, CUtensorMapInterleave, CUtensorMapSwizzle, CUtensorMapL2promotion, CUtensorMapFloatOOBfill);

void make_map2(EncFn enc, CUtensorMap* m, void* p, uint64_t rows, uint64_t cols, uint32_t brows, CUtensorMapL2promotion promo) {
  cuuint64_t gd[2] = {cols, rows}, gs[1] = {cols * 2};
  cuuint32_t bd[2] = {64, brows}, es[2] = {1, 1};
  enc(m, CU_TENSOR_MAP_DATA_TYPE_BFLOAT16, 2, p, gd, gs, bd, es, CU_TENSOR_MAP_INTERLEAVE_NONE, CU_TENSOR_MAP_SWIZZLE_128B, promo,
      CU_TENSOR_MAP_FLOAT_OOB_FILL_NONE);
}
void make_map3(EncFn enc, CUtensorMap* m, void* p, uint64_t rows, uint64_t cols, uint32_t brows) {
  cuuint64_t gd[3] = {64, rows, cols / 64}, gs[2] = {cols * 2, 128};
  cuuint32_t bd[3] = {64, brows, 2}, es[3] = {1, 1, 1};
  enc(m, CU_TENSOR_MAP_DATA_TYPE_BFLOAT16, 3, p, gd, gs, bd, es, CU_TENSOR_MAP_INTERLEAVE_NONE, CU_TENSOR_MAP_SWIZZLE_128B,
      CU_TENSOR_MAP_L2_PROMOTION_L2_256B, CU_TENSOR_MAP_FLOAT_OOB_FILL_NONE);
}

}

extern "C" void kernel_launch(void* const* d_in, const int* in_sizes, int n_in, void* d_out, int out_size) {
  static EncFn enc = nullptr;
  static int by_sm = 0;
  if (!enc) {
    void* fn = nullptr;
    cudaDriverEntryPointQueryResult qr;
    cudaGetDriverEntryPoint("cuTensorMapEncodeTiled", &fn, cudaEnableDefault, &qr);
    enc = (EncFn)fn;
    int dev = 0, sms = 0;
    cudaGetDevice(&dev);
    cudaDeviceGetAttribute(&sms, cudaDevAttrMultiProcessorCount, dev);
    by_sm = MAP == 2 && sms == NCTA + NSVC;
    cudaFuncSetAttribute(fused_kernel, cudaFuncAttributeMaxDynamicSharedMemorySize, SMEM_BYTES);
  }
  CUtensorMap tmX, tmW, tmWo, tmOut, tmG, tmU, tmD, tmR, tmWp;
  {
    cuuint64_t gd[5] = {64, 2, 128, 4, 16}, gs[4] = {2048, 16384, 4096, 128};
    cuuint32_t bd[5] = {64, 2, 4, 4, 2}, es[5] = {1, 1, 1, 1, 1};
    enc(&tmWp, CU_TENSOR_MAP_DATA_TYPE_BFLOAT16, 5, d_in[2], gd, gs, bd, es, CU_TENSOR_MAP_INTERLEAVE_NONE, CU_TENSOR_MAP_SWIZZLE_128B,
        CU_TENSOR_MAP_L2_PROMOTION_L2_256B, CU_TENSOR_MAP_FLOAT_OOB_FILL_NONE);
  }
  make_map2(enc, &tmR, d_in[0], SEQ, DM, 1, CU_TENSOR_MAP_L2_PROMOTION_L2_128B);
  make_map2(enc, &tmX, d_in[0], SEQ, DM, 128, XPROMO);
  make_map3(enc, &tmW, d_in[1], DM, 3 * DM, 64);
  make_map3(enc, &tmWo, d_in[2], DM, DM, 32);
  if (OUTV) make_map2(enc, &tmOut, d_out, SEQ, DM, 16, CU_TENSOR_MAP_L2_PROMOTION_L2_128B); else make_map3(enc, &tmOut, d_out, SEQ, DM, 64);
  make_map2(enc, &tmG, d_in[5], DM, FF, 64, MPROMO);
  make_map2(enc, &tmU, d_in[6], DM, FF, 64, MPROMO);
  make_map2(enc, &tmD, d_in[7], FF, DM, 64, MPROMO);
  typedef const __nv_bfloat16* P;
  cudaLaunchConfig_t cfg = {};
  cfg.gridDim = dim3(NCTA + NSVC); cfg.blockDim = dim3(512); cfg.dynamicSmemBytes = SMEM_BYTES; cfg.stream = cudaStreamPerThread;
  cudaLaunchAttribute at[1];
  at[0].id = cudaLaunchAttributeClusterDimension;
  at[0].val.clusterDim.x = 2; at[0].val.clusterDim.y = 1; at[0].val.clusterDim.z = 1;
  cfg.attrs = at; cfg.numAttrs = 1;
  cudaLaunchKernelEx(&cfg, fused_kernel, (P)d_in[0], (P)d_in[1], (P)d_in[2], (P)d_in[4], (P)d_in[7], by_sm, tmX, tmW, tmWo, tmOut, tmG, tmU, tmD, tmR, tmWp);
}
```

```cpp
#include <cuda_runtime.h>
#include <cuda.h>
#include <cuda_bf16.h>
#include <stdint.h>

namespace {

template <int TA, int TB> __device__ __forceinline__ void wgmma_ss_n128(float (&d)[64], uint64_t da, uint64_t db) {
  asm volatile("wgmma.mma_async.sync.aligned.m64n128k16.f32.bf16.bf16 "
  "{%0,%1,%2,%3,%4,%5,%6,%7,%8,%9,%10,%11,%12,%13,%14,%15,%16,%17,%18,%19,%20,%21,%22,%23,%24,%25,%26,%27,%28,%29,%30,%31,%32,%33,%34,%35,%36,%37,%38,%39,%40,%41,%42,%43,%44,%45,%46,%47,%48,%49,%50,%51,%52,%53,%54,%55,%56,%57,%58,%59,%60,%61,%62,%63}, "
  "%64, %65, 1, 1, 1, %66, %67;"
  : "+f"(d[0]),"+f"(d[1]),"+f"(d[2]),"+f"(d[3]),"+f"(d[4]),"+f"(d[5]),"+f"(d[6]),"+f"(d[7]),"+f"(d[8]),"+f"(d[9]),"+f"(d[10]),"+f"(d[11]),"+f"(d[12]),"+f"(d[13]),"+f"(d[14]),"+f"(d[15]),"+f"(d[16]),"+f"(d[17]),"+f"(d[18]),"+f"(d[19]),"+f"(d[20]),"+f"(d[21]),"+f"(d[22]),"+f"(d[23]),"+f"(d[24]),"+f"(d[25]),"+f"(d[26]),"+f"(d[27]),"+f"(d[28]),"+f"(d[29]),"+f"(d[30]),"+f"(d[31]),"+f"(d[32]),"+f"(d[33]),"+f"(d[34]),"+f"(d[35]),"+f"(d[36]),"+f"(d[37]),"+f"(d[38]),"+f"(d[39]),"+f"(d[40]),"+f"(d[41]),"+f"(d[42]),"+f"(d[43]),"+f"(d[44]),"+f"(d[45]),"+f"(d[46]),"+f"(d[47]),"+f"(d[48]),"+f"(d[49]),"+f"(d[50]),"+f"(d[51]),"+f"(d[52]),"+f"(d[53]),"+f"(d[54]),"+f"(d[55]),"+f"(d[56]),"+f"(d[57]),"+f"(d[58]),"+f"(d[59]),"+f"(d[60]),"+f"(d[61]),"+f"(d[62]),"+f"(d[63])
  : "l"(da), "l"(db), "n"(TA), "n"(TB));
}
template <int TB> __device__ __forceinline__ void wgmma_rs_n72(float (&d)[36], uint32_t a0, uint32_t a1, uint32_t a2, uint32_t a3, uint64_t db) {
  asm volatile("wgmma.mma_async.sync.aligned.m64n72k16.f32.bf16.bf16 "
  "{%0,%1,%2,%3,%4,%5,%6,%7,%8,%9,%10,%11,%12,%13,%14,%15,%16,%17,%18,%19,%20,%21,%22,%23,%24,%25,%26,%27,%28,%29,%30,%31,%32,%33,%34,%35}, "
  "{%36,%37,%38,%39}, %40, 1, 1, 1, %41;"
  : "+f"(d[0]),"+f"(d[1]),"+f"(d[2]),"+f"(d[3]),"+f"(d[4]),"+f"(d[5]),"+f"(d[6]),"+f"(d[7]),"+f"(d[8]),"+f"(d[9]),"+f"(d[10]),"+f"(d[11]),"+f"(d[12]),"+f"(d[13]),"+f"(d[14]),"+f"(d[15]),"+f"(d[16]),"+f"(d[17]),"+f"(d[18]),"+f"(d[19]),"+f"(d[20]),"+f"(d[21]),"+f"(d[22]),"+f"(d[23]),"+f"(d[24]),"+f"(d[25]),"+f"(d[26]),"+f"(d[27]),"+f"(d[28]),"+f"(d[29]),"+f"(d[30]),"+f"(d[31]),"+f"(d[32]),"+f"(d[33]),"+f"(d[34]),"+f"(d[35])
  : "r"(a0), "r"(a1), "r"(a2), "r"(a3), "l"(db), "n"(TB));
}
template <int TB> __device__ __forceinline__ void wgmma_rz_n72(float (&d)[36], uint32_t a0, uint32_t a1, uint32_t a2, uint32_t a3, uint64_t db) {
  asm volatile("wgmma.mma_async.sync.aligned.m64n72k16.f32.bf16.bf16 "
  "{%0,%1,%2,%3,%4,%5,%6,%7,%8,%9,%10,%11,%12,%13,%14,%15,%16,%17,%18,%19,%20,%21,%22,%23,%24,%25,%26,%27,%28,%29,%30,%31,%32,%33,%34,%35}, "
  "{%36,%37,%38,%39}, %40, 0, 1, 1, %41;"
  : "=f"(d[0]),"=f"(d[1]),"=f"(d[2]),"=f"(d[3]),"=f"(d[4]),"=f"(d[5]),"=f"(d[6]),"=f"(d[7]),"=f"(d[8]),"=f"(d[9]),"=f"(d[10]),"=f"(d[11]),"=f"(d[12]),"=f"(d[13]),"=f"(d[14]),"=f"(d[15]),"=f"(d[16]),"=f"(d[17]),"=f"(d[18]),"=f"(d[19]),"=f"(d[20]),"=f"(d[21]),"=f"(d[22]),"=f"(d[23]),"=f"(d[24]),"=f"(d[25]),"=f"(d[26]),"=f"(d[27]),"=f"(d[28]),"=f"(d[29]),"=f"(d[30]),"=f"(d[31]),"=f"(d[32]),"=f"(d[33]),"=f"(d[34]),"=f"(d[35])
  : "r"(a0), "r"(a1), "r"(a2), "r"(a3), "l"(db), "n"(TB));
}
template <int TB> __device__ __forceinline__ void wgmma_rs_n40(float (&d)[20], uint32_t a0, uint32_t a1, uint32_t a2, uint32_t a3, uint64_t db) {
  asm volatile("wgmma.mma_async.sync.aligned.m64n40k16.f32.bf16.bf16 "
  "{%0,%1,%2,%3,%4,%5,%6,%7,%8,%9,%10,%11,%12,%13,%14,%15,%16,%17,%18,%19}, "
  "{%20,%21,%22,%23}, %24, 1, 1, 1, %25;"
  : "+f"(d[0]),"+f"(d[1]),"+f"(d[2]),"+f"(d[3]),"+f"(d[4]),"+f"(d[5]),"+f"(d[6]),"+f"(d[7]),"+f"(d[8]),"+f"(d[9]),"+f"(d[10]),"+f"(d[11]),"+f"(d[12]),"+f"(d[13]),"+f"(d[14]),"+f"(d[15]),"+f"(d[16]),"+f"(d[17]),"+f"(d[18]),"+f"(d[19])
  : "r"(a0), "r"(a1), "r"(a2), "r"(a3), "l"(db), "n"(TB));
}
template <int TB> __device__ __forceinline__ void wgmma_rz_n40(float (&d)[20], uint32_t a0, uint32_t a1, uint32_t a2, uint32_t a3, uint64_t db) {
  asm volatile("wgmma.mma_async.sync.aligned.m64n40k16.f32.bf16.bf16 "
  "{%0,%1,%2,%3,%4,%5,%6,%7,%8,%9,%10,%11,%12,%13,%14,%15,%16,%17,%18,%19}, "
  "{%20,%21,%22,%23}, %24, 0, 1, 1, %25;"
  : "=f"(d[0]),"=f"(d[1]),"=f"(d[2]),"=f"(d[3]),"=f"(d[4]),"=f"(d[5]),"=f"(d[6]),"=f"(d[7]),"=f"(d[8]),"=f"(d[9]),"=f"(d[10]),"=f"(d[11]),"=f"(d[12]),"=f"(d[13]),"=f"(d[14]),"=f"(d[15]),"=f"(d[16]),"=f"(d[17]),"=f"(d[18]),"=f"(d[19])
  : "r"(a0), "r"(a1), "r"(a2), "r"(a3), "l"(db), "n"(TB));
}
template <int TB> __device__ __forceinline__ void wgmma_rs_n128(float (&d)[64], uint32_t a0, uint32_t a1, uint32_t a2, uint32_t a3, uint64_t db) {
  asm volatile("wgmma.mma_async.sync.aligned.m64n128k16.f32.bf16.bf16 "
  "{%0,%1,%2,%3,%4,%5,%6,%7,%8,%9,%10,%11,%12,%13,%14,%15,%16,%17,%18,%19,%20,%21,%22,%23,%24,%25,%26,%27,%28,%29,%30,%31,%32,%33,%34,%35,%36,%37,%38,%39,%40,%41,%42,%43,%44,%45,%46,%47,%48,%49,%50,%51,%52,%53,%54,%55,%56,%57,%58,%59,%60,%61,%62,%63}, "
  "{%64,%65,%66,%67}, %68, 1, 1, 1, %69;"
  : "+f"(d[0]),"+f"(d[1]),"+f"(d[2]),"+f"(d[3]),"+f"(d[4]),"+f"(d[5]),"+f"(d[6]),"+f"(d[7]),"+f"(d[8]),"+f"(d[9]),"+f"(d[10]),"+f"(d[11]),"+f"(d[12]),"+f"(d[13]),"+f"(d[14]),"+f"(d[15]),"+f"(d[16]),"+f"(d[17]),"+f"(d[18]),"+f"(d[19]),"+f"(d[20]),"+f"(d[21]),"+f"(d[22]),"+f"(d[23]),"+f"(d[24]),"+f"(d[25]),"+f"(d[26]),"+f"(d[27]),"+f"(d[28]),"+f"(d[29]),"+f"(d[30]),"+f"(d[31]),"+f"(d[32]),"+f"(d[33]),"+f"(d[34]),"+f"(d[35]),"+f"(d[36]),"+f"(d[37]),"+f"(d[38]),"+f"(d[39]),"+f"(d[40]),"+f"(d[41]),"+f"(d[42]),"+f"(d[43]),"+f"(d[44]),"+f"(d[45]),"+f"(d[46]),"+f"(d[47]),"+f"(d[48]),"+f"(d[49]),"+f"(d[50]),"+f"(d[51]),"+f"(d[52]),"+f"(d[53]),"+f"(d[54]),"+f"(d[55]),"+f"(d[56]),"+f"(d[57]),"+f"(d[58]),"+f"(d[59]),"+f"(d[60]),"+f"(d[61]),"+f"(d[62]),"+f"(d[63])
  : "r"(a0), "r"(a1), "r"(a2), "r"(a3), "l"(db), "n"(TB));
}
template <int TA, int TB> __device__ __forceinline__ void wgmma_ss_n8(float (&d)[4], uint64_t da, uint64_t db) {
  asm volatile("wgmma.mma_async.sync.aligned.m64n8k16.f32.bf16.bf16 "
  "{%0,%1,%2,%3}, "
  "%4, %5, 1, 1, 1, %6, %7;"
  : "+f"(d[0]),"+f"(d[1]),"+f"(d[2]),"+f"(d[3])
  : "l"(da), "l"(db), "n"(TA), "n"(TB));
}
template <int TA, int TB> __device__ __forceinline__ void wgmma_ss_n16(float (&d)[8], uint64_t da, uint64_t db) {
  asm volatile("wgmma.mma_async.sync.aligned.m64n16k16.f32.bf16.bf16 "
  "{%0,%1,%2,%3,%4,%5,%6,%7}, "
  "%8, %9, 1, 1, 1, %10, %11;"
  : "+f"(d[0]),"+f"(d[1]),"+f"(d[2]),"+f"(d[3]),"+f"(d[4]),"+f"(d[5]),"+f"(d[6]),"+f"(d[7])
  : "l"(da), "l"(db), "n"(TA), "n"(TB));
}

constexpr int SEQ = 2048, DM = 1024, FF = 3584;
constexpr int NCTA = 128, NSVC = 4;
constexpr int NUNIT = 112;
constexpr uint32_t SLOT = 16384;
constexpr uint32_t MISC = 14 * SLOT;
constexpr uint32_t SMEM_BYTES = MISC + 3072;
constexpr uint32_t M_MOE = 0;
constexpr uint32_t M_BAR = 2048;
constexpr uint32_t M_DUM = 2048 + 1020;
constexpr uint32_t M_IDX = 2048 + 688;
constexpr uint32_t M_KEY = 2048 + 960;
constexpr uint32_t M_TL = 2048 + 720;
#define NQ 5
constexpr int NF = 16 - NQ, NR = NQ == 5 ? 4 : 3;
constexpr int B_FXQ = 0, B_FKV = 3, B_AST = 6, B_MOE = 7, B_MF = 8  , B_CQ = 12, B_XS = 13, B_DF = 14, B_ZOK = 15, B_FWO = 21  , B_FQ = B_FWO - NQ,
              B_UP = 37, B_FIN = 38, B_KVB = 39, B_ME = 40  , B_HF = 44, B_AF = 45  , B_AR = 50  , B_GO = 52,
              B_FAUX = 53, B_EAUX = 54, B_T0 = 55, B_DE = 56, B_EA = 57  , B_VAL = 62  ,
              B_E = 67  , B_STG = 70, B_EQ = 71  , B_EO = 76  , NBAR = 83, B_KV4 = 83, B_MS = 84;
constexpr uint32_t MT = 9216, A_ONES = 12 * SLOT + 3 * MT, A_CS = A_ONES + 2048, A_ST = A_CS + 1536;
constexpr int S_V0 = 11, S_V1 = 7;
constexpr int C_B = 0, C_DONE = 32, NCNT = 2;
constexpr uint32_t QX_SLOTS = NQ == 5 ? 0x43102u : 0x354021u;
constexpr uint32_t QW_SLOTS = 0xB76A98u;
constexpr uint32_t qx(int k) { return (QX_SLOTS >> (4 * k)) & 15u; }
constexpr uint32_t qw(int k) { return (QW_SLOTS >> (4 * k)) & 15u; }
constexpr uint32_t S_KVB = 8, S_D0 = NQ == 5 ? 5 : 1, S_D1 = NQ == 5 ? 11 : 2;
constexpr int WQ0 = NQ == 5 ? 1 : 3;
constexpr uint32_t wo_slot_c(int i) { return i >= 9 ? wo_slot_c(i - 9) : (i == 7 ? S_D0 : (i == 8 ? S_D1 : (((i & 1) || i + WQ0 == 1) ? qx((i + WQ0) >> 1) : qw((i + WQ0) >> 1)))); }
constexpr uint64_t wo_slots() { uint64_t t = 0; for (int i = 0; i < 16; i++) t |= (uint64_t)wo_slot_c(i) << (4 * i); return t; }
constexpr uint64_t WO_SLOTS = wo_slots();
constexpr uint32_t A_SLOTS = 0xDC000u | (S_KVB << 8) | (qw(NQ - 1) << 4) | qx(NQ - 1);
constexpr uint32_t SX14 = qx(NQ - 2), SX15 = qx(NQ - 1), SXQ0 = qx(0);
#define WOD 2
#define PLC 3
#define PFG1 10
#define PFNS1 150
#define PFG0 3
#define RS0 0
#define WPF 1
#define POLLNS 150
#define SVNS 100
#define MPROMO CU_TENSOR_MAP_L2_PROMOTION_L2_128B
#define MW0 0
#define PFILL 0
#define H2W (NQ - 3)
#define TOPW 1000
#define PFT 0
#define SV0 2
#define SV0A 14
#define SV0B 22
#define ASTE 2
#define PFS 1
#define PFTAB 0x0012222220000ull
#define HW 0
#define DPF 1
#define PROBE 0x8
#define OS1 0
#define YW 0
#define OS2 3
#define NOVAL 0
#define NDIR 1
#define I0 (2 + NDIR)
#define DW 0
#define OSP 1
#define NA 5
#define STAG 4
#define GOE 0
#define SVP 99
#define KEY1 0
#define HYB 0
#define DV 0
#define DVJ 4
#define DVK 10
#define FW 0
#define E1E 0
#define GATE 0
#define SVD 0
#define XPROMO CU_TENSOR_MAP_L2_PROMOTION_L2_128B
#define MC0 3
#define MX 0
#define OUTV 1
#define BW0 2
#define QL 1
#define NP 0
#define FINCP 0
#define DNS 0
#define WOK 99
#define WOD1 2
#define SVT 64
#define MRED 1
#define MRW 0
#define H2D 400
#define MRD 0
#define STP 0
#define TPNS 50
#define DLP 0
#define MFIN 0
#define MFD 300
#define SF 1
#define PH MFIN
#define RSL 0
#define PFW 3000
#define KVE 1
#define P2NS 0
#define OS3 4
#define PLP 2
#define FINJ 9
#define PFD 0
#define PFG 3
#define PFNS2 150
#define PFNS 250
#define MAP 2
#define RSNS 60
#define SVS 6
#define PRODLATE 0
#define MC 7
#define QE 0
#define TMP 1
#define TMPW 4
#define DS 14
#define RL 0
#define EV 0
#define LQ 1
#define E7 1
#define RK 1
#define LE 0
#define SL7 0
#define XP 3
#define VR 4
#define KEEP 1
#define KP 4
#define KC 1
#define MS 0
constexpr int CON_REGS = 224, MOE_REGS = 40, PROD_REGS = 24;
constexpr uint32_t SPIN_MAX = 2000000;
constexpr uint32_t SENT = 0xFFFFFFFFu;

struct __align__(128) Scratch {
  uint4 o[NCTA * 2048];
  uint4 part[NCTA * 544];
  uint4 fin[8 * 640];
  float2 stats[SEQ];
  uint32_t key[SEQ];
  uint32_t cs[3 * DM];
  uint4 y[NCTA * 128];
  uint32_t h[56 * 256];
  uint32_t top[128];
  uint32_t cnt[NCNT * 32];
};
__device__ Scratch G;
#define TLS(th, i)
#define TLP_(i)
#define TLG(i)
#define TLDUMP()

__device__ __forceinline__ bool elect_one() {
  uint32_t p;
  asm volatile("{\n.reg .pred P;\nelect.sync _|P, 0xffffffff;\nselp.b32 %0, 1, 0, P;\n}" : "=r"(p));
  return p;
}
__device__ __forceinline__ void mbar_init(uint32_t b, uint32_t c) { asm volatile("mbarrier.init.shared::cta.b64 [%0], %1;" ::"r"(b), "r"(c) : "memory"); }
__device__ __forceinline__ void mbar_expect_tx(uint32_t b, uint32_t bytes) { asm volatile("mbarrier.arrive.expect_tx.shared::cta.b64 _, [%0], %1;" ::"r"(b), "r"(bytes) : "memory"); }
__device__ __forceinline__ void mbar_arrive(uint32_t b) { asm volatile("mbarrier.arrive.shared::cta.b64 _, [%0];" ::"r"(b) : "memory"); }
__device__ __forceinline__ void mbar_wait_b(uint32_t b, uint32_t parity) {
  asm volatile(
      "{\n.reg .pred p;\n.reg .u32 cnt;\nmov.u32 cnt, 0;\n"
      "LW:\nmbarrier.try_wait.parity.shared::cta.b64 p, [%0], %1;\n@p bra LD;\n"
      "add.u32 cnt, cnt, 1;\nsetp.lt.u32 p, cnt, 4000000;\n@p bra LW;\ntrap;\nLD:\n}" ::"r"(b), "r"(parity) : "memory");
}
__device__ __forceinline__ void mbar_wait(uint32_t b, uint32_t parity) {
  asm volatile("{\n.reg .pred p;\nLW:\nmbarrier.try_wait.parity.shared::cta.b64 p, [%0], %1;\n@!p bra LW;\n}" ::"r"(b), "r"(parity) : "memory");
}
__device__ __forceinline__ bool mbar_test(uint32_t b, uint32_t parity) {
  uint32_t r;
  asm volatile("{\n.reg .pred p;\nmbarrier.test_wait.parity.shared::cta.b64 p, [%1], %2;\nselp.b32 %0, 1, 0, p;\n}" : "=r"(r) : "r"(b), "r"(parity) : "memory");
  return r;
}
__device__ __forceinline__ uint32_t ev_arrive(uint32_t a) { uint32_t r; asm volatile("atom.shared.add.u32 %0, [%1], 1;" : "=r"(r) : "r"(a) : "memory"); return r; }
__device__ __forceinline__ void tma2d(uint32_t dst, const CUtensorMap* m, int c0, int c1, uint32_t bar) {
  asm volatile("cp.async.bulk.tensor.2d.shared::cluster.global.mbarrier::complete_tx::bytes [%0], [%1, {%3, %4}], [%2];" ::"r"(dst), "l"(m), "r"(bar), "r"(c0), "r"(c1) : "memory");
}
__device__ __forceinline__ void tma3d(uint32_t dst, const CUtensorMap* m, int c1, int c2, uint32_t bar) {
  asm volatile("cp.async.bulk.tensor.3d.shared::cluster.global.mbarrier::complete_tx::bytes [%0], [%1, {%3, %4, %5}], [%2];" ::"r"(dst), "l"(m), "r"(bar), "r"(0), "r"(c1), "r"(c2) : "memory");
}
__device__ __forceinline__ void tma3d_mc(uint32_t dst, const CUtensorMap* m, int c1, int c2, uint32_t bar) {
  asm volatile("cp.async.bulk.tensor.3d.shared::cluster.global.mbarrier::complete_tx::bytes.multicast::cluster [%0], [%1, {%3, %4, %5}], [%2], %6;" ::"r"(dst), "l"(m), "r"(bar), "r"(0), "r"(c1), "r"(c2), "h"((uint16_t)3) : "memory");
}
__device__ __forceinline__ void tma5d(uint32_t dst, const CUtensorMap* m, int c2, int c4, uint32_t bar, bool mc) {
  if (mc) asm volatile("cp.async.bulk.tensor.5d.shared::cluster.global.mbarrier::complete_tx::bytes.multicast::cluster [%0], [%1, {%3, %3, %4, %3, %5}], [%2], %6;" ::"r"(dst), "l"(m), "r"(bar), "r"(0), "r"(c2), "r"(c4), "h"((uint16_t)3) : "memory");
  else asm volatile("cp.async.bulk.tensor.5d.shared::cluster.global.mbarrier::complete_tx::bytes [%0], [%1, {%3, %3, %4, %3, %5}], [%2];" ::"r"(dst), "l"(m), "r"(bar), "r"(0), "r"(c2), "r"(c4) : "memory");
}
__device__ __forceinline__ void mbar_arrive_cta(uint32_t b, uint32_t cta) {
  asm volatile("{\n.reg .b32 ra;\nmapa.shared::cluster.u32 ra, %0, %1;\nmbarrier.arrive.shared::cluster.b64 _, [ra];\n}" ::"r"(b), "r"(cta) : "memory");
}
constexpr uint64_t POL_FIRST = 0x12F0000000000000ull;
__device__ __forceinline__ void tma2d_ef(uint32_t dst, const CUtensorMap* m, int c0, int c1, uint32_t bar) {
  asm volatile("cp.async.bulk.tensor.2d.shared::cluster.global.mbarrier::complete_tx::bytes.L2::cache_hint [%0], [%1, {%3, %4}], [%2], %5;" ::"r"(dst), "l"(m), "r"(bar), "r"(c0), "r"(c1), "l"(POL_FIRST) : "memory");
}
__device__ __forceinline__ void bulk_ld(uint32_t dst, const void* src, uint32_t bytes, uint32_t bar) {
  asm volatile("cp.async.bulk.shared::cluster.global.mbarrier::complete_tx::bytes [%0], [%1], %2, [%3];" ::"r"(dst), "l"(src), "r"(bytes), "r"(bar) : "memory");
}
__device__ __forceinline__ void bulk_pf(const void* src, uint32_t bytes) { asm volatile("cp.async.bulk.prefetch.L2.global [%0], %1;" ::"l"(src), "r"(bytes) : "memory"); }
__device__ __forceinline__ void tma2d_pf(const CUtensorMap* m, int c0, int c1) {
  asm volatile("cp.async.bulk.prefetch.tensor.2d.L2.global [%0, {%1, %2}];" ::"l"(m), "r"(c0), "r"(c1) : "memory");
}
__device__ __forceinline__ void map_pf(const CUtensorMap* m) { asm volatile("prefetch.tensormap [%0];" ::"l"(m) : "memory"); }
__device__ __forceinline__ void line_pf(const void* p) { asm volatile("prefetch.global.L2 [%0];" ::"l"(p)); }
__device__ __forceinline__ void pf128(uint32_t dummy, const void* src) { asm volatile("cp.async.ca.shared.global.L2::128B [%0], [%1], 4;" ::"r"(dummy), "l"(src) : "memory"); }
__device__ __forceinline__ void pf256(uint32_t dummy, const void* src) { asm volatile("cp.async.ca.shared.global.L2::256B [%0], [%1], 4;" ::"r"(dummy), "l"(src) : "memory"); }
__device__ __forceinline__ void cp16x2(uint32_t dst, const void* src) {
  asm volatile("cp.async.cg.shared.global [%0], [%1], 16;\ncp.async.cg.shared.global [%0+4096], [%1+512], 16;" ::"r"(dst), "l"(src) : "memory");
}
constexpr uint32_t HI_SW128 = 0x40000000u | (1024 >> 4), HI_SW64 = 0x80000000u | (512 >> 4), HI_NOSW = 512 >> 4;
__device__ __forceinline__ uint64_t mkdesc(uint32_t lo, uint32_t hi) { uint64_t d; asm("mov.b64 %0, {%1, %2};" : "=l"(d) : "r"(lo), "r"(hi)); return d; }
__device__ __forceinline__ void wg_fence() { asm volatile("wgmma.fence.sync.aligned;" ::: "memory"); }
__device__ __forceinline__ void wg_commit() { asm volatile("wgmma.commit_group.sync.aligned;" ::: "memory"); }
template <int N> __device__ __forceinline__ void wg_wait() { asm volatile("wgmma.wait_group.sync.aligned %0;" ::"n"(N) : "memory"); }
template <int N> __device__ __forceinline__ void reg_fence(float (&a)[N]) {
#pragma unroll
  for (int i = 0; i < N; i++) asm volatile("" : "+f"(a[i])::"memory");
}
template <int ID, int N> __device__ __forceinline__ void bar_sync() { asm volatile("bar.sync %0, %1;" ::"n"(ID), "n"(N) : "memory"); }
__device__ __forceinline__ void fence_async_smem() { asm volatile("fence.proxy.async.shared::cta;" ::: "memory"); }
__device__ __forceinline__ void fence_async_gmem() { asm volatile("fence.proxy.async.global;" ::: "memory"); }
__device__ __forceinline__ uint32_t pack_bf16(float lo, float hi) { uint32_t r; asm("cvt.rn.bf16x2.f32 %0, %1, %2;" : "=r"(r) : "f"(hi), "f"(lo)); return r; }
__device__ __forceinline__ float bf_lo(uint32_t v) { return __uint_as_float(v << 16); }
__device__ __forceinline__ float bf_hi(uint32_t v) { return __uint_as_float(v & 0xFFFF0000u); }
__device__ __forceinline__ float bf_round(float v) { return bf_lo(pack_bf16(v, v)); }
__device__ __forceinline__ uint32_t bf_sub2(uint32_t a, uint32_t b) { uint32_t r; asm("sub.rn.bf16x2 %0, %1, %2;" : "=r"(r) : "r"(a), "r"(b)); return r; }
__device__ __forceinline__ float rcp(float v) { float r; asm("rcp.approx.ftz.f32 %0, %1;" : "=f"(r) : "f"(v)); return r; }
__device__ __forceinline__ float ex2(float v) { float r; asm("ex2.approx.ftz.f32 %0, %1;" : "=f"(r) : "f"(v)); return r; }
__device__ __forceinline__ float sigmoid(float v) { return rcp(1.f + ex2(v * -1.4426950408889634f)); }
__device__ __forceinline__ void stsm4(uint32_t a, uint32_t r0, uint32_t r1, uint32_t r2, uint32_t r3) {
  asm volatile("stmatrix.sync.aligned.m8n8.x4.shared.b16 [%0], {%1,%2,%3,%4};" ::"r"(a), "r"(r0), "r"(r1), "r"(r2), "r"(r3) : "memory");
}
__device__ __forceinline__ void stsm4t(uint32_t a, uint32_t r0, uint32_t r1, uint32_t r2, uint32_t r3) {
  asm volatile("stmatrix.sync.aligned.m8n8.x4.trans.shared.b16 [%0], {%1,%2,%3,%4};" ::"r"(a), "r"(r0), "r"(r1), "r"(r2), "r"(r3) : "memory");
}
__device__ __forceinline__ void ldsm4(uint32_t a, uint32_t& r0, uint32_t& r1, uint32_t& r2, uint32_t& r3) {
  asm volatile("ldmatrix.sync.aligned.m8n8.x4.shared.b16 {%0,%1,%2,%3}, [%4];" : "=r"(r0), "=r"(r1), "=r"(r2), "=r"(r3) : "r"(a) : "memory");
}
__device__ __forceinline__ uint32_t movmat(uint32_t a) { uint32_t d; asm volatile("movmatrix.sync.aligned.m8n8.trans.b16 %0, %1;" : "=r"(d) : "r"(a)); return d; }
__device__ __forceinline__ void sts_h(uint32_t a, float v) { asm volatile("st.shared.u16 [%0], %1;" ::"r"(a), "h"((uint16_t)pack_bf16(v, v)) : "memory"); }
__device__ __forceinline__ float2 lds_f2(uint32_t a) { float2 v; asm volatile("ld.shared.v2.f32 {%0,%1}, [%2];" : "=f"(v.x), "=f"(v.y) : "r"(a)); return v; }
__device__ __forceinline__ float lds_f(uint32_t a) { float v; asm volatile("ld.shared.f32 %0, [%1];" : "=f"(v) : "r"(a)); return v; }
__device__ __forceinline__ float4 lds_f4(uint32_t a) { float4 v; asm volatile("ld.shared.v4.f32 {%0,%1,%2,%3}, [%4];" : "=f"(v.x), "=f"(v.y), "=f"(v.z), "=f"(v.w) : "r"(a)); return v; }
__device__ __forceinline__ uint32_t lds_u(uint32_t a) { uint32_t v; asm volatile("ld.shared.u32 %0, [%1];" : "=r"(v) : "r"(a) : "memory"); return v; }
__device__ __forceinline__ uint4 lds_u4(uint32_t a) { uint4 v; asm volatile("ld.shared.v4.u32 {%0,%1,%2,%3}, [%4];" : "=r"(v.x), "=r"(v.y), "=r"(v.z), "=r"(v.w) : "r"(a) : "memory"); return v; }
__device__ __forceinline__ void sts_u(uint32_t a, uint32_t v) { asm volatile("st.shared.u32 [%0], %1;" ::"r"(a), "r"(v) : "memory"); }
__device__ __forceinline__ void sts_u4(uint32_t a, uint4 v) { asm volatile("st.shared.v4.u32 [%0], {%1,%2,%3,%4};" ::"r"(a), "r"(v.x), "r"(v.y), "r"(v.z), "r"(v.w) : "memory"); }
__device__ __forceinline__ uint4 ldx4(const void* p) { uint4 v; asm volatile("ld.relaxed.gpu.global.v4.u32 {%0,%1,%2,%3}, [%4];" : "=r"(v.x), "=r"(v.y), "=r"(v.z), "=r"(v.w) : "l"(p) : "memory"); return v; }
__device__ __forceinline__ uint2 ldx2(const void* p) { uint2 v; asm volatile("ld.relaxed.gpu.global.v2.u32 {%0,%1}, [%2];" : "=r"(v.x), "=r"(v.y) : "l"(p) : "memory"); return v; }
__device__ __forceinline__ uint32_t ldx1(const void* p) { uint32_t v; asm volatile("ld.relaxed.gpu.global.u32 %0, [%1];" : "=r"(v) : "l"(p) : "memory"); return v; }
__device__ __forceinline__ void stx4(void* p, uint32_t a, uint32_t b, uint32_t c, uint32_t d) { asm volatile("st.relaxed.gpu.global.v4.u32 [%0], {%1,%2,%3,%4};" ::"l"(p), "r"(a), "r"(b), "r"(c), "r"(d) : "memory"); }
__device__ __forceinline__ void stx2(void* p, uint32_t a, uint32_t b) { asm volatile("st.relaxed.gpu.global.v2.u32 [%0], {%1,%2};" ::"l"(p), "r"(a), "r"(b) : "memory"); }
__device__ __forceinline__ void stx1(void* p, uint32_t a) { asm volatile("st.relaxed.gpu.global.u32 [%0], %1;" ::"l"(p), "r"(a) : "memory"); }
__device__ __forceinline__ uint32_t umax4(uint4 v) { return max(max(v.x, v.y), max(v.z, v.w)); }
__device__ __forceinline__ uint32_t f2x(float f) { return min(__float_as_uint(f), 0xFFFFFFFEu); }
__device__ __forceinline__ void red4(float* p, float a, float b, float c, float d) { asm volatile("red.relaxed.gpu.global.add.v4.f32 [%0], {%1,%2,%3,%4};" ::"l"(p), "f"(a), "f"(b), "f"(c), "f"(d) : "memory"); }
__device__ __forceinline__ void cnt_arrive(int c) { asm volatile("red.release.gpu.global.add.u32 [%0], 1;" ::"l"(&G.cnt[c]) : "memory"); }
__device__ __forceinline__ void cnt_wait(int c, uint32_t target) {
#pragma unroll 1
  for (uint32_t it = 0; it < SPIN_MAX; it++) {
    uint32_t v;
    asm volatile("ld.acquire.gpu.global.u32 %0, [%1];" : "=r"(v) : "l"(&G.cnt[c]) : "memory");
    if (v >= target) break;
    __nanosleep(POLLNS);
  }
}
__device__ __forceinline__ void cnt_done() {
  uint32_t t;
  asm volatile("atom.acq_rel.gpu.global.add.u32 %0, [%1], 1;" : "=r"(t) : "l"(&G.cnt[C_DONE]) : "memory");
  if (t == NCTA + NSVC - 1) {
#pragma unroll 1
    for (int i = 0; i < NCNT; i++) G.cnt[i * 32] = 0;
  }
}
__device__ __forceinline__ float phi(float u, float rs, float rl) {
  float a = fmaf(u, rs, 1.000001f), e = ex2(u * rl), r;
  asm("add.sat.f32 %0, %1, 0f358637BD;" : "=f"(e) : "f"(e));
  asm("max.NaN.f32 %0, %1, %2;" : "=f"(r) : "f"(a), "f"(e));
  return r;
}

__device__ __forceinline__ int kstep1(int e, int hg) { return e < 14 ? (e < 2 * hg ? e : e + 2) : 2 * hg + e - 14; }
__device__ __forceinline__ int slab(int n, int hg) {
  return n + (((n + 7 - hg) * 37) >> 8);
}
__host__ __device__ constexpr uint32_t d_off(int i) { return i < 3 ? 12 * SLOT + (NR == 4 ? i : (i == 2 ? 0 : i + 1)) * MT : (i < 5 ? S_D0 * SLOT + (i - 3) * 8192 : S_D1 * SLOT + (i - 5) * 8192); }
__host__ __device__ constexpr uint32_t h_off(int i) { return i < 3 ? 12 * SLOT + i * MT + 8192 : (i < 5 ? A_ONES + (i - 3) * 1024 : MISC + M_MOE + (i - 5) * 1024); }
__device__ __forceinline__ uint32_t m_off(int r) { return r < 3 ? 12 * SLOT + r * MT : 5 * SLOT; }
__device__ __forceinline__ int x_slot(int e, int s) { return NQ == 5 ? (e < 14 ? s : e - 11) : (e < 13 ? s : 3 + s); }
__device__ __forceinline__ uint32_t wo_slot(int i) { return (uint32_t)(WO_SLOTS >> (4 * i)) & 15u; }

__global__ void __launch_bounds__(512, 1)
fused_kernel(const __nv_bfloat16* __restrict__ x, const __nv_bfloat16* __restrict__ wqkv, const __nv_bfloat16* __restrict__ wo,
             const __nv_bfloat16* __restrict__ wr, const __nv_bfloat16* __restrict__ wd, const int by_sm,
             const __grid_constant__ CUtensorMap tmX, const __grid_constant__ CUtensorMap tmW,
             const __grid_constant__ CUtensorMap tmWo, const __grid_constant__ CUtensorMap tmOut,
             const __grid_constant__ CUtensorMap tmG, const __grid_constant__ CUtensorMap tmU,
             const __grid_constant__ CUtensorMap tmD, const __grid_constant__ CUtensorMap tmR,
             const __grid_constant__ CUtensorMap tmWp) {
  if (TMP && threadIdx.x == 32 * TMPW) { map_pf(&tmX); map_pf(&tmW); }
  extern __shared__ __align__(1024) uint8_t smem_raw[];
  const uint32_t sb = (uint32_t)__cvta_generic_to_shared(smem_raw);
  const uint32_t bars = sb + MISC + M_BAR;
  uint32_t smid;
  asm("mov.u32 %0, %%smid;" : "=r"(smid));
  const int tpc = smid >> 1;
  int cl = tpc + max(((tpc - 25) * 37) >> 8, 0);
  cl = tpc < 60 ? cl : cl - 1;
  cl = tpc < 62 ? cl : (tpc - 58) * 8;
  const int u = by_sm ? 2 * cl + (blockIdx.x & 1) : blockIdx.x;
  const int hg = (u >> 4) & 7, tb = u & 15;
  const int b = tb * 8 + hg;
  const int lane = threadIdx.x & 31;
  const int warp = __shfl_sync(~0u, threadIdx.x >> 5, 0);
  const int ltid = threadIdx.x;
  const int g = lane >> 2, t = lane & 3;
  const uint32_t d0 = (sb & 0x3FFFF) >> 4;
#define BAR(i) (bars + 8 * (i))
  TLS(0, 0);

  const int rank = u & 1;
  auto load_entry = [&](int e, int s) {
    const int k0 = kstep1(e, hg) * 64;
    mbar_expect_tx(BAR(B_FXQ + s), e < NF ? 2 * SLOT : SLOT);
    mbar_expect_tx(BAR(B_FKV + s), 2 * SLOT);
    tma2d(sb + x_slot(e, s) * SLOT, &tmX, k0, tb * 128, BAR(B_FXQ + s));
    if (e < MC0 || !(MC & 1)) {
      if (e < NF) tma3d(sb + (3 + s) * SLOT, &tmW, k0, 2 * hg, BAR(B_FXQ + s));
      tma3d(sb + (6 + 2 * s) * SLOT, &tmW, k0, 16 + 2 * hg, BAR(B_FKV + s));
      tma3d(sb + (7 + 2 * s) * SLOT, &tmW, k0, 32 + 2 * hg, BAR(B_FKV + s));
    } else {
      if (e < NF && (e & 1) == rank) tma3d_mc(sb + (3 + s) * SLOT, &tmW, k0, 2 * hg, BAR(B_FXQ + s));
      tma3d_mc(sb + (6 + 2 * s + rank) * SLOT, &tmW, k0, 16 + 16 * rank + 2 * hg, BAR(B_FKV + s));
    }
  };
  if (warp == FW && u < NCTA) {
    if (elect_one()) {
      mbar_init(BAR(B_FXQ), 1); mbar_init(BAR(B_FKV), 1);
      load_entry(0, 0);
      asm volatile("fence.mbarrier_init.release.cluster;" ::: "memory");
      TLS(FW * 32, 61);
    }
    __syncwarp();
  }
  if (u >= NCTA) {
    const int j = u - NCTA;
    if (warp == 8 && elect_one()) {
#pragma unroll
      for (int i = 0; i < 13; i++) mbar_init(BAR(i), 1);
    }
    if (ltid < 64) sts_u4(sb + MISC + ltid * 16, make_uint4(0x3F803F80u, 0x3F803F80u, 0x3F803F80u, 0x3F803F80u));
    fence_async_smem();
    __syncthreads();
    if (warp < 4) {
      int s = 0, p = 0;
#pragma unroll 1
      for (int pass = 0; pass < 3; pass++) {
        float acc[4][4];
#pragma unroll
        for (int c = 0; c < 4; c++) acc[c][0] = acc[c][1] = acc[c][2] = acc[c][3] = 0.f;
#pragma unroll 1
        for (int k = 0; k < 16; k++) {
          mbar_wait(BAR(s), p);
          wg_fence();
#pragma unroll
          for (int c = 0; c < 4; c++)
#pragma unroll
            for (int kk = 0; kk < 4; kk++)
              wgmma_ss_n8<1, 0>(acc[c], mkdesc((d0 + s * 2048 + c * 512 + kk * 128) | (512u << 16), HI_SW128), mkdesc((d0 + (MISC >> 4)) | (1u << 16), HI_SW128));
          wg_commit();
          wg_wait<0>();
          if (ltid == 0) mbar_arrive(BAR(6 + s));
          if (++s == SVS) { s = 0; p ^= 1; }
        }
        uint32_t* pc = G.cs + (pass < 2 ? DM + pass * DM : 0) + j * 256 + warp * 16 + g;
#pragma unroll
        for (int c = 0; c < 4; c++) {
          reg_fence(acc[c]);
          const uint32_t v = __float_as_uint((t & 1) ? acc[c][2] : acc[c][0]);
          if (t < 2) stx1(pc + c * 64 + t * 8, v ? v : 0x80000000u);
        }
        TLS(0, 1 + pass);
      }
    } else if (warp >= 8 && j == 0) {
      const int wq = warp - 8;
      const uint32_t top = sb + MISC + 1024;
#pragma unroll 1
      for (uint32_t it = 0; it < SPIN_MAX; it++) {
        const uint4 v0 = ldx4(G.key + wq * 256 + lane * 4), v1 = ldx4(G.key + wq * 256 + 128 + lane * 4);
        uint32_t ok;
        asm volatile("{\n.reg .pred p, q;\nsetp.ne.u32 p, %1, 0;\nbar.red.and.pred q, 2, 256, p;\nselp.b32 %0, 1, 0, q;\n}" : "=r"(ok) : "r"((v0.x & v0.y & v0.z & v0.w & v1.x & v1.y & v1.z & v1.w) >> 27) : "memory");
        ok = __any_sync(~0u, ok);
        if (!ok && it) continue;
        TLS(256, 4);
        uint32_t np = 0u - (1u << 28), mine = 0;
#pragma unroll 1
        for (int r = 0; r < 8; r++) {
          const uint32_t m0 = __viaddmax_u32(v0.x, np, v0.y + np), m1 = __viaddmax_u32(v0.z, np, v0.w + np), m2 = __viaddmax_u32(v1.x, np, v1.y + np), m3 = __viaddmax_u32(v1.z, np, v1.w + np);
          np -= __reduce_max_sync(~0u, max(max(m0, m1), max(m2, m3)));
          if (g == r) mine = 0u - np;
        }
        if (t == 0) sts_u(top + (wq * 8 + g) * 4, mine);
        bar_sync<2, 256>();
        TLS(256, 5);
        int rk = 0;
#pragma unroll
        for (int i = 0; i < 4; i++) {
          const uint4 o = lds_u4(top + t * 64 + i * 16);
          rk += (o.x > mine) + (o.y > mine) + (o.z > mine) + (o.w > mine);
        }
        rk += __shfl_xor_sync(~0u, rk, 1);
        rk += __shfl_xor_sync(~0u, rk, 2);
        if (ok) { if (rk < 8) stx1(G.top + t * 32 + rk, mine); break; }
        __nanosleep(2500);
      }
      TLS(256, 7);
    } else if (warp == 4) {
      int s = 0, p = 1;
      if (SVD) __nanosleep(SVD);
#pragma unroll 1
      for (int i = 0; i < 48; i++) {
        mbar_wait(BAR(6 + s), p);
        if (j == 0 && i >= SV0A && i < SV0B) mbar_wait(BAR(s >= SV0 ? s - SV0 : s - SV0 + SVS), s >= SV0 ? p ^ 1 : p);
        if (elect_one()) {
          mbar_expect_tx(BAR(s), 2 * SLOT);
          const int ch = (i < 32 ? 16 + (i & 16) : 0) + j * 4, k0 = (i & 15) * 64;
          tma3d(sb + s * 2 * SLOT, &tmW, k0, ch, BAR(s));
          tma3d(sb + s * 2 * SLOT + SLOT, &tmW, k0, ch + 2, BAR(s));
        }
        if (++s == SVS) { s = 0; p ^= 1; }
      }
    }
    if (ltid == 0) cnt_wait(C_DONE, NCTA);
    __syncthreads();
    const uint4 zero = make_uint4(0, 0, 0, 0);
    if (ltid < 128) reinterpret_cast<uint4*>(G.key)[j * 128 + ltid] = zero;
    else if (ltid < 320) reinterpret_cast<uint4*>(G.cs)[j * 192 + ltid - 128] = zero;
    else if (ltid < 322) reinterpret_cast<uint4*>(G.top)[j * 8 + ltid - 320] = zero;
    if (ltid == 0) { cnt_done(); TLDUMP(); }
    return;
  }

  if (warp == 12) {
    if (elect_one()) {
#pragma unroll
      for (int i = 1; i < 7; i++) if (i != B_FKV) mbar_init(BAR(i), 1);
      if (E1E) load_entry(1, 1);
      asm volatile("fence.mbarrier_init.release.cluster;" ::: "memory");
    }
  } else if (warp >= 13) {
    if (elect_one()) {
      if (warp == 15) {
#pragma unroll
        for (int i = B_FAUX; i < NBAR; i++) mbar_init(BAR(i), i < B_E || !MC ? 2 : 4);
        mbar_init(BAR(B_KV4), 4); mbar_init(BAR(B_MS), 2);
      } else {
#pragma unroll
        for (int i = 0; i < 23; i++) mbar_init(BAR((warp == 13 ? 7 : 30) + i), 1);
      }
      asm volatile("fence.mbarrier_init.release.cluster;" ::: "memory");
    }
  }
  __syncthreads();
  if (MC) asm volatile("barrier.cluster.arrive.relaxed.aligned;" ::: "memory");

  const bool unit = u < NUNIT;
  const int dcol = (u & 15) * 64, drow = (u >> 4) * 448;
  if (warp >= 12) {
    asm volatile("setmaxnreg.dec.sync.aligned.u32 %0;" ::"n"(PROD_REGS));
    if (MC && warp != 12) asm volatile("barrier.cluster.wait.aligned;" ::: "memory");
    if (warp == 12) {
      int s = 1 + E1E, p = 1, pn = 3;
#pragma unroll 1
      for (int e = 1 + E1E; e < 16; e++) {
        if (MC && e == MC0) asm volatile("barrier.cluster.wait.aligned;" ::: "memory");
        if (e == GATE) mbar_wait(BAR(B_FXQ), 0);
        mbar_wait(BAR(B_E + s), p);
        if (elect_one()) {
          load_entry(e, s);
          if (NR == 4 && e == 11) mbar_arrive(BAR(B_ME + 3));
          if (e == ASTE) {
            mbar_expect_tx(BAR(B_AST), 2 * SLOT + 2048);
            bulk_ld(sb + 12 * SLOT, x + (size_t)b * 16 * DM, 2 * SLOT, BAR(B_AST));
            bulk_ld(sb + MISC + M_MOE, wr, 2048, BAR(B_AST));
          } else if (e >= 3) {
            if (e < 6) bulk_pf(wqkv + (size_t)((e - 2) * 256 + 2 * b) * 3 * DM, 2 * 3 * DM * 2);
            if (e < 7) bulk_pf(wo + (size_t)((e - 3) * 256 + 2 * b) * DM, 2 * DM * 2);
            if (NUNIT) {
#pragma unroll 1
              for (int i = (PFTAB >> (4 * (e - 3))) & 15; i > 0; i--, pn++) {
                if (pn >= 16) { if (!(MX & 8)) tma2d_pf(&tmD, dcol, drow + (pn - 16) * 64); }
                else if (unit && !(MX & 2)) tma2d_pf(rank ? &tmU : &tmG, (u >> 1) * 64, pn * 64);
              }
            }
          }
        }
        if (++s == 3) { s = 0; p ^= 1; }
      }
#pragma unroll 1
      for (int k = 0; k < NQ; k++) {
        if (k == 0) mbar_wait(BAR(B_E + 1), 0);
        if (k == 2) mbar_wait(BAR(B_E + 2), 0);
        if (k == 3) mbar_wait(BAR(B_E + 0), 1);
        if (k == 4) mbar_wait(BAR(B_STG), 0);
        if (elect_one()) {
          const int k0 = kstep1(NF + k, hg) * 64;
          mbar_expect_tx(BAR(B_FQ + k), SLOT);
          if (!(MC & 2)) tma3d(sb + ((QW_SLOTS >> (4 * k)) & 15u) * SLOT, &tmW, k0, 2 * hg, BAR(B_FQ + k));
          else if ((k & 1) == rank) tma3d_mc(sb + ((QW_SLOTS >> (4 * k)) & 15u) * SLOT, &tmW, k0, 2 * hg, BAR(B_FQ + k));
        }
      }
#pragma unroll 1
      for (int i = 0; i < 16; i++) {
        mbar_wait(i < 7 ? BAR(B_EQ + ((i + WQ0) >> 1)) : (i < 9 ? BAR(B_DE) : BAR(B_EO + i - 9)), 0);
        if (i == WOK) mbar_wait(BAR(B_KVB), 0);
        mbar_wait(BAR(B_FWO + i - (i < WOK ? WOD1 : WOD)), 0);
        if (elect_one()) {
          mbar_expect_tx(BAR(B_FWO + i), SLOT);
#pragma unroll
          for (int hf = 0; hf < ((MC & 4) ? 1 : 2); hf++) {
            const int n = 2 * i + ((MC & 4) ? rank : hf), m = slab(n - 4, hg), hd = n < 4 ? 4 * hg + n : 4 * (m & 7) + (m >> 3);
            if (i < 2 + NDIR) tma5d(sb + wo_slot(i) * SLOT + (n & 1) * 8192, &tmWp, hd * 4, 2 * hg, BAR(B_FWO + i), MC & 4);
            else if (MC & 4) tma3d_mc(sb + wo_slot(i) * SLOT + rank * 8192, &tmWo, hd * 32, 2 * hg, BAR(B_FWO + i));
            else tma3d(sb + wo_slot(i) * SLOT + hf * 8192, &tmWo, hd * 32, 2 * hg, BAR(B_FWO + i));
          }
        }
      }
    } else if (warp == 13) {
      if (elect_one()) {
        map_pf(rank ? &tmU : &tmG); map_pf(&tmR); map_pf(&tmD); map_pf(&tmWo); map_pf(&tmWp); map_pf(&tmOut);
      }
      bar_sync<6, 64>();
      if (elect_one()) {
        cnt_wait(C_B, NCTA);
        fence_async_gmem();
        mbar_expect_tx(BAR(B_FAUX), 1024);
        bulk_ld(sb + A_ST, G.stats + tb * 128, 1024, BAR(B_FAUX));
      }
      __syncwarp();
      TLS(416, 68);
#pragma unroll 1
      for (int m = 1; m < 4; m++) {
        const int part = m == 3 ? 0 : m;
        uint4 c;
#pragma unroll 1
        for (uint32_t it = 0; it < SPIN_MAX; it++) {
          c = ldx4(G.cs + part * DM + hg * 128 + lane * 4);
          if (__all_sync(~0u, min(min(c.x, c.y), min(c.z, c.w)))) break;
          __nanosleep(POLLNS);
        }
        sts_u4(sb + A_CS + part * 512 + lane * 16, c);
        __syncwarp();
        if (m > 1 && lane == 0) mbar_arrive(BAR(m == 2 ? B_FAUX : B_CQ));
        TLS(416, 71 + m);
      }
      mbar_wait(BAR(B_XS), 1);
      if (elect_one()) asm volatile("red.relaxed.gpu.global.add.u32 [%0], 1;" ::"l"(&G.cnt[C_DONE]) : "memory");
    } else if (warp == 14) {
      const uint4 sent = make_uint4(SENT, SENT, SENT, SENT);
      uint4* ro = G.o + (tb * 32 + hg) * 512 + lane;
      uint4* rp = G.part + b * 544 + lane;
      if (RSL) bar_sync<5, 160>(); else mbar_wait(BAR(B_AST), 0);
#pragma unroll 1
      for (int i = RS0; i < 40; i++) {
        uint4* q = i < 32 ? ro + (i >> 3) * 4096 + (i & 7) * 64 : rp + (i - 32) * 64;
        q[0] = sent; q[32] = sent;
        __nanosleep(RSNS);
      }
      rp[512] = sent;
#pragma unroll
      for (int i = 0; i < 4; i++) G.y[u * 128 + i * 32 + lane] = sent;
      if (unit) reinterpret_cast<uint4*>(G.h)[u * 32 + lane] = sent;
      G.fin[hg * 640 + tb * 40 + lane] = sent;
      if (lane < 8) G.fin[hg * 640 + tb * 40 + 32 + lane] = sent;
      if (!RSL) bar_sync<5, 160>();
      __syncwarp();
      TLS(448, 67);
      if (lane == 0) cnt_arrive(C_B);
      __syncwarp();
      TLS(448, 32);
      asm volatile("bar.arrive 6, 64;" ::: "memory");
    } else {
      const uint32_t stg = sb + 12 * SLOT;
      auto load_a = [&](int n, int r) {
        mbar_expect_tx(BAR(B_MF + r), (MX & 2) ? 1024 : MT);
        if (!(MX & 2)) tma2d_ef(sb + m_off(r), rank ? &tmU : &tmG, (u >> 1) * 64, n * 64, BAR(B_MF + r));
      };
      mbar_wait(BAR(B_XS), 0);
      if (unit) {
#pragma unroll 1
        for (int i = 0; i < 3; i++) {
          if (elect_one()) load_a(i, i);
          __nanosleep(PFILL);
        }
      }
      uint32_t key;
#pragma unroll 1
      for (uint32_t it = 0; it < SPIN_MAX; it++) {
        key = ldx1(G.top + ((u >> 1) & 3) * 32 + (lane & 7));
        if (__all_sync(~0u, key)) break;
        __nanosleep(TPNS);
      }
      TLS(480, 66);
      if (lane < 8) sts_u(sb + MISC + M_IDX + lane * 4, key);
      __syncwarp();
      if (lane == 0) mbar_arrive(BAR(B_XS));
      if (unit) {
        int tok[8];
#pragma unroll
        for (int i = 0; i < 8; i++) tok[i] = ~__shfl_sync(~0u, key, i) & 2047;
        int r = 0, p = 0;
#pragma unroll 1
        for (int n = 0; n < 16; n++) {
          if (n >= 3) mbar_wait(BAR(B_ME + r), r == 3 ? p : p ^ 1);
          if (elect_one()) {
            if (n >= 3) load_a(n, r);
#pragma unroll
            for (int i = 0; i < 8; i++) tma2d(sb + m_off(r) + 8192 + i * 128, &tmR, n * 64, tok[i], BAR(B_MF + r));
          }
          if (++r == NR) { r = 0; p ^= 1; }
        }
      }
      if (NUNIT) {
        if (lane == 0) mbar_expect_tx(BAR(B_DF), (MX & 8) ? 0 : 7 * 8192);
#pragma unroll 1
        for (int i = 0; i < 7; i++) {
          if (NR == 4) {
            if (i >= 3) mbar_wait(i < 5 ? BAR(B_ME + 3) : BAR(B_STG), 0);
            else if (unit) mbar_wait(BAR(B_ME + i), 1);
          } else {
            if (i >= 3) mbar_wait(BAR(B_EQ + ((i - 3) >> 1)), 0);
            else if (unit) mbar_wait(BAR(B_ME + (i == 2 ? 0 : i + 1)), i == 2);
          }
          if (!(MX & 8) && elect_one()) tma2d_ef(sb + d_off(i), &tmD, dcol, drow + i * 64, BAR(B_DF));
          if (DNS) __nanosleep(DNS);
        }
      }
    }
    if (warp == 14) {
      if (DPF && NUNIT && !(MX & 8)) {
        mbar_wait(DS ? BAR(B_MS) : (DPF == 1 ? BAR(B_FQ) : BAR(B_T0)), 0);
#pragma unroll 1
        for (int pf = 0; pf < 7; pf++) { pf256(sb + MISC + M_DUM, wd + (size_t)(drow + pf * 64 + rank * 32 + lane) * DM + (dcol & ~127)); __nanosleep(PFNS2); }
      }
      const uint32_t* src = reinterpret_cast<const uint32_t*>(G.part + ((lane >> 3) * 32 + hg) * 544 + 512) + tb * 8 + (lane & 7);
      mbar_wait(BAR(B_EQ + MRW), 0);
      if (MRD) __nanosleep(MRD);
      uint32_t z0, z1, z2, z3;
#pragma unroll 1
      for (uint32_t it = 0; it < SPIN_MAX; it++) {
        z0 = ldx1(src); z1 = ldx1(src + 8 * 2176); z2 = ldx1(src + 16 * 2176); z3 = ldx1(src + 24 * 2176);
        if (!__any_sync(~0u, max(max(z0, z1), max(z2, z3)) == SENT)) break;
      }
      if (MRED == 2 && elect_one()) mbar_arrive(BAR(B_ZOK));
      float zz = (__uint_as_float(z0) + __uint_as_float(z1)) + (__uint_as_float(z2) + __uint_as_float(z3));
      zz += __shfl_xor_sync(~0u, zz, 8);
      zz += __shfl_xor_sync(~0u, zz, 16);
      stx1(reinterpret_cast<uint32_t*>(G.fin + hg * 640) + (tb >> 2) * 640 + 512 + ((tb >> 1) & 1) * 64 + (lane & 1) * 32 + (tb & 1) * 16 + ((lane & 7) >> 1) * 4 + (lane >> 3),
           pack_bf16(zz, zz));
      TLS(448, 12);
    }
    if (!MFIN && (warp == 13 || warp == 14)) {
      mbar_wait(BAR(B_EQ + H2W), 0);
      if (H2D) __nanosleep(H2D);
#pragma unroll 1
      for (uint32_t it = 0; it < SPIN_MAX; it++) {
        if (warp == 14 && elect_one()) { mbar_expect_tx(BAR(B_FIN), 10240); bulk_ld(sb + S_KVB * SLOT, G.fin + hg * 640, 10240, BAR(B_FIN)); }
        mbar_wait(BAR(B_FIN), it & 1);
        uint32_t m = 0;
#pragma unroll
        for (int i = 0; i < 10; i++) m = max(m, lds_u(sb + S_KVB * SLOT + (i * 64 + ltid - 416) * 16 + (g >> 1) * 4));
        uint32_t bad;
        asm volatile("{\n.reg .pred p, q;\nsetp.eq.u32 p, %1, 0xFFFFFFFF;\nbar.red.or.pred q, 7, 64, p;\nselp.b32 %0, 1, 0, q;\n}" : "=r"(bad) : "r"(m) : "memory");
        if (!__any_sync(~0u, bad)) break;
      }
      if (warp == 14 && elect_one()) mbar_arrive(BAR(B_KVB));
      TLS(448, 14);
    }
    if (PH && (warp == 13 || warp == 14)) {
      bar_sync<3, 192>();
      mbar_wait(BAR(B_STG), 0);
#pragma unroll 1
      for (uint32_t it = 0; NUNIT && it < SPIN_MAX; it++) {
        if (elect_one()) {
          const uint32_t* ph = G.h + (u >> 4) * 7 * 256;
          if (warp == 13) { mbar_expect_tx(BAR(B_HF), 7168); bulk_ld(sb + h_off(3), ph + 768, 2048, BAR(B_HF)); bulk_ld(sb + h_off(5), ph + 1280, 2048, BAR(B_HF)); }
          else { bulk_ld(sb + h_off(0), ph, 1024, BAR(B_HF)); bulk_ld(sb + h_off(1), ph + 256, 1024, BAR(B_HF)); bulk_ld(sb + h_off(2), ph + 512, 1024, BAR(B_HF)); }
        }
        mbar_wait(BAR(B_HF), it & 1);
        uint32_t m = 0;
#pragma unroll
        for (int i = 0; i < 7; i++) m = max(m, lds_u(sb + h_off(i) + (ltid - 416) * 16 + (g >> 1) * 4));
        uint32_t bad;
        asm volatile("{\n.reg .pred p, q;\nsetp.eq.u32 p, %1, 0xFFFFFFFF;\nbar.red.or.pred q, 7, 64, p;\nselp.b32 %0, 1, 0, q;\n}" : "=r"(bad) : "r"(m) : "memory");
        if (!__any_sync(~0u, bad)) break;
        __nanosleep(POLLNS);
      }
      if (warp == 14 && elect_one()) mbar_arrive(BAR(B_KVB));
    }
    __syncwarp();
    if (warp >= 13) {
      const char* og = reinterpret_cast<const char*>(G.o + tb * 16384);
      auto probe = [&](uint32_t m) {
        const char* p = og + m * 8192u + (lane & 15) * 512 + 496;
#pragma unroll 1
        for (uint32_t it = 0; it < SPIN_MAX; it++)
          if (!__any_sync(~0u, ldx1(p) == SENT)) break;
      };
      if (warp == 15) {
        int r = 0, p = 1;
        mbar_wait(BAR(B_EAUX), 0);
#pragma unroll 1
        for (int i = I0; i < 16; i++) {
          const uint32_t dst = sb + ((A_SLOTS >> (4 * r)) & 15u) * SLOT, m0 = slab(2 * i - 4, hg), m1 = slab(2 * i - 3, hg);
          if (i == I0 + 3) mbar_wait(BAR(B_DE), 0);
          mbar_wait(BAR(B_EA + r), p);
          if ((PROBE >> i) & 1) probe(lane < 16 ? m0 : m1);
          if (elect_one()) {
            mbar_expect_tx(BAR(B_AF + r), SLOT);
            bulk_ld(dst, og + m0 * 8192u, 8192, BAR(B_AF + r)); bulk_ld(dst + 8192, og + m1 * 8192u, 8192, BAR(B_AF + r));
          }
          if (++r == NA) { r = 0; p ^= 1; }
        }
      } else {
        const uint32_t lo = lane * 32 + g * 4, hb = sb + (warp - 13) * 8192;
        uint32_t ph = 0;
        int r = 0, p = 0;
#pragma unroll 1
        for (int i = I0; i < 16; i++) {
          const uint32_t mine = hb + ((A_SLOTS >> (4 * r)) & 15u) * SLOT;
          auto bad = [&]() {
            uint32_t v[8];
#pragma unroll
            for (int j = 0; j < 8; j++) v[j] = lds_u(mine + lo + j * 1024);
            return __any_sync(~0u, max(max(max(v[0], v[1]), max(v[2], v[3])), max(max(v[4], v[5]), max(v[6], v[7]))) == SENT);
          };
          mbar_wait(BAR(B_AF + r), p);
          if (!NOVAL && bad()) {
            const uint32_t m = slab(2 * i - 17 + warp, hg);
#pragma unroll 1
            for (uint32_t it = 0; it < 64; it++) {
              probe(m);
              if (elect_one()) { mbar_expect_tx(BAR(B_AR + warp - 13), 8192); bulk_ld(mine, og + m * 8192u, 8192, BAR(B_AR + warp - 13)); }
              mbar_wait(BAR(B_AR + warp - 13), ph);
              ph ^= 1;
              if (!bad()) break;
            }
          }
          if (elect_one()) mbar_arrive(BAR(B_VAL + r));
          if (++r == NA) { r = 0; p ^= 1; }
        }
      }
    }
  } else if (warp >= 8) {
    asm volatile("setmaxnreg.dec.sync.aligned.u32 %0;" ::"n"(MOE_REGS));
    if (MC) asm volatile("barrier.cluster.wait.aligned;" ::: "memory");
    const int aw = warp - 8;
    const uint32_t mbuf = sb + MISC + M_MOE, stg = sb + 12 * SLOT;
    mbar_wait(BAR(B_AST), 0);
    TLS(288, 64);
    {
      float v[16];
#pragma unroll
      for (int r = 0; r < 16; r++) v[r] = 0.f;
      const uint32_t base = stg + aw * 4 * 2048 + lane * 8;
#pragma unroll 1
      for (int c = 0; c < 8; c++) {
        const float2 w2 = lds_f2(mbuf + c * 256 + lane * 8);
        const float w[4] = {bf_lo(__float_as_uint(w2.x)), bf_hi(__float_as_uint(w2.x)), bf_lo(__float_as_uint(w2.y)), bf_hi(__float_as_uint(w2.y))};
        v[12] += (w[0] + w[1]) + (w[2] + w[3]);
#pragma unroll
        for (int r = 0; r < 4; r++) {
          const float2 x2 = lds_f2(base + r * 2048 + c * 256);
#pragma unroll
          for (int e = 0; e < 2; e++) {
            const uint32_t xx = __float_as_uint(e ? x2.y : x2.x);
            const float lo = bf_lo(xx), hi = bf_hi(xx);
            v[r] += lo; v[4 + r] = fmaf(lo, lo, v[4 + r]); v[8 + r] = fmaf(lo, w[2 * e], v[8 + r]);
            v[r] += hi; v[4 + r] = fmaf(hi, hi, v[4 + r]); v[8 + r] = fmaf(hi, w[2 * e + 1], v[8 + r]);
          }
        }
      }
#pragma unroll
      for (int l = 0; l < 4; l++) {
        const int n = 8 >> l;
        const bool up = lane & (2 * n);
#pragma unroll
        for (int r = 0; r < 8; r++) {
          if (r < n) { const float a = v[r], c = v[n + r]; v[r] = (up ? c : a) + __shfl_xor_sync(~0u, up ? a : c, 2 * n); }
        }
      }
      v[0] += __shfl_xor_sync(~0u, v[0], 1);
      const float sx = __shfl_sync(~0u, v[0], 2 * t), sq = __shfl_sync(~0u, v[0], 8 + 2 * t), sw = __shfl_sync(~0u, v[0], 16 + 2 * t), ws = __shfl_sync(~0u, v[0], 24);
      if (lane < 4) {
        const int row = b * 16 + aw * 4 + lane;
        const float mean = sx * (1.f / DM);
        const float var = fmaxf(fmaf(-mean, mean, sq * (1.f / DM)), 0.f);
        float sd;
        asm("sqrt.approx.ftz.f32 %0, %1;" : "=f"(sd) : "f"(bf_round(bf_round(var) + 1e-5f)));
        const float rstd = rcp(bf_round(sd));
        const float mb = bf_round(mean);
        uint32_t rb = pack_bf16(fmaf(-mb, ws, sw) * rstd, 0.f) & 0xFFFFu;
        rb = (rb & 0x8000u) ? (~rb & 0xFFFFu) : (rb | 0x8000u);
        const uint32_t key = (1u << 27) | (rb << 11) | (uint32_t)(2047 - row);
        if (KEY1) sts_u(sb + MISC + M_KEY + (aw * 4 + lane) * 4, key); else stx1(G.key + row, key);
        G.stats[row] = make_float2(mb, rstd);
      }
    }
    bar_sync<2, 128>();
    if (KEY1 && ltid < 272) stx1(G.key + b * 16 + lane, lds_u(sb + MISC + M_KEY + lane * 4));
    TLS(288, 65);
    sts_u4(sb + A_ONES + (ltid - 256) * 16, make_uint4(0x3F803F80u, 0x3F803F80u, 0x3F803F80u, 0x3F803F80u));
    fence_async_smem();
    asm volatile("bar.arrive 5, 160;" ::: "memory");
    if (ltid == 256) { if (unit && rank == 0) mbar_expect_tx(BAR(B_UP), 2048); mbar_arrive(BAR(B_XS)); }
    bar_sync<2, 128>();
    mbar_wait(BAR(B_XS), 1);
    TLS(288, 70);
    if (NUNIT) {
      if (unit) {
        int r = 0, p = 0;
        uint32_t rel = 0;
        float acc[8];
        uint2 s0, s1;
#pragma unroll
        for (int i = 0; i < 8; i++) acc[i] = 0.f;
        if (MS == 16) mbar_wait(BAR(B_T0), 0); else if (MS) mbar_wait(BAR(B_MS), 0);
#pragma unroll 1
        for (int n = 0; n < 16; n++) {
          if (n == 15) {
            mbar_wait(BAR(B_FAUX), 0);
            s0 = ldx2(G.stats + (~lds_u(sb + MISC + M_IDX + t * 8) & 2047)); s1 = ldx2(G.stats + (~lds_u(sb + MISC + M_IDX + t * 8 + 4) & 2047));
          }
          mbar_wait(BAR(B_MF + r), p);
          if (!(n & 3)) TLS(288, 56 + (n >> 2));
          const uint32_t mo = m_off(r) >> 4, da = (d0 + mo) | (512u << 16), db = (d0 + mo + 512) | (1u << 16);
          const uint32_t hb = 0x40000000u | ((A_ONES >> 4) - 512 - mo);
          wg_fence();
#pragma unroll
          for (int kk = 0; kk < ((MX & 1) ? 1 : 4); kk++) wgmma_ss_n16<1, 0>(acc, mkdesc(da + kk * 128, HI_SW128), mkdesc(db + kk * 2, hb));
          wg_commit();
          wg_wait<1>();
          if (n > 0 && !rel && ltid == 256) mbar_arrive(BAR(B_ME + (r == 0 ? NR - 1 : r - 1)));
          rel = 0;
          const int r0 = r;
          if (++r == NR) { r = 0; p ^= 1; }
        }
        wg_wait<0>();
        reg_fence(acc);
        {
          if (!MW0 && !rel && ltid == 256) mbar_arrive(BAR(B_ME + 15 % NR));
          TLS(288, 71);
          const float v0 = bf_round(fmaf(-__uint_as_float(s0.x), acc[4], acc[0]) * __uint_as_float(s0.y));
          const float v1 = bf_round(fmaf(-__uint_as_float(s1.x), acc[4], acc[1]) * __uint_as_float(s1.y));
          const float v2 = bf_round(fmaf(-__uint_as_float(s0.x), acc[6], acc[2]) * __uint_as_float(s0.y));
          const float v3 = bf_round(fmaf(-__uint_as_float(s1.x), acc[6], acc[3]) * __uint_as_float(s1.y));
          if (rank) {
            asm volatile("{\n.reg .b32 ra, rb;\nmapa.shared::cluster.u32 ra, %0, 0;\nmapa.shared::cluster.u32 rb, %1, 0;\n"
                         "st.async.weak.shared::cluster.mbarrier::complete_tx::bytes.v4.f32 [ra], {%2, %3, %4, %5}, [rb];\n}"
                         ::"r"(mbuf + (ltid - 256) * 16), "r"(BAR(B_UP)), "f"(v0), "f"(v1), "f"(v2), "f"(v3) : "memory");
          } else {
            const float g0 = bf_round(v0 * sigmoid(v0)), g1 = bf_round(v1 * sigmoid(v1)), g2 = bf_round(v2 * sigmoid(v2)), g3 = bf_round(v3 * sigmoid(v3));
            mbar_wait(BAR(B_UP), 0);
            const uint4 uu = lds_u4(mbuf + (ltid - 256) * 16);
            const uint32_t h0 = movmat(pack_bf16(g0 * __uint_as_float(uu.x), g1 * __uint_as_float(uu.y)));
            const uint32_t h1 = movmat(pack_bf16(g2 * __uint_as_float(uu.z), g3 * __uint_as_float(uu.w)));
            uint32_t* ph = G.h + (u >> 1) * 256 + g * 32 + t;
            stx1(ph + ((2 * aw) ^ g) * 4, h0); stx1(ph + ((2 * aw + 1) ^ g) * 4, h1);
          }
          TLS(288, 60);
        }
      }
    }
    if (PH) asm volatile("bar.arrive 3, 192;" ::: "memory");
    {
      const int wd_ = ltid & 63;
      const uint32_t* src = reinterpret_cast<const uint32_t*>(G.part + hg * 544 + (aw >> 1) * 256 + tb * 16) + wd_;
      mbar_wait(MRED == 2 ? BAR(B_ZOK) : BAR(B_EQ + MRW), 0);
      if (MRD) __nanosleep(MRD);
      TLS(256, 48);
      uint32_t v[16];
#pragma unroll 1
      for (uint32_t it = 0; it < SPIN_MAX; it++) {
        uint32_t m = 0;
#pragma unroll
        for (int i = 0; i < 16; i++) v[i] = ldx1(src + i * 8 * 2176);
#pragma unroll
        for (int i = 0; i < 16; i++) m = max(m, v[i]);
        if (!__any_sync(~0u, m == SENT)) break;
      }
      TLS(256, 55);
      float lo[4], hi[4];
#pragma unroll
      for (int i = 0; i < 4; i++) {
        lo[i] = (bf_lo(v[4 * i]) + bf_lo(v[4 * i + 1])) + (bf_lo(v[4 * i + 2]) + bf_lo(v[4 * i + 3]));
        hi[i] = (bf_hi(v[4 * i]) + bf_hi(v[4 * i + 1])) + (bf_hi(v[4 * i + 2]) + bf_hi(v[4 * i + 3]));
      }
      stx1(reinterpret_cast<uint32_t*>(G.fin + hg * 640) + (tb >> 2) * 640 + ((tb >> 1) & 1) * 64 + (tb & 1) * 16 + (aw >> 1) * 32 + ((wd_ >> 2) & 3) * 128 + (wd_ >> 4) * 4 + (wd_ & 3),
           pack_bf16((lo[0] + lo[1]) + (lo[2] + lo[3]), (hi[0] + hi[1]) + (hi[2] + hi[3])));
      TLS(256, 5);
    }
    if (NUNIT) {
      mbar_wait(BAR(B_STG), 0);
      bar_sync<2, 128>();
      if (HW) __nanosleep(HW);
#pragma unroll 1
      for (uint32_t it = 0; it < SPIN_MAX; it++) {
        if (elect_one()) {
          const uint32_t* ph = G.h + (u >> 4) * 7 * 256;
          if (aw == 3) { mbar_expect_tx(BAR(B_HF), 7168); bulk_ld(sb + h_off(3), ph + 768, 2048, BAR(B_HF)); bulk_ld(sb + h_off(5), ph + 1280, 2048, BAR(B_HF)); }
          else bulk_ld(stg + aw * MT + 8192, ph + aw * 256, 1024, BAR(B_HF));
        }
        mbar_wait(BAR(B_HF), it & 1);
        const uint32_t o = (ltid & 63) * 16 + (g >> 1) * 4, o2 = o + (aw >> 1) * 1024;
        const uint32_t m = max(max(lds_u(sb + h_off(0) + (aw >> 1) * MT + o), lds_u(sb + h_off(2) + o)), max(lds_u(sb + h_off(3) + o2), lds_u(sb + h_off(5) + o2)));
        uint32_t bad;
        asm volatile("{\n.reg .pred p, q;\nsetp.eq.u32 p, %1, 0xFFFFFFFF;\nbar.red.or.pred q, 2, 128, p;\nselp.b32 %0, 1, 0, q;\n}" : "=r"(bad) : "r"(m) : "memory");
        if (!__any_sync(~0u, bad)) break;
        __nanosleep(POLLNS);
      }
      TLS(288, 62);
      float acc[4] = {0.f, 0.f, 0.f, 0.f};
      mbar_wait(BAR(B_DF), 0);
      TLS(288, 63);
#pragma unroll 1
      for (int i = 0; i < 7; i++) {
        const uint32_t da = (d0 + (d_off(i) >> 4)) | (512u << 16), db = (d0 + (h_off(i) >> 4)) | (1u << 16);
        wg_fence();
#pragma unroll
        for (int kk = 0; kk < ((MX & 4) ? 1 : 4); kk++) wgmma_ss_n8<1, 0>(acc, mkdesc(da + kk * 128, HI_SW128), mkdesc(db + kk * 2, HI_SW128));
        wg_commit();
      }
      wg_wait<0>();
      reg_fence(acc);
      if (ltid < 258) { if (MC) mbar_arrive_cta(BAR(B_DE), ltid & 1); else mbar_arrive(BAR(B_DE)); }
      {
        uint32_t* py = reinterpret_cast<uint32_t*>(G.y) + u * 512 + t * 128 + aw * 16 + g;
        stx1(py, f2x(acc[0])); stx1(py + 64, f2x(acc[1])); stx1(py + 8, f2x(acc[2])); stx1(py + 72, f2x(acc[3]));
      }
      TLS(288, 69);
      const uint32_t key = lds_u(sb + MISC + M_IDX + (lane & 7) * 4);
      uint32_t rb = (key >> 11) & 0xFFFFu;
      rb = (rb & 0x8000u) ? (rb & 0x7FFFu) : (~rb & 0xFFFFu);
      const float sg = bf_round(sigmoid(__uint_as_float(rb << 16)));
      uint32_t hits = __ballot_sync(~0u, ((~key >> 7) & 15) == tb) & 255u;
      const uint32_t* py = reinterpret_cast<const uint32_t*>(G.y) + (2 * hg + (aw >> 1)) * 512 + (ltid & 63);
      if (hits) {
        sts_u4(mbuf + (ltid - 256) * 16, make_uint4(0, 0, 0, 0));
        bar_sync<2, 128>();
        if (YW >= 0) mbar_wait(BAR(B_EO + YW), 0); else if (YW == -2) mbar_wait(BAR(B_EAUX), 0);
      }
#pragma unroll 1
      while (hits) {
        const int n0 = __ffs(hits) - 1;
        hits &= hits - 1;
        const int n1 = hits ? __ffs(hits) - 1 : n0;
        hits &= hits - 1;
        uint32_t v[16];
#pragma unroll 1
        for (uint32_t it = 0; it < SPIN_MAX; it++) {
          uint32_t m = 0;
#pragma unroll
          for (int i = 0; i < 8; i++) { v[i] = ldx1(py + n0 * 64 + i * 8192); v[8 + i] = ldx1(py + n1 * 64 + i * 8192); }
#pragma unroll
          for (int i = 0; i < 16; i++) m = max(m, v[i]);
          if (!__any_sync(~0u, m == SENT)) break;
          __nanosleep(POLLNS);
        }
#pragma unroll
        for (int e = 0; e < 2; e++) {
          const uint32_t* w8 = v + 8 * e;
          const float y = ((__uint_as_float(w8[0]) + __uint_as_float(w8[1])) + (__uint_as_float(w8[2]) + __uint_as_float(w8[3]))) +
                          ((__uint_as_float(w8[4]) + __uint_as_float(w8[5])) + (__uint_as_float(w8[6]) + __uint_as_float(w8[7])));
          const int n = e ? n1 : n0;
          sts_h(mbuf + (aw >> 1) * 1024 + n * 128 + ((((ltid >> 3) & 7) ^ n) << 4) + (lane & 7) * 2, bf_round(y) * __shfl_sync(~0u, sg, n));
        }
      }
    }
    if (!NUNIT && ltid < 258) mbar_arrive(BAR(B_DE));
    fence_async_smem();
    bar_sync<2, 128>();
    TLS(288, 33);
    if (ltid == 288) mbar_arrive(BAR(B_MOE));
  } else {
    asm volatile("setmaxnreg.inc.sync.aligned.u32 %0;" ::"n"(CON_REGS));
    if (MC) asm volatile("barrier.cluster.wait.aligned;" ::: "memory");
    const int w = warp >> 2, wq = warp & 3, tid = ltid;
    const bool lead = (tid & 127) == 0;
    const uint32_t dA = (d0 + w * 512) | (1u << 16);
    const uint32_t dB = d0 | (512u << 16);
    auto release = [&](int bar) { if (lead) mbar_arrive(BAR(bar)); };
    auto release2 = [&](int bar) {
      if (MC) { if ((tid & 127) < 2) mbar_arrive_cta(BAR(bar), tid & 1); } else release(bar);
    };
    float aq[64], ak[64], av[64];
#pragma unroll
    for (int i = 0; i < 64; i++) aq[i] = ak[i] = av[i] = 0.f;
    auto q_step = [&](uint32_t bar, int p, uint32_t xs, uint32_t qs) {
      mbar_wait_b(bar, p);
      wg_fence();
#pragma unroll
      for (int kk = 0; kk < 4; kk++)
        wgmma_ss_n128<0, 1>(aq, mkdesc(dA + xs * 1024 + kk * 2, HI_SW128), mkdesc(dB + qs * 1024 + kk * 128, HI_SW128));
      wg_commit();
    };
    const uint32_t dT = dB + w * 512, dX = d0 | (1u << 16);
    auto t_step = [&](float (&a)[64], uint32_t ws, uint32_t xs) {
      wg_fence();
#pragma unroll
      for (int kk = 0; kk < 4; kk++)
        wgmma_ss_n128<1, 0>(a, mkdesc(dT + ws * 1024 + kk * 128, HI_SW128), mkdesc(dX + xs * 1024 + kk * 2, HI_SW128));
      wg_commit();
    };
    {
      int s = 0, p = 0, sp = 2;
#pragma unroll 1
      for (int e = 0; e < NF; e++) {
        TLS(0, 16 + e);
        if (((MS && MS < NF) || (DS && DS < NF)) && e == (MS ? MS : DS)) release(B_MS);
        q_step(BAR(B_FXQ + s), p, s, 3 + s);
        wg_wait<1>();
        if (e > 0) release2(B_E + sp);
        mbar_wait(BAR(B_FKV + s), p);
        t_step(ak, 6 + 2 * s, s); t_step(av, 7 + 2 * s, s);
        sp = s;
        if (++s == 3) { s = 0; p ^= 1; }
      }
#pragma unroll 1
      for (int e = NF; e < 16; e++) {
        TLS(0, 16 + e);
        if (((MS >= NF && MS < 16) || DS >= NF) && e == (MS ? MS : DS)) release(B_MS);
        mbar_wait(BAR(B_FXQ + s), p);
        mbar_wait(BAR(B_FKV + s), p);
        t_step(ak, 6 + 2 * s, x_slot(e, s));
        wg_wait<1>();
        release2(B_E + sp);
        t_step(av, 7 + 2 * s, x_slot(e, s));
        sp = s;
        if (++s == 3) { s = 0; p ^= 1; }
      }
    }
    const uint32_t aux = sb;
    mbar_wait(BAR(B_FAUX), 0);
    const int row0 = w * 64 + wq * 16 + g;
    const float ck0 = lds_f(aux + A_CS + 512 + row0 * 4), ck1 = lds_f(aux + A_CS + 512 + (row0 + 8) * 4);
    const float cv0 = lds_f(aux + A_CS + 1024 + row0 * 4), cv1 = lds_f(aux + A_CS + 1024 + (row0 + 8) * 4);
    const uint32_t moff = (uint32_t)(w * 64 + wq * 16 + (lane & 15)) * 128 + (((lane >> 4) ^ (lane & 7)) << 4);
    const uint32_t sta = aux + A_ST + t * 16;
    float kvp[36], ao[64];
    uint32_t xr[32];
    float nm0, nm1, rs0, rs1;
    auto row_stats = [&]() {
      const float2 st0 = lds_f2(aux + A_ST + row0 * 8), st1 = lds_f2(aux + A_ST + (row0 + 8) * 8);
      nm0 = -st0.x; nm1 = -st1.x; rs0 = st0.y; rs1 = st1.y;
    };
    auto ld_x = [&]() {
#pragma unroll
      for (int j = 0; j < 16; j += 2) ldsm4(sb + (j < 8 ? SX14 : SX15) * SLOT + (moff ^ ((j & 7) << 4)), xr[2 * j], xr[2 * j + 1], xr[2 * j + 2], xr[2 * j + 3]);
    };
    auto resid = [&]() {
      const float c0 = 1.f + rs0, c1 = 1.f + rs1, e0 = nm0 * rs0, e1 = nm1 * rs1;
#pragma unroll
      for (int j = 0; j < 16; j++) {
        ao[4 * j + 0] = fmaf(bf_lo(xr[2 * j]), c0, e0); ao[4 * j + 1] = fmaf(bf_hi(xr[2 * j]), c0, e0);
        ao[4 * j + 2] = fmaf(bf_lo(xr[2 * j + 1]), c1, e1); ao[4 * j + 3] = fmaf(bf_hi(xr[2 * j + 1]), c1, e1);
      }
    };
    {
      uint32_t pa[32];
      float4 st[16];
      auto ld = [&](int j) { st[j] = lds_f4(sta + j * 64); };
      auto k_blk = [&](int c) {
#pragma unroll
        for (int i = 0; i < 2; i++) {
          const float4 u = st[2 * c + i];
          const float l0 = u.y * 1.4426950408889634f, l1 = u.w * 1.4426950408889634f;
          const float* a = ak + 8 * c + 4 * i;
          pa[4 * c + 2 * i] = pack_bf16(phi(fmaf(-u.x, ck0, a[0]), u.y, l0), phi(fmaf(-u.z, ck0, a[1]), u.w, l1));
          pa[4 * c + 2 * i + 1] = pack_bf16(phi(fmaf(-u.x, ck1, a[2]), u.y, l0), phi(fmaf(-u.z, ck1, a[3]), u.w, l1));
        }
      };
      const uint32_t voff = sb + w * 8192 + (uint32_t)(8 * (lane >> 4) + (lane & 7)) * 128 + (((2 * wq + ((lane >> 3) & 1)) ^ (lane & 7)) << 4);
      auto v_blk = [&](int c) {
        uint32_t r[4];
#pragma unroll
        for (int i = 0; i < 2; i++) {
          const float4 u = st[2 * c + i];
          const float* a = av + 8 * c + 4 * i;
          r[2 * i] = pack_bf16(fmaf(-u.x, cv0, a[0]) * u.y, fmaf(-u.z, cv0, a[1]) * u.w);
          r[2 * i + 1] = pack_bf16(fmaf(-u.x, cv1, a[2]) * u.y, fmaf(-u.z, cv1, a[3]) * u.w);
        }
        stsm4t(voff + (c < 4 ? S_V0 : S_V1) * SLOT + (c & 3) * 2048, r[0], r[1], r[2], r[3]);
      };
      auto kv_mma = [&](int c) {
        const uint32_t bo = (c < 4 ? S_V0 : S_V1) * 1024 + w * 512 + (c & 3) * 128;
        const uint64_t bb = mkdesc((d0 + bo) | (((A_ONES >> 4) - bo) << 16), HI_SW128);
        if (c == 0) wgmma_rz_n72<1>(kvp, pa[4 * c], pa[4 * c + 1], pa[4 * c + 2], pa[4 * c + 3], bb);
        else wgmma_rs_n72<1>(kvp, pa[4 * c], pa[4 * c + 1], pa[4 * c + 2], pa[4 * c + 3], bb);
      };
      ld(0); ld(1);
      wg_wait<0>();
      reg_fence(ak); reg_fence(av);
      TLS(0, 2);
      release2(B_E);
      release(B_T0);
      if (LQ) { v_blk(0); ld(2); ld(3); } else { ld(2); ld(3); v_blk(0); }
      ld(4); ld(5); v_blk(1); k_blk(0);
      ld(6); ld(7); v_blk(2); ld(8); ld(9); v_blk(3); k_blk(1);
      ld(10); ld(11); v_blk(4); ld(12); ld(13); v_blk(5); k_blk(2);
      ld(14); ld(15); v_blk(6); v_blk(7); k_blk(3);
      if (RL) { ld(8); ld(9); }
      TLS(0, 3);
      fence_async_smem();
      asm volatile("bar.sync %0, 128;" ::"r"(3 + w) : "memory");
      if (XP == 0) ld_x();
      wg_fence();
      kv_mma(0); kv_mma(1); kv_mma(2); kv_mma(3);
      wg_commit();
#pragma unroll
      for (int c = 4; c < 8; c++) {
        if (RL && c < 7) { ld(2 * c + 2); ld(2 * c + 3); }
        k_blk(c);
        wg_fence();
        kv_mma(c);
        wg_commit();
      }
      if (XP == 3 && (RK == 0 || RK > 4)) ld_x();
      if (QE) { q_step(BAR(B_FQ), 0, SXQ0, QW_SLOTS & 15u); wg_wait<1>(); } else wg_wait<0>();
      reg_fence(kvp);
      auto hand_back = [&]() { release2(B_STG); __syncwarp(); };
      if (!SF) hand_back();
      TLS(0, 4);
      uint4* pp = G.part + b * 544;
      uint32_t pk[8];
#pragma unroll
      for (int j = 0; j < 8; j++) pk[j] = wq >= 2 ? pack_bf16(kvp[16 + 2 * j], kvp[17 + 2 * j]) : pack_bf16(kvp[2 * j], kvp[2 * j + 1]);
      stx4(pp + tid, pk[0], pk[2], pk[4], pk[6]);
      stx4(pp + 256 + tid, pk[1], pk[3], pk[5], pk[7]);
      if (t == 0) stx2(reinterpret_cast<uint2*>(pp + 512) + (tid >> 2), f2x(kvp[32]), f2x(kvp[34]));
      if (SF == 1) hand_back();
      if (XP == 1) ld_x();
      if (!QE) q_step(BAR(B_FQ), 0, SXQ0, QW_SLOTS & 15u);
      if (XP == 2) ld_x();
      if (SF == 2) hand_back();
      const int wd_ = wq * 16 + (lane & 15);
      const uint32_t* src = reinterpret_cast<const uint32_t*>(G.part + ((lane >> 4) * 64 + hg) * 544 + w * 256 + tb * 16) + wd_;
      uint32_t* fin = reinterpret_cast<uint32_t*>(G.fin + hg * 640) + (tb >> 2) * 640 + ((tb >> 1) & 1) * 64 + (tb & 1) * 16 + w * 32 + ((wd_ >> 2) & 3) * 128 + wq * 4 + (wd_ & 3);
      uint32_t v[8];
      auto part_load = [&]() {
#pragma unroll
        for (int i = 0; i < 8; i++) v[i] = ldx1(src + i * 8 * 2176);
      };
#pragma unroll
      for (int k = 1; k < NQ; k++) {
        q_step(BAR(B_FQ + k), 0, (QX_SLOTS >> (4 * k)) & 15u, (QW_SLOTS >> (4 * k)) & 15u);
        TLS(0, 48 + k);
        if (k == RK) { row_stats(); ld_x(); resid(); }
        if (!MRED && k == PLP) part_load();
        if (!MRED && k == PLC) {
#pragma unroll 1
          for (uint32_t it = 0; it < SPIN_MAX; it++) {
            if (!__any_sync(~0u, max(max(max(v[0], v[1]), max(v[2], v[3])), max(max(v[4], v[5]), max(v[6], v[7]))) == SENT)) break;
            part_load();
          }
          float lo = ((bf_lo(v[0]) + bf_lo(v[1])) + (bf_lo(v[2]) + bf_lo(v[3]))) + ((bf_lo(v[4]) + bf_lo(v[5])) + (bf_lo(v[6]) + bf_lo(v[7])));
          float hi = ((bf_hi(v[0]) + bf_hi(v[1])) + (bf_hi(v[2]) + bf_hi(v[3]))) + ((bf_hi(v[4]) + bf_hi(v[5])) + (bf_hi(v[6]) + bf_hi(v[7])));
          lo += __shfl_xor_sync(~0u, lo, 16); hi += __shfl_xor_sync(~0u, hi, 16);
          if (lane < 16) stx1(fin, pack_bf16(lo, hi));
          TLS(0, 5);
        }
        wg_wait<1>();
        release2(B_EQ + k - 1);
      }
      TLS(0, 13);
      mbar_wait(BAR(B_CQ), 0);
    }
    wg_wait<0>();
    reg_fence(aq);
    TLS(0, 15);
    if (RK == 0 || RK > 4) row_stats();
    const float rl0 = rs0 * 1.4426950408889634f, rl1 = rs1 * 1.4426950408889634f;
    uint32_t pq[32];
#pragma unroll
    for (int j = 0; j < 16; j++) {
      const float2 c = lds_f2(aux + A_CS + (j * 8 + 2 * t) * 4);
      const float* a = aq + 4 * j;
      pq[2 * j] = pack_bf16(phi(fmaf(nm0, c.x, a[0]), rs0, rl0), phi(fmaf(nm0, c.y, a[1]), rs0, rl0));
      pq[2 * j + 1] = pack_bf16(phi(fmaf(nm1, c.x, a[2]), rs1, rl1), phi(fmaf(nm1, c.y, a[3]), rs1, rl1));
    }
    TLS(0, 6);
    if (RK == 5) resid();
    mbar_wait_b(BAR(MFIN ? B_KV4 : B_KVB), 0);
    TLS(0, 7);
    uint32_t of[32];
    uint4* mine = G.o + (tb * 32 + hg) * 512 + warp * 64 + g * 4 + (t ^ (g >> 1));
    const uint32_t dW = d0 | (256u << 16);
    auto o_store = [&](int h) {
#pragma unroll
      for (int c = 0; c < 2; c++) stx4(mine + h * 4096 + c * 32, of[8 * h + c], of[8 * h + 2 + c], of[8 * h + 4 + c], of[8 * h + 6 + c]);
    };
    auto out_step = [&](uint32_t slot, const uint32_t* a) {
      const uint32_t d = dW + slot * 1024;
      wg_fence();
#pragma unroll
      for (int kk = 0; kk < 4; kk++) wgmma_rs_n128<1>(ao, a[4 * kk], a[4 * kk + 1], a[4 * kk + 2], a[4 * kk + 3], mkdesc(d + (kk >> 1) * 512 + (kk & 1) * 128, HI_SW128));
      wg_commit();
    };
    uint4 v[NDIR][4];
    auto ld_o = [&](int k) {
      const uint4* p0 = mine + (slab(2 * k, hg) - hg) * 512;
      const uint4* p1 = mine + (slab(2 * k + 1, hg) - hg) * 512;
      v[k][0] = ldx4(p0); v[k][1] = ldx4(p0 + 32); v[k][2] = ldx4(p1); v[k][3] = ldx4(p1 + 32);
    };
    auto ld_all = [&]() {
#pragma unroll
      for (int k = 0; k < NDIR; k++) ld_o(k);
    };
    {
      float oa[4][20];
      const uint32_t dK = (d0 + S_KVB * 1024) | (8u << 16);
      wg_fence();
#pragma unroll
      for (int h = 0; h < 4; h++) {
        wgmma_rz_n40<1>(oa[h], pq[8 * h], pq[8 * h + 1], pq[8 * h + 2], pq[8 * h + 3], mkdesc(dK + h * 160, HI_NOSW));
        wgmma_rs_n40<1>(oa[h], pq[8 * h + 4], pq[8 * h + 5], pq[8 * h + 6], pq[8 * h + 7], mkdesc(dK + h * 160 + 16, HI_NOSW));
        if (h == 0 || h == 3) wg_commit();
      }
      auto norm = [&](int h) {
        const float r0 = rcp(oa[h][16] + 1e-6f), r1 = rcp(oa[h][18] + 1e-6f);
#pragma unroll
        for (int j = 0; j < 4; j++) {
          of[8 * h + 2 * j] = pack_bf16(oa[h][4 * j] * r0, oa[h][4 * j + 1] * r0);
          of[8 * h + 2 * j + 1] = pack_bf16(oa[h][4 * j + 2] * r1, oa[h][4 * j + 3] * r1);
        }
      };
      wg_wait<1>();
      reg_fence(oa[0]);
      norm(0);
      if (LE == 4) ld_all();
      o_store(0);
      if (LE == 3) ld_all();
      TLS(0, 8);
      wg_wait<0>();
      reg_fence(oa[1]); reg_fence(oa[2]); reg_fence(oa[3]);
      TLP_(0);
      release(B_EAUX);
      norm(1);
      if (OS1 == 3) o_store(1);
      if (E7 && NP == 0 && SL7 && hg == 7) o_store(1);
      if (NP == 0) { norm(2); norm(3); }
      if (E7 && NP == 0 && SL7 && hg == 7) { o_store(2); o_store(3); }
      TLP_(1);
      mbar_wait_b(BAR(B_FWO), 0);
      TLP_(2);
      if (RK == 0) resid();
      if (LE == 2) ld_all();
      TLP_(3);
      out_step(WO_SLOTS & 15u, of);
      TLP_(4);
      if (NP == 1) { norm(2); norm(3); }
      if (LE == 1) ld_all();
    }
    if (OS1 == 0) o_store(1);
    mbar_wait(BAR(B_FWO + 1), 0);
    TLP_(5);
    out_step((WO_SLOTS >> 4) & 15u, of + 16);
    TLP_(6);
    const bool early = SL7 && hg == 7;
    if (OS1 == 1 && !(E7 && early)) o_store(1);
    TLP_(7);
    if (early && !E7) { o_store(2); o_store(3); }
    {
      if (DW) __nanosleep(DW);
      if (LE == 0) ld_all();
      if (OS1 == 2 && !(E7 && early)) o_store(1);
#pragma unroll
      for (int k = 0; k < NDIR; k++) {
#pragma unroll 1
        for (uint32_t it = 0; it < SPIN_MAX; it++) {
          if (!__any_sync(~0u, max(max(v[k][0].x, v[k][1].x), max(v[k][2].x, v[k][3].x)) == SENT)) break;
#pragma unroll
          for (int j = k; j < NDIR; j++) ld_o(j);
        }
        TLP_(8);
        const uint32_t a[16] = {v[k][0].x, v[k][1].x, v[k][0].y, v[k][1].y, v[k][0].z, v[k][1].z, v[k][0].w, v[k][1].w,
                                v[k][2].x, v[k][3].x, v[k][2].y, v[k][3].y, v[k][2].z, v[k][3].z, v[k][2].w, v[k][3].w};
        mbar_wait(BAR(B_FWO + 2 + k), 0);
        TLS(0, 34 + k);
        out_step((WO_SLOTS >> (8 + 4 * k)) & 15u, a);
        TLP_(9);
        if (k) { wg_wait<1>(); release2(B_EO); }
      }
      if (!early) o_store(2);
    }
    {
      const uint32_t dO = (d0 + w * 256) | (1u << 16);
      auto step = [&](int i, int r, int p, uint32_t as, uint32_t ws) {
        mbar_wait(BAR(B_FWO + i), 0);
        mbar_wait(BAR(B_VAL + r), p);
        TLS(0, 32 + i);
        const uint32_t da = dO + as * 1024, db = dW + ws * 1024;
        wg_fence();
#pragma unroll
        for (int kk = 0; kk < 4; kk++)
          wgmma_ss_n128<0, 1>(ao, mkdesc(da + (kk >> 1) * 512 + (kk & 1) * 2, HI_SW64), mkdesc(db + (kk >> 1) * 512 + (kk & 1) * 128, HI_SW128));
        wg_commit();
      };
      uint64_t tbl = WO_SLOTS >> (4 * I0);
      int r = 0, p = 0, rp = 0;
#pragma unroll 1
      for (int i = I0; i < 12; i++) {
        step(i, r, p, (A_SLOTS >> (4 * r)) & 15u, (uint32_t)tbl & 15u);
        tbl >>= 4;
#pragma unroll
        for (int c = 0; c < 2; c++)
          if (i == OS3 + c && !early) stx4(mine + 3 * 4096 + c * 32, of[24 + c], of[26 + c], of[28 + c], of[30 + c]);
        wg_wait<1>();
        if (i > I0) release(B_EA + rp);
        rp = r;
        if (++r == NA) { r = 0; p ^= 1; }
        if (i >= 3 && i <= 9) release2(B_EO + i - 3);
      }
#pragma unroll
      for (int i = 12; i < 16; i++) {
        if (i == 16 - STAG && w == 1) mbar_wait(BAR(B_GO), 0);
        step(i, (i - I0) % NA, ((i - I0) / NA) & 1, (A_SLOTS >> (4 * ((i - I0) % NA))) & 15u, (uint32_t)(WO_SLOTS >> (4 * i)) & 15u);
        if (STAG && i == 15 - GOE && tid == 0) mbar_arrive(BAR(B_GO));
      }
    }
    mbar_wait(BAR(B_MOE), 0);
    {
      const float2 kk = lds_f2(sb + MISC + M_IDX + t * 8);
      const int k0 = (int)(~__float_as_uint(kk.x) & 2047u) - tb * 128, k1 = (int)(~__float_as_uint(kk.y) & 2047u) - tb * 128;
      if (NUNIT && __any_sync(~0u, (k0 >> 6) == w || (k1 >> 6) == w)) {
        const uint32_t a0 = (k0 == row0 ? 0x3F80u : 0u) | (k1 == row0 ? 0x3F800000u : 0u);
        const uint32_t a1 = (k0 == row0 + 8 ? 0x3F80u : 0u) | (k1 == row0 + 8 ? 0x3F800000u : 0u);
        wg_fence();
        wgmma_rs_n128<1>(ao, a0, a1, 0u, 0u, mkdesc((d0 + ((MISC + M_MOE) >> 4)) | (64u << 16), 0x40000000u));
        wg_commit();
      }
    }
    wg_wait<0>();
    reg_fence(ao);
    TLS(0, 10);
    const uint32_t ost = sb + (w ? S_D1 : S_D0) * SLOT + wq * 4096;
#pragma unroll
    for (int h = 0; h < 2; h++) {
#pragma unroll
      for (int j = 8 * h; j < 8 * h + 8; j += 2)
        stsm4(ost + h * 2048 + ((moff & 2047) ^ ((j & 7) << 4)), pack_bf16(ao[4 * j], ao[4 * j + 1]), pack_bf16(ao[4 * j + 2], ao[4 * j + 3]),
              pack_bf16(ao[4 * j + 4], ao[4 * j + 5]), pack_bf16(ao[4 * j + 6], ao[4 * j + 7]));
      if (OUTV == 2 || h) {
        fence_async_smem();
        __syncwarp();
        if (elect_one()) {
#pragma unroll
          for (int c = (OUTV == 2 ? h : 0); c <= h; c++)
            asm volatile("cp.async.bulk.tensor.2d.global.shared::cta.bulk_group [%0, {%2, %3}], [%1];" ::"l"(&tmOut), "r"(ost + c * 2048), "r"(hg * 128 + c * 64), "r"(tb * 128 + warp * 16) : "memory");
          if (h) asm volatile("cp.async.bulk.commit_group;\ncp.async.bulk.wait_group.read 0;" ::: "memory");
        }
        __syncwarp();
      }
    }
    TLS(0, 11);
    TLS(128, 9);
  }
}

typedef CUresult (*EncFn)(CUtensorMap*, CUtensorMapDataType, cuuint32_t, void*, const cuuint64_t*, const cuuint64_t*, const cuuint32_t*,
                          const cuuint32_t*, CUtensorMapInterleave, CUtensorMapSwizzle, CUtensorMapL2promotion, CUtensorMapFloatOOBfill);

void make_map2(EncFn enc, CUtensorMap* m, void* p, uint64_t rows, uint64_t cols, uint32_t brows, CUtensorMapL2promotion promo) {
  cuuint64_t gd[2] = {cols, rows}, gs[1] = {cols * 2};
  cuuint32_t bd[2] = {64, brows}, es[2] = {1, 1};
  enc(m, CU_TENSOR_MAP_DATA_TYPE_BFLOAT16, 2, p, gd, gs, bd, es, CU_TENSOR_MAP_INTERLEAVE_NONE, CU_TENSOR_MAP_SWIZZLE_128B, promo,
      CU_TENSOR_MAP_FLOAT_OOB_FILL_NONE);
}
void make_map3(EncFn enc, CUtensorMap* m, void* p, uint64_t rows, uint64_t cols, uint32_t brows) {
  cuuint64_t gd[3] = {64, rows, cols / 64}, gs[2] = {cols * 2, 128};
  cuuint32_t bd[3] = {64, brows, 2}, es[3] = {1, 1, 1};
  enc(m, CU_TENSOR_MAP_DATA_TYPE_BFLOAT16, 3, p, gd, gs, bd, es, CU_TENSOR_MAP_INTERLEAVE_NONE, CU_TENSOR_MAP_SWIZZLE_128B,
      CU_TENSOR_MAP_L2_PROMOTION_L2_256B, CU_TENSOR_MAP_FLOAT_OOB_FILL_NONE);
}

}

extern "C" void kernel_launch(void* const* d_in, const int* in_sizes, int n_in, void* d_out, int out_size) {
  static EncFn enc = nullptr;
  static int by_sm = 0;
  if (!enc) {
    void* fn = nullptr;
    cudaDriverEntryPointQueryResult qr;
    cudaGetDriverEntryPoint("cuTensorMapEncodeTiled", &fn, cudaEnableDefault, &qr);
    enc = (EncFn)fn;
    int dev = 0, sms = 0;
    cudaGetDevice(&dev);
    cudaDeviceGetAttribute(&sms, cudaDevAttrMultiProcessorCount, dev);
    by_sm = MAP == 2 && sms == NCTA + NSVC;
    cudaFuncSetAttribute(fused_kernel, cudaFuncAttributeMaxDynamicSharedMemorySize, SMEM_BYTES);
  }
  CUtensorMap tmX, tmW, tmWo, tmOut, tmG, tmU, tmD, tmR, tmWp;
  {
    cuuint64_t gd[5] = {64, 2, 128, 4, 16}, gs[4] = {2048, 16384, 4096, 128};
    cuuint32_t bd[5] = {64, 2, 4, 4, 2}, es[5] = {1, 1, 1, 1, 1};
    enc(&tmWp, CU_TENSOR_MAP_DATA_TYPE_BFLOAT16, 5, d_in[2], gd, gs, bd, es, CU_TENSOR_MAP_INTERLEAVE_NONE, CU_TENSOR_MAP_SWIZZLE_128B,
        CU_TENSOR_MAP_L2_PROMOTION_L2_256B, CU_TENSOR_MAP_FLOAT_OOB_FILL_NONE);
  }
  make_map2(enc, &tmR, d_in[0], SEQ, DM, 1, CU_TENSOR_MAP_L2_PROMOTION_L2_128B);
  make_map2(enc, &tmX, d_in[0], SEQ, DM, 128, XPROMO);
  make_map3(enc, &tmW, d_in[1], DM, 3 * DM, 64);
  make_map3(enc, &tmWo, d_in[2], DM, DM, 32);
  if (OUTV) make_map2(enc, &tmOut, d_out, SEQ, DM, 16, CU_TENSOR_MAP_L2_PROMOTION_L2_128B); else make_map3(enc, &tmOut, d_out, SEQ, DM, 64);
  make_map2(enc, &tmG, d_in[5], DM, FF, 64, MPROMO);
  make_map2(enc, &tmU, d_in[6], DM, FF, 64, MPROMO);
  make_map2(enc, &tmD, d_in[7], FF, DM, 64, MPROMO);
  typedef const __nv_bfloat16* P;
  cudaLaunchConfig_t cfg = {};
  cfg.gridDim = dim3(NCTA + NSVC); cfg.blockDim = dim3(512); cfg.dynamicSmemBytes = SMEM_BYTES; cfg.stream = cudaStreamPerThread;
  cudaLaunchAttribute at[1];
  at[0].id = cudaLaunchAttributeClusterDimension;
  at[0].val.clusterDim.x = 2; at[0].val.clusterDim.y = 1; at[0].val.clusterDim.z = 1;
  cfg.attrs = at; cfg.numAttrs = 1;
  cudaLaunchKernelEx(&cfg, fused_kernel, (P)d_in[0], (P)d_in[1], (P)d_in[2], (P)d_in[4], (P)d_in[7], by_sm, tmX, tmW, tmWo, tmOut, tmG, tmU, tmD, tmR, tmWp);
}
```

```cpp
#include <cuda_runtime.h>
#include <cuda.h>
#include <cuda_bf16.h>
#include <stdint.h>

namespace {

template <int TA, int TB> __device__ __forceinline__ void wgmma_ss_n128(float (&d)[64], uint64_t da, uint64_t db) {
  asm volatile("wgmma.mma_async.sync.aligned.m64n128k16.f32.bf16.bf16 "
  "{%0,%1,%2,%3,%4,%5,%6,%7,%8,%9,%10,%11,%12,%13,%14,%15,%16,%17,%18,%19,%20,%21,%22,%23,%24,%25,%26,%27,%28,%29,%30,%31,%32,%33,%34,%35,%36,%37,%38,%39,%40,%41,%42,%43,%44,%45,%46,%47,%48,%49,%50,%51,%52,%53,%54,%55,%56,%57,%58,%59,%60,%61,%62,%63}, "
  "%64, %65, 1, 1, 1, %66, %67;"
  : "+f"(d[0]),"+f"(d[1]),"+f"(d[2]),"+f"(d[3]),"+f"(d[4]),"+f"(d[5]),"+f"(d[6]),"+f"(d[7]),"+f"(d[8]),"+f"(d[9]),"+f"(d[10]),"+f"(d[11]),"+f"(d[12]),"+f"(d[13]),"+f"(d[14]),"+f"(d[15]),"+f"(d[16]),"+f"(d[17]),"+f"(d[18]),"+f"(d[19]),"+f"(d[20]),"+f"(d[21]),"+f"(d[22]),"+f"(d[23]),"+f"(d[24]),"+f"(d[25]),"+f"(d[26]),"+f"(d[27]),"+f"(d[28]),"+f"(d[29]),"+f"(d[30]),"+f"(d[31]),"+f"(d[32]),"+f"(d[33]),"+f"(d[34]),"+f"(d[35]),"+f"(d[36]),"+f"(d[37]),"+f"(d[38]),"+f"(d[39]),"+f"(d[40]),"+f"(d[41]),"+f"(d[42]),"+f"(d[43]),"+f"(d[44]),"+f"(d[45]),"+f"(d[46]),"+f"(d[47]),"+f"(d[48]),"+f"(d[49]),"+f"(d[50]),"+f"(d[51]),"+f"(d[52]),"+f"(d[53]),"+f"(d[54]),"+f"(d[55]),"+f"(d[56]),"+f"(d[57]),"+f"(d[58]),"+f"(d[59]),"+f"(d[60]),"+f"(d[61]),"+f"(d[62]),"+f"(d[63])
  : "l"(da), "l"(db), "n"(TA), "n"(TB));
}
template <int TA, int TB> __device__ __forceinline__ void wgmma_ss_n64(float (&d)[32], uint64_t da, uint64_t db) {
  asm volatile("wgmma.mma_async.sync.aligned.m64n64k16.f32.bf16.bf16 "
  "{%0,%1,%2,%3,%4,%5,%6,%7,%8,%9,%10,%11,%12,%13,%14,%15,%16,%17,%18,%19,%20,%21,%22,%23,%24,%25,%26,%27,%28,%29,%30,%31}, "
  "%32, %33, 1, 1, 1, %34, %35;"
  : "+f"(d[0]),"+f"(d[1]),"+f"(d[2]),"+f"(d[3]),"+f"(d[4]),"+f"(d[5]),"+f"(d[6]),"+f"(d[7]),"+f"(d[8]),"+f"(d[9]),"+f"(d[10]),"+f"(d[11]),"+f"(d[12]),"+f"(d[13]),"+f"(d[14]),"+f"(d[15]),"+f"(d[16]),"+f"(d[17]),"+f"(d[18]),"+f"(d[19]),"+f"(d[20]),"+f"(d[21]),"+f"(d[22]),"+f"(d[23]),"+f"(d[24]),"+f"(d[25]),"+f"(d[26]),"+f"(d[27]),"+f"(d[28]),"+f"(d[29]),"+f"(d[30]),"+f"(d[31])
  : "l"(da), "l"(db), "n"(TA), "n"(TB));
}
template <int TA, int TB> __device__ __forceinline__ void wgmma_sz_n64(float (&d)[32], uint64_t da, uint64_t db) {
  asm volatile("wgmma.mma_async.sync.aligned.m64n64k16.f32.bf16.bf16 "
  "{%0,%1,%2,%3,%4,%5,%6,%7,%8,%9,%10,%11,%12,%13,%14,%15,%16,%17,%18,%19,%20,%21,%22,%23,%24,%25,%26,%27,%28,%29,%30,%31}, "
  "%32, %33, 0, 1, 1, %34, %35;"
  : "=f"(d[0]),"=f"(d[1]),"=f"(d[2]),"=f"(d[3]),"=f"(d[4]),"=f"(d[5]),"=f"(d[6]),"=f"(d[7]),"=f"(d[8]),"=f"(d[9]),"=f"(d[10]),"=f"(d[11]),"=f"(d[12]),"=f"(d[13]),"=f"(d[14]),"=f"(d[15]),"=f"(d[16]),"=f"(d[17]),"=f"(d[18]),"=f"(d[19]),"=f"(d[20]),"=f"(d[21]),"=f"(d[22]),"=f"(d[23]),"=f"(d[24]),"=f"(d[25]),"=f"(d[26]),"=f"(d[27]),"=f"(d[28]),"=f"(d[29]),"=f"(d[30]),"=f"(d[31])
  : "l"(da), "l"(db), "n"(TA), "n"(TB));
}
template <int TB> __device__ __forceinline__ void wgmma_rs_n72(float (&d)[36], uint32_t a0, uint32_t a1, uint32_t a2, uint32_t a3, uint64_t db) {
  asm volatile("wgmma.mma_async.sync.aligned.m64n72k16.f32.bf16.bf16 "
  "{%0,%1,%2,%3,%4,%5,%6,%7,%8,%9,%10,%11,%12,%13,%14,%15,%16,%17,%18,%19,%20,%21,%22,%23,%24,%25,%26,%27,%28,%29,%30,%31,%32,%33,%34,%35}, "
  "{%36,%37,%38,%39}, %40, 1, 1, 1, %41;"
  : "+f"(d[0]),"+f"(d[1]),"+f"(d[2]),"+f"(d[3]),"+f"(d[4]),"+f"(d[5]),"+f"(d[6]),"+f"(d[7]),"+f"(d[8]),"+f"(d[9]),"+f"(d[10]),"+f"(d[11]),"+f"(d[12]),"+f"(d[13]),"+f"(d[14]),"+f"(d[15]),"+f"(d[16]),"+f"(d[17]),"+f"(d[18]),"+f"(d[19]),"+f"(d[20]),"+f"(d[21]),"+f"(d[22]),"+f"(d[23]),"+f"(d[24]),"+f"(d[25]),"+f"(d[26]),"+f"(d[27]),"+f"(d[28]),"+f"(d[29]),"+f"(d[30]),"+f"(d[31]),"+f"(d[32]),"+f"(d[33]),"+f"(d[34]),"+f"(d[35])
  : "r"(a0), "r"(a1), "r"(a2), "r"(a3), "l"(db), "n"(TB));
}
template <int TB> __device__ __forceinline__ void wgmma_rz_n72(float (&d)[36], uint32_t a0, uint32_t a1, uint32_t a2, uint32_t a3, uint64_t db) {
  asm volatile("wgmma.mma_async.sync.aligned.m64n72k16.f32.bf16.bf16 "
  "{%0,%1,%2,%3,%4,%5,%6,%7,%8,%9,%10,%11,%12,%13,%14,%15,%16,%17,%18,%19,%20,%21,%22,%23,%24,%25,%26,%27,%28,%29,%30,%31,%32,%33,%34,%35}, "
  "{%36,%37,%38,%39}, %40, 0, 1, 1, %41;"
  : "=f"(d[0]),"=f"(d[1]),"=f"(d[2]),"=f"(d[3]),"=f"(d[4]),"=f"(d[5]),"=f"(d[6]),"=f"(d[7]),"=f"(d[8]),"=f"(d[9]),"=f"(d[10]),"=f"(d[11]),"=f"(d[12]),"=f"(d[13]),"=f"(d[14]),"=f"(d[15]),"=f"(d[16]),"=f"(d[17]),"=f"(d[18]),"=f"(d[19]),"=f"(d[20]),"=f"(d[21]),"=f"(d[22]),"=f"(d[23]),"=f"(d[24]),"=f"(d[25]),"=f"(d[26]),"=f"(d[27]),"=f"(d[28]),"=f"(d[29]),"=f"(d[30]),"=f"(d[31]),"=f"(d[32]),"=f"(d[33]),"=f"(d[34]),"=f"(d[35])
  : "r"(a0), "r"(a1), "r"(a2), "r"(a3), "l"(db), "n"(TB));
}
template <int TB> __device__ __forceinline__ void wgmma_rs_n40(float (&d)[20], uint32_t a0, uint32_t a1, uint32_t a2, uint32_t a3, uint64_t db) {
  asm volatile("wgmma.mma_async.sync.aligned.m64n40k16.f32.bf16.bf16 "
  "{%0,%1,%2,%3,%4,%5,%6,%7,%8,%9,%10,%11,%12,%13,%14,%15,%16,%17,%18,%19}, "
  "{%20,%21,%22,%23}, %24, 1, 1, 1, %25;"
  : "+f"(d[0]),"+f"(d[1]),"+f"(d[2]),"+f"(d[3]),"+f"(d[4]),"+f"(d[5]),"+f"(d[6]),"+f"(d[7]),"+f"(d[8]),"+f"(d[9]),"+f"(d[10]),"+f"(d[11]),"+f"(d[12]),"+f"(d[13]),"+f"(d[14]),"+f"(d[15]),"+f"(d[16]),"+f"(d[17]),"+f"(d[18]),"+f"(d[19])
  : "r"(a0), "r"(a1), "r"(a2), "r"(a3), "l"(db), "n"(TB));
}
template <int TB> __device__ __forceinline__ void wgmma_rz_n40(float (&d)[20], uint32_t a0, uint32_t a1, uint32_t a2, uint32_t a3, uint64_t db) {
  asm volatile("wgmma.mma_async.sync.aligned.m64n40k16.f32.bf16.bf16 "
  "{%0,%1,%2,%3,%4,%5,%6,%7,%8,%9,%10,%11,%12,%13,%14,%15,%16,%17,%18,%19}, "
  "{%20,%21,%22,%23}, %24, 0, 1, 1, %25;"
  : "=f"(d[0]),"=f"(d[1]),"=f"(d[2]),"=f"(d[3]),"=f"(d[4]),"=f"(d[5]),"=f"(d[6]),"=f"(d[7]),"=f"(d[8]),"=f"(d[9]),"=f"(d[10]),"=f"(d[11]),"=f"(d[12]),"=f"(d[13]),"=f"(d[14]),"=f"(d[15]),"=f"(d[16]),"=f"(d[17]),"=f"(d[18]),"=f"(d[19])
  : "r"(a0), "r"(a1), "r"(a2), "r"(a3), "l"(db), "n"(TB));
}
template <int TB> __device__ __forceinline__ void wgmma_rs_n128(float (&d)[64], uint32_t a0, uint32_t a1, uint32_t a2, uint32_t a3, uint64_t db) {
  asm volatile("wgmma.mma_async.sync.aligned.m64n128k16.f32.bf16.bf16 "
  "{%0,%1,%2,%3,%4,%5,%6,%7,%8,%9,%10,%11,%12,%13,%14,%15,%16,%17,%18,%19,%20,%21,%22,%23,%24,%25,%26,%27,%28,%29,%30,%31,%32,%33,%34,%35,%36,%37,%38,%39,%40,%41,%42,%43,%44,%45,%46,%47,%48,%49,%50,%51,%52,%53,%54,%55,%56,%57,%58,%59,%60,%61,%62,%63}, "
  "{%64,%65,%66,%67}, %68, 1, 1, 1, %69;"
  : "+f"(d[0]),"+f"(d[1]),"+f"(d[2]),"+f"(d[3]),"+f"(d[4]),"+f"(d[5]),"+f"(d[6]),"+f"(d[7]),"+f"(d[8]),"+f"(d[9]),"+f"(d[10]),"+f"(d[11]),"+f"(d[12]),"+f"(d[13]),"+f"(d[14]),"+f"(d[15]),"+f"(d[16]),"+f"(d[17]),"+f"(d[18]),"+f"(d[19]),"+f"(d[20]),"+f"(d[21]),"+f"(d[22]),"+f"(d[23]),"+f"(d[24]),"+f"(d[25]),"+f"(d[26]),"+f"(d[27]),"+f"(d[28]),"+f"(d[29]),"+f"(d[30]),"+f"(d[31]),"+f"(d[32]),"+f"(d[33]),"+f"(d[34]),"+f"(d[35]),"+f"(d[36]),"+f"(d[37]),"+f"(d[38]),"+f"(d[39]),"+f"(d[40]),"+f"(d[41]),"+f"(d[42]),"+f"(d[43]),"+f"(d[44]),"+f"(d[45]),"+f"(d[46]),"+f"(d[47]),"+f"(d[48]),"+f"(d[49]),"+f"(d[50]),"+f"(d[51]),"+f"(d[52]),"+f"(d[53]),"+f"(d[54]),"+f"(d[55]),"+f"(d[56]),"+f"(d[57]),"+f"(d[58]),"+f"(d[59]),"+f"(d[60]),"+f"(d[61]),"+f"(d[62]),"+f"(d[63])
  : "r"(a0), "r"(a1), "r"(a2), "r"(a3), "l"(db), "n"(TB));
}
template <int TA, int TB> __device__ __forceinline__ void wgmma_ss_n8(float (&d)[4], uint64_t da, uint64_t db) {
  asm volatile("wgmma.mma_async.sync.aligned.m64n8k16.f32.bf16.bf16 "
  "{%0,%1,%2,%3}, "
  "%4, %5, 1, 1, 1, %6, %7;"
  : "+f"(d[0]),"+f"(d[1]),"+f"(d[2]),"+f"(d[3])
  : "l"(da), "l"(db), "n"(TA), "n"(TB));
}
template <int TA, int TB> __device__ __forceinline__ void wgmma_ss_n16(float (&d)[8], uint64_t da, uint64_t db) {
  asm volatile("wgmma.mma_async.sync.aligned.m64n16k16.f32.bf16.bf16 "
  "{%0,%1,%2,%3,%4,%5,%6,%7}, "
  "%8, %9, 1, 1, 1, %10, %11;"
  : "+f"(d[0]),"+f"(d[1]),"+f"(d[2]),"+f"(d[3]),"+f"(d[4]),"+f"(d[5]),"+f"(d[6]),"+f"(d[7])
  : "l"(da), "l"(db), "n"(TA), "n"(TB));
}

constexpr int SEQ = 2048, DM = 1024, FF = 3584;
constexpr int NCTA = 128, NSVC = 4;
constexpr int NUNIT = 112;
constexpr uint32_t SLOT = 16384;
constexpr uint32_t MISC = 14 * SLOT;
constexpr uint32_t SMEM_BYTES = MISC + 3072;
constexpr uint32_t M_MOE = 0;
constexpr uint32_t M_BAR = 2048;
constexpr uint32_t M_DUM = 2048 + 1020;
constexpr uint32_t M_IDX = 2048 + 768;
constexpr uint32_t M_KEY = 2048 + 960;
#define R5 1
#define NQ (R5 ? 6 : 5)
constexpr int NF = 16 - NQ, NR = (NQ == 5 || R5) ? 4 : 3;
constexpr int B_FXQ = 0, B_FKV = 3, B_AST = 6, B_MOE = 7, B_MF = 8  , B_CQ = 12, B_XS = 13, B_DF = 14, B_ZOK = 15, B_FWO = 21  , B_FQ = B_FWO - NQ,
              B_UP = 37, B_FIN = 38, B_KVB = 39, B_ME = 40  , B_HF = 44, B_AF = 45  , B_AR = 50  , B_GO = 52,
              B_FAUX = 53, B_EAUX = 54, B_T0 = 55, B_DE = 56, B_EA = 57  , B_VAL = 62  ,
              B_E = 67  , B_STG = 70, B_EQ = 71  , B_EO = 76  , NBAR = 83, B_KV4 = 83, B_MS = 84,
              B_FV = 85  , B_EK = 88  ;
constexpr uint32_t MT = 9216, A_ONES = 12 * SLOT + 3 * MT, A_CS = A_ONES + 2048, A_ST = A_CS + 1536;
constexpr uint32_t A_TL = MISC + 2048 + 808;
constexpr int S_V0 = R5 ? 7 : 11, S_V1 = R5 ? 9 : 7;
constexpr uint32_t K_SLOTS = 0x8697A8u, V_SLOTS = 0x97A869u;
constexpr int C_B = 0, C_DONE = 32, NCNT = 2;
constexpr uint32_t QX_SLOTS = NQ == 5 ? 0x43102u : 0x354021u;
constexpr uint32_t QW_SLOTS = R5 ? 0xA9786Au : 0xB76A98u;
constexpr uint32_t qx(int k) { return (QX_SLOTS >> (4 * k)) & 15u; }
constexpr uint32_t qw(int k) { return (QW_SLOTS >> (4 * k)) & 15u; }
constexpr uint32_t S_KVB = R5 ? 1 : 8, S_D0 = R5 ? 11 : (NQ == 5 ? 5 : 1), S_D1 = R5 ? 2 : (NQ == 5 ? 11 : 2);
constexpr uint32_t S_M3 = R5 ? 11 : 5;
constexpr int WQ0 = NQ == 5 ? 1 : 3;
constexpr uint32_t wo_slot_c(int i) { return i >= 9 ? wo_slot_c(i - 9) : (i == 7 ? S_D0 : (i == 8 ? S_D1 : (((i & 1) || i + WQ0 == 1) ? qx((i + WQ0) >> 1) : qw((i + WQ0) >> 1)))); }
constexpr uint64_t wo_slots() { uint64_t t = 0; for (int i = 0; i < 16; i++) t |= (uint64_t)wo_slot_c(i) << (4 * i); return t; }
constexpr uint64_t WO_SLOTS = wo_slots();
constexpr uint32_t A_SLOTS = 0xDC000u | (S_KVB << 8) | (qw(NQ - 1) << 4) | qx(NQ - 1);
constexpr uint32_t SX14 = qx(NQ - 2), SX15 = qx(NQ - 1), SXQ0 = qx(0);
#define WOD 2
#define PLC 3
#define PFG1 10
#define PFNS1 150
#define PFG0 3
#define RS0 0
#define WPF 1
#define POLLNS 150
#define SVNS 100
#define MPROMO CU_TENSOR_MAP_L2_PROMOTION_L2_128B
#define MW0 0
#define PFILL 0
#define H2W (NQ - 3)
#define TOPW 1000
#define PFT 0
#define SV0 2
#define SV0A 14
#define SV0B 22
#define ASTE 2
#define PFS 1
#define PFTAB 0x0012222220000ull
#define HW 0
#define DPF 1
#define PROBE 0x8
#define OS1 0
#define YW 0
#define OS2 3
#define NOVAL 0
#define NDIR 1
#define I0 (2 + NDIR)
#define DW 0
#define OSP 1
#define NA 5
#define STAG 4
#define GOE 0
#define SVP 99
#define KEY1 0
#define HYB 0
#define DV 0
#define DVJ 4
#define DVK 10
#define FW 0
#define E1E 0
#define GATE 0
#define SVD 0
#define XPROMO CU_TENSOR_MAP_L2_PROMOTION_L2_128B
#define MC0 3
#define MX 0
#define OUTV 1
#define BW0 2
#define QL 1
#define NP 0
#define FINCP 0
#define DNS 0
#define WOK 99
#define WOD1 2
#define SVT 64
#define MRED 1
#define MRW 0
#define H2D 400
#define MRD 0
#define STP 0
#define TPNS 50
#define DLP 0
#define MFIN 0
#define MFD 300
#define SF 1
#define PH MFIN
#define RSL 0
#define PFW 3000
#define KVE 1
#define P2NS 0
#define OS3 4
#define PLP 2
#define FINJ 9
#define PFD 0
#define PFG 3
#define PFNS2 150
#define PFNS 250
#define MAP 2
#define RSNS 60
#define SVS 6
#define PRODLATE 0
#define MC 7
#define QE 0
#define TMP 1
#define TMPW 4
#define DS 14
#define RL 0
#define EV 0
#define LQ 0
#define SPL 0
#define HALFST 0
#define PHI2 1
#define E7 1
#define RK 1
#define LE 0
#define SL7 0
#define XP 3
#define VR 4
#define KEEP 1
#define KP 4
#define KC 1
#define MS 0
constexpr int CON_REGS = 224, MOE_REGS = 40, PROD_REGS = 24;
constexpr uint32_t SPIN_MAX = 2000000;
constexpr uint32_t SENT = 0xFFFFFFFFu;

struct __align__(128) Scratch {
  uint4 o[NCTA * 2048];
  uint4 part[NCTA * 544];
  uint4 fin[8 * 640];
  float2 stats[SEQ];
  uint32_t key[SEQ];
  uint32_t cs[3 * DM];
  uint4 y[NCTA * 128];
  uint32_t h[56 * 256];
  uint32_t top[128];
  uint32_t cnt[NCNT * 32];
};
__device__ Scratch G;
#define TLS(th, i)
#define TLP_(i)
#define TLG(i)
#define TLDUMP()

__device__ __forceinline__ bool elect_one() {
  uint32_t p;
  asm volatile("{\n.reg .pred P;\nelect.sync _|P, 0xffffffff;\nselp.b32 %0, 1, 0, P;\n}" : "=r"(p));
  return p;
}
__device__ __forceinline__ void mbar_init(uint32_t b, uint32_t c) { asm volatile("mbarrier.init.shared::cta.b64 [%0], %1;" ::"r"(b), "r"(c) : "memory"); }
__device__ __forceinline__ void mbar_expect_tx(uint32_t b, uint32_t bytes) { asm volatile("mbarrier.arrive.expect_tx.shared::cta.b64 _, [%0], %1;" ::"r"(b), "r"(bytes) : "memory"); }
__device__ __forceinline__ void mbar_arrive(uint32_t b) { asm volatile("mbarrier.arrive.shared::cta.b64 _, [%0];" ::"r"(b) : "memory"); }
__device__ __forceinline__ void mbar_wait_b(uint32_t b, uint32_t parity) {
  asm volatile(
      "{\n.reg .pred p;\n.reg .u32 cnt;\nmov.u32 cnt, 0;\n"
      "LW:\nmbarrier.try_wait.parity.shared::cta.b64 p, [%0], %1;\n@p bra LD;\n"
      "add.u32 cnt, cnt, 1;\nsetp.lt.u32 p, cnt, 4000000;\n@p bra LW;\ntrap;\nLD:\n}" ::"r"(b), "r"(parity) : "memory");
}
__device__ __forceinline__ void mbar_wait(uint32_t b, uint32_t parity) {
  asm volatile("{\n.reg .pred p;\nLW:\nmbarrier.try_wait.parity.shared::cta.b64 p, [%0], %1;\n@!p bra LW;\n}" ::"r"(b), "r"(parity) : "memory");
}
__device__ __forceinline__ bool mbar_test(uint32_t b, uint32_t parity) {
  uint32_t r;
  asm volatile("{\n.reg .pred p;\nmbarrier.test_wait.parity.shared::cta.b64 p, [%1], %2;\nselp.b32 %0, 1, 0, p;\n}" : "=r"(r) : "r"(b), "r"(parity) : "memory");
  return r;
}
__device__ __forceinline__ uint32_t ev_arrive(uint32_t a) { uint32_t r; asm volatile("atom.shared.add.u32 %0, [%1], 1;" : "=r"(r) : "r"(a) : "memory"); return r; }
__device__ __forceinline__ void tma2d(uint32_t dst, const CUtensorMap* m, int c0, int c1, uint32_t bar) {
  asm volatile("cp.async.bulk.tensor.2d.shared::cluster.global.mbarrier::complete_tx::bytes [%0], [%1, {%3, %4}], [%2];" ::"r"(dst), "l"(m), "r"(bar), "r"(c0), "r"(c1) : "memory");
}
__device__ __forceinline__ void tma3d(uint32_t dst, const CUtensorMap* m, int c1, int c2, uint32_t bar) {
  asm volatile("cp.async.bulk.tensor.3d.shared::cluster.global.mbarrier::complete_tx::bytes [%0], [%1, {%3, %4, %5}], [%2];" ::"r"(dst), "l"(m), "r"(bar), "r"(0), "r"(c1), "r"(c2) : "memory");
}
__device__ __forceinline__ void tma3d_mc(uint32_t dst, const CUtensorMap* m, int c1, int c2, uint32_t bar) {
  asm volatile("cp.async.bulk.tensor.3d.shared::cluster.global.mbarrier::complete_tx::bytes.multicast::cluster [%0], [%1, {%3, %4, %5}], [%2], %6;" ::"r"(dst), "l"(m), "r"(bar), "r"(0), "r"(c1), "r"(c2), "h"((uint16_t)3) : "memory");
}
__device__ __forceinline__ void tma5d(uint32_t dst, const CUtensorMap* m, int c2, int c4, uint32_t bar, bool mc) {
  if (mc) asm volatile("cp.async.bulk.tensor.5d.shared::cluster.global.mbarrier::complete_tx::bytes.multicast::cluster [%0], [%1, {%3, %3, %4, %3, %5}], [%2], %6;" ::"r"(dst), "l"(m), "r"(bar), "r"(0), "r"(c2), "r"(c4), "h"((uint16_t)3) : "memory");
  else asm volatile("cp.async.bulk.tensor.5d.shared::cluster.global.mbarrier::complete_tx::bytes [%0], [%1, {%3, %3, %4, %3, %5}], [%2];" ::"r"(dst), "l"(m), "r"(bar), "r"(0), "r"(c2), "r"(c4) : "memory");
}
__device__ __forceinline__ void mbar_arrive_cta(uint32_t b, uint32_t cta) {
  asm volatile("{\n.reg .b32 ra;\nmapa.shared::cluster.u32 ra, %0, %1;\nmbarrier.arrive.shared::cluster.b64 _, [ra];\n}" ::"r"(b), "r"(cta) : "memory");
}
constexpr uint64_t POL_FIRST = 0x12F0000000000000ull;
__device__ __forceinline__ void tma2d_ef(uint32_t dst, const CUtensorMap* m, int c0, int c1, uint32_t bar) {
  asm volatile("cp.async.bulk.tensor.2d.shared::cluster.global.mbarrier::complete_tx::bytes.L2::cache_hint [%0], [%1, {%3, %4}], [%2], %5;" ::"r"(dst), "l"(m), "r"(bar), "r"(c0), "r"(c1), "l"(POL_FIRST) : "memory");
}
__device__ __forceinline__ void bulk_ld(uint32_t dst, const void* src, uint32_t bytes, uint32_t bar) {
  asm volatile("cp.async.bulk.shared::cluster.global.mbarrier::complete_tx::bytes [%0], [%1], %2, [%3];" ::"r"(dst), "l"(src), "r"(bytes), "r"(bar) : "memory");
}
__device__ __forceinline__ void bulk_pf(const void* src, uint32_t bytes) { asm volatile("cp.async.bulk.prefetch.L2.global [%0], %1;" ::"l"(src), "r"(bytes) : "memory"); }
__device__ __forceinline__ void tma2d_pf(const CUtensorMap* m, int c0, int c1) {
  asm volatile("cp.async.bulk.prefetch.tensor.2d.L2.global [%0, {%1, %2}];" ::"l"(m), "r"(c0), "r"(c1) : "memory");
}
__device__ __forceinline__ void map_pf(const CUtensorMap* m) { asm volatile("prefetch.tensormap [%0];" ::"l"(m) : "memory"); }
__device__ __forceinline__ void line_pf(const void* p) { asm volatile("prefetch.global.L2 [%0];" ::"l"(p)); }
__device__ __forceinline__ void pf128(uint32_t dummy, const void* src) { asm volatile("cp.async.ca.shared.global.L2::128B [%0], [%1], 4;" ::"r"(dummy), "l"(src) : "memory"); }
__device__ __forceinline__ void pf256(uint32_t dummy, const void* src) { asm volatile("cp.async.ca.shared.global.L2::256B [%0], [%1], 4;" ::"r"(dummy), "l"(src) : "memory"); }
__device__ __forceinline__ void cp16x2(uint32_t dst, const void* src) {
  asm volatile("cp.async.cg.shared.global [%0], [%1], 16;\ncp.async.cg.shared.global [%0+4096], [%1+512], 16;" ::"r"(dst), "l"(src) : "memory");
}
constexpr uint32_t HI_SW128 = 0x40000000u | (1024 >> 4), HI_SW64 = 0x80000000u | (512 >> 4), HI_NOSW = 512 >> 4;
__device__ __forceinline__ uint64_t mkdesc(uint32_t lo, uint32_t hi) { uint64_t d; asm("mov.b64 %0, {%1, %2};" : "=l"(d) : "r"(lo), "r"(hi)); return d; }
__device__ __forceinline__ void wg_fence() { asm volatile("wgmma.fence.sync.aligned;" ::: "memory"); }
__device__ __forceinline__ void wg_commit() { asm volatile("wgmma.commit_group.sync.aligned;" ::: "memory"); }
template <int N> __device__ __forceinline__ void wg_wait() { asm volatile("wgmma.wait_group.sync.aligned %0;" ::"n"(N) : "memory"); }
template <int N> __device__ __forceinline__ void reg_fence(float (&a)[N]) {
#pragma unroll
  for (int i = 0; i < N; i++) asm volatile("" : "+f"(a[i])::"memory");
}
template <int ID, int N> __device__ __forceinline__ void bar_sync() { asm volatile("bar.sync %0, %1;" ::"n"(ID), "n"(N) : "memory"); }
__device__ __forceinline__ void fence_async_smem() { asm volatile("fence.proxy.async.shared::cta;" ::: "memory"); }
__device__ __forceinline__ void fence_async_gmem() { asm volatile("fence.proxy.async.global;" ::: "memory"); }
__device__ __forceinline__ uint32_t pack_bf16(float lo, float hi) { uint32_t r; asm("cvt.rn.bf16x2.f32 %0, %1, %2;" : "=r"(r) : "f"(hi), "f"(lo)); return r; }
__device__ __forceinline__ float bf_lo(uint32_t v) { return __uint_as_float(v << 16); }
__device__ __forceinline__ float bf_hi(uint32_t v) { return __uint_as_float(v & 0xFFFF0000u); }
__device__ __forceinline__ float bf_round(float v) { return bf_lo(pack_bf16(v, v)); }
__device__ __forceinline__ uint32_t bf_sub2(uint32_t a, uint32_t b) { uint32_t r; asm("sub.rn.bf16x2 %0, %1, %2;" : "=r"(r) : "r"(a), "r"(b)); return r; }
__device__ __forceinline__ float rcp(float v) { float r; asm("rcp.approx.ftz.f32 %0, %1;" : "=f"(r) : "f"(v)); return r; }
__device__ __forceinline__ float ex2(float v) { float r; asm("ex2.approx.ftz.f32 %0, %1;" : "=f"(r) : "f"(v)); return r; }
__device__ __forceinline__ float sigmoid(float v) { return rcp(1.f + ex2(v * -1.4426950408889634f)); }
__device__ __forceinline__ void stsm4(uint32_t a, uint32_t r0, uint32_t r1, uint32_t r2, uint32_t r3) {
  asm volatile("stmatrix.sync.aligned.m8n8.x4.shared.b16 [%0], {%1,%2,%3,%4};" ::"r"(a), "r"(r0), "r"(r1), "r"(r2), "r"(r3) : "memory");
}
__device__ __forceinline__ void stsm4t(uint32_t a, uint32_t r0, uint32_t r1, uint32_t r2, uint32_t r3) {
  asm volatile("stmatrix.sync.aligned.m8n8.x4.trans.shared.b16 [%0], {%1,%2,%3,%4};" ::"r"(a), "r"(r0), "r"(r1), "r"(r2), "r"(r3) : "memory");
}
__device__ __forceinline__ void ldsm4(uint32_t a, uint32_t& r0, uint32_t& r1, uint32_t& r2, uint32_t& r3) {
  asm volatile("ldmatrix.sync.aligned.m8n8.x4.shared.b16 {%0,%1,%2,%3}, [%4];" : "=r"(r0), "=r"(r1), "=r"(r2), "=r"(r3) : "r"(a) : "memory");
}
__device__ __forceinline__ uint32_t movmat(uint32_t a) { uint32_t d; asm volatile("movmatrix.sync.aligned.m8n8.trans.b16 %0, %1;" : "=r"(d) : "r"(a)); return d; }
__device__ __forceinline__ void sts_h(uint32_t a, float v) { asm volatile("st.shared.u16 [%0], %1;" ::"r"(a), "h"((uint16_t)pack_bf16(v, v)) : "memory"); }
__device__ __forceinline__ float2 lds_f2(uint32_t a) { float2 v; asm volatile("ld.shared.v2.f32 {%0,%1}, [%2];" : "=f"(v.x), "=f"(v.y) : "r"(a)); return v; }
__device__ __forceinline__ float lds_f(uint32_t a) { float v; asm volatile("ld.shared.f32 %0, [%1];" : "=f"(v) : "r"(a)); return v; }
__device__ __forceinline__ float4 lds_f4(uint32_t a) { float4 v; asm volatile("ld.shared.v4.f32 {%0,%1,%2,%3}, [%4];" : "=f"(v.x), "=f"(v.y), "=f"(v.z), "=f"(v.w) : "r"(a)); return v; }
__device__ __forceinline__ uint32_t lds_u(uint32_t a) { uint32_t v; asm volatile("ld.shared.u32 %0, [%1];" : "=r"(v) : "r"(a) : "memory"); return v; }
__device__ __forceinline__ uint4 lds_u4(uint32_t a) { uint4 v; asm volatile("ld.shared.v4.u32 {%0,%1,%2,%3}, [%4];" : "=r"(v.x), "=r"(v.y), "=r"(v.z), "=r"(v.w) : "r"(a) : "memory"); return v; }
__device__ __forceinline__ void sts_u(uint32_t a, uint32_t v) { asm volatile("st.shared.u32 [%0], %1;" ::"r"(a), "r"(v) : "memory"); }
__device__ __forceinline__ void sts_u4(uint32_t a, uint4 v) { asm volatile("st.shared.v4.u32 [%0], {%1,%2,%3,%4};" ::"r"(a), "r"(v.x), "r"(v.y), "r"(v.z), "r"(v.w) : "memory"); }
__device__ __forceinline__ uint4 ldx4(const void* p) { uint4 v; asm volatile("ld.relaxed.gpu.global.v4.u32 {%0,%1,%2,%3}, [%4];" : "=r"(v.x), "=r"(v.y), "=r"(v.z), "=r"(v.w) : "l"(p) : "memory"); return v; }
__device__ __forceinline__ uint2 ldx2(const void* p) { uint2 v; asm volatile("ld.relaxed.gpu.global.v2.u32 {%0,%1}, [%2];" : "=r"(v.x), "=r"(v.y) : "l"(p) : "memory"); return v; }
__device__ __forceinline__ uint32_t ldx1(const void* p) { uint32_t v; asm volatile("ld.relaxed.gpu.global.u32 %0, [%1];" : "=r"(v) : "l"(p) : "memory"); return v; }
__device__ __forceinline__ void stx4(void* p, uint32_t a, uint32_t b, uint32_t c, uint32_t d) { asm volatile("st.relaxed.gpu.global.v4.u32 [%0], {%1,%2,%3,%4};" ::"l"(p), "r"(a), "r"(b), "r"(c), "r"(d) : "memory"); }
__device__ __forceinline__ void stx2(void* p, uint32_t a, uint32_t b) { asm volatile("st.relaxed.gpu.global.v2.u32 [%0], {%1,%2};" ::"l"(p), "r"(a), "r"(b) : "memory"); }
__device__ __forceinline__ void stx1(void* p, uint32_t a) { asm volatile("st.relaxed.gpu.global.u32 [%0], %1;" ::"l"(p), "r"(a) : "memory"); }
__device__ __forceinline__ uint32_t umax4(uint4 v) { return max(max(v.x, v.y), max(v.z, v.w)); }
__device__ __forceinline__ uint32_t f2x(float f) { return min(__float_as_uint(f), 0xFFFFFFFEu); }
__device__ __forceinline__ void red4(float* p, float a, float b, float c, float d) { asm volatile("red.relaxed.gpu.global.add.v4.f32 [%0], {%1,%2,%3,%4};" ::"l"(p), "f"(a), "f"(b), "f"(c), "f"(d) : "memory"); }
__device__ __forceinline__ void cnt_arrive(int c) { asm volatile("red.release.gpu.global.add.u32 [%0], 1;" ::"l"(&G.cnt[c]) : "memory"); }
__device__ __forceinline__ void cnt_wait(int c, uint32_t target) {
#pragma unroll 1
  for (uint32_t it = 0; it < SPIN_MAX; it++) {
    uint32_t v;
    asm volatile("ld.acquire.gpu.global.u32 %0, [%1];" : "=r"(v) : "l"(&G.cnt[c]) : "memory");
    if (v >= target) break;
    __nanosleep(POLLNS);
  }
}
__device__ __forceinline__ void cnt_done() {
  uint32_t t;
  asm volatile("atom.acq_rel.gpu.global.add.u32 %0, [%1], 1;" : "=r"(t) : "l"(&G.cnt[C_DONE]) : "memory");
  if (t == NCTA + NSVC - 1) {
#pragma unroll 1
    for (int i = 0; i < NCNT; i++) G.cnt[i * 32] = 0;
  }
}
__device__ __forceinline__ float phi(float u, float rs, float rl) {
  float a = fmaf(u, rs, 1.000001f), e = ex2(u * rl), r;
  asm("add.sat.f32 %0, %1, 0f358637BD;" : "=f"(e) : "f"(e));
  asm("max.NaN.f32 %0, %1, %2;" : "=f"(r) : "f"(a), "f"(e));
  return r;
}

__device__ __forceinline__ uint32_t phi2(float u0, float rs0, float rl0, float u1, float rs1, float rl1) {
  float e0, e1;
  asm("{\n.reg .f32 t;\nabs.f32 t, %1;\nneg.f32 t, t;\nex2.approx.ftz.f32 %0, t;\n}" : "=f"(e0) : "f"(u0 * rl0));
  asm("{\n.reg .f32 t;\nabs.f32 t, %1;\nneg.f32 t, t;\nex2.approx.ftz.f32 %0, t;\n}" : "=f"(e1) : "f"(u1 * rl1));
  uint32_t e = pack_bf16(e0, e1), r;
  const uint32_t a = pack_bf16(fmaf(u0, rs0, 1.000001f), fmaf(u1, rs1, 1.000001f));
  asm("add.rn.bf16x2 %0, %0, %1;" : "+r"(e) : "r"(0x35863586u));
  asm("max.NaN.bf16x2 %0, %1, %2;" : "=r"(r) : "r"(a), "r"(e));
  return r;
}

__device__ __forceinline__ int kstep1(int e, int hg) { return e < 14 ? (e < 2 * hg ? e : e + 2) : 2 * hg + e - 14; }
__device__ __forceinline__ int slab(int n, int hg) {
  return n + (((n + 7 - hg) * 37) >> 8);
}
__host__ __device__ constexpr uint32_t d_off(int i) { return i < 3 ? 12 * SLOT + (NR == 4 ? i : (i == 2 ? 0 : i + 1)) * MT : (i < 5 ? S_D0 * SLOT + (i - 3) * 8192 : S_D1 * SLOT + (i - 5) * 8192); }
__host__ __device__ constexpr uint32_t h_off(int i) { return i < 3 ? 12 * SLOT + i * MT + 8192 : (i < 5 ? A_ONES + (i - 3) * 1024 : MISC + M_MOE + (i - 5) * 1024); }
__device__ __forceinline__ uint32_t m_off(int r) { return r < 3 ? 12 * SLOT + r * MT : S_M3 * SLOT; }
__device__ __forceinline__ int x_slot(int e, int s) { return NQ == 5 ? (e < 14 ? s : e - 11) : (e < 13 ? s : 3 + s); }
__device__ __forceinline__ uint32_t wo_slot(int i) { return (uint32_t)(WO_SLOTS >> (4 * i)) & 15u; }

__global__ void __launch_bounds__(512, 1)
fused_kernel(const __nv_bfloat16* __restrict__ x, const __nv_bfloat16* __restrict__ wqkv, const __nv_bfloat16* __restrict__ wo,
             const __nv_bfloat16* __restrict__ wr, const __nv_bfloat16* __restrict__ wd, const int by_sm,
             const __grid_constant__ CUtensorMap tmX, const __grid_constant__ CUtensorMap tmW,
             const __grid_constant__ CUtensorMap tmWo, const __grid_constant__ CUtensorMap tmOut,
             const __grid_constant__ CUtensorMap tmG, const __grid_constant__ CUtensorMap tmU,
             const __grid_constant__ CUtensorMap tmD, const __grid_constant__ CUtensorMap tmR,
             const __grid_constant__ CUtensorMap tmWp) {
  if (TMP && threadIdx.x == 32 * TMPW) { map_pf(&tmX); map_pf(&tmW); }
  extern __shared__ __align__(1024) uint8_t smem_raw[];
  const uint32_t sb = (uint32_t)__cvta_generic_to_shared(smem_raw);
  const uint32_t bars = sb + MISC + M_BAR;
  uint32_t smid;
  asm("mov.u32 %0, %%smid;" : "=r"(smid));
  const int tpc = smid >> 1;
  int cl = tpc + max(((tpc - 25) * 37) >> 8, 0);
  cl = tpc < 60 ? cl : cl - 1;
  cl = tpc < 62 ? cl : (tpc - 58) * 8;
  const int u = by_sm ? 2 * cl + (blockIdx.x & 1) : blockIdx.x;
  const int hg = (u >> 4) & 7, tb = u & 15;
  const int b = tb * 8 + hg;
  const int lane = threadIdx.x & 31;
  const int warp = __shfl_sync(~0u, threadIdx.x >> 5, 0);
  const int ltid = threadIdx.x;
  const int g = lane >> 2, t = lane & 3;
  const uint32_t d0 = (sb & 0x3FFFF) >> 4;
#define BAR(i) (bars + 8 * (i))
  TLS(0, 0);

  const int rank = u & 1;
  auto load_entry = [&](int e, int s) {
    const int k0 = kstep1(e, hg) * 64;
    mbar_expect_tx(BAR(B_FXQ + s), e < NF ? 2 * SLOT : SLOT);
    mbar_expect_tx(BAR(B_FKV + s), R5 ? SLOT : 2 * SLOT);
    if (R5 && e < 11) mbar_expect_tx(BAR(B_FV + s), SLOT);
    const uint32_t vb = R5 ? BAR(B_FV + s) : BAR(B_FKV + s);
    tma2d(sb + x_slot(e, s) * SLOT, &tmX, k0, tb * 128, BAR(B_FXQ + s));
    if (e < MC0 || !(MC & 1)) {
      if (e < NF) tma3d(sb + (3 + s) * SLOT, &tmW, k0, 2 * hg, BAR(B_FXQ + s));
      tma3d(sb + (6 + 2 * s) * SLOT, &tmW, k0, 16 + 2 * hg, BAR(B_FKV + s));
      tma3d(sb + (7 + 2 * s) * SLOT, &tmW, k0, 32 + 2 * hg, vb);
    } else {
      if (e < NF && (e & 1) == rank) tma3d_mc(sb + (3 + s) * SLOT, &tmW, k0, 2 * hg, BAR(B_FXQ + s));
      if (R5 && e >= 11) { if (rank == 0) tma3d_mc(sb + ((K_SLOTS >> (4 * (e - 10))) & 15u) * SLOT, &tmW, k0, 16 + 2 * hg, BAR(B_FKV + s)); }
      else tma3d_mc(sb + (6 + 2 * s + rank) * SLOT, &tmW, k0, 16 + 16 * rank + 2 * hg, rank ? vb : BAR(B_FKV + s));
    }
  };
  if (warp == FW && u < NCTA) {
    if (elect_one()) {
      mbar_init(BAR(B_FXQ), 1); mbar_init(BAR(B_FKV), 1);
      if (R5) mbar_init(BAR(B_FV), 1);
      load_entry(0, 0);
      asm volatile("fence.mbarrier_init.release.cluster;" ::: "memory");
      TLS(FW * 32, 61);
    }
    __syncwarp();
  }
  if (u >= NCTA) {
    const int j = u - NCTA;
    if (warp == 8 && elect_one()) {
#pragma unroll
      for (int i = 0; i < 13; i++) mbar_init(BAR(i), 1);
    }
    if (ltid < 64) sts_u4(sb + MISC + ltid * 16, make_uint4(0x3F803F80u, 0x3F803F80u, 0x3F803F80u, 0x3F803F80u));
    fence_async_smem();
    __syncthreads();
    if (warp < 4) {
      int s = 0, p = 0;
#pragma unroll 1
      for (int pass = 0; pass < 3; pass++) {
        float acc[4][4];
#pragma unroll
        for (int c = 0; c < 4; c++) acc[c][0] = acc[c][1] = acc[c][2] = acc[c][3] = 0.f;
#pragma unroll 1
        for (int k = 0; k < 16; k++) {
          mbar_wait(BAR(s), p);
          wg_fence();
#pragma unroll
          for (int c = 0; c < 4; c++)
#pragma unroll
            for (int kk = 0; kk < 4; kk++)
              wgmma_ss_n8<1, 0>(acc[c], mkdesc((d0 + s * 2048 + c * 512 + kk * 128) | (512u << 16), HI_SW128), mkdesc((d0 + (MISC >> 4)) | (1u << 16), HI_SW128));
          wg_commit();
          wg_wait<0>();
          if (ltid == 0) mbar_arrive(BAR(6 + s));
          if (++s == SVS) { s = 0; p ^= 1; }
        }
        uint32_t* pc = G.cs + (pass < 2 ? DM + pass * DM : 0) + j * 256 + warp * 16 + g;
#pragma unroll
        for (int c = 0; c < 4; c++) {
          reg_fence(acc[c]);
          const uint32_t v = __float_as_uint((t & 1) ? acc[c][2] : acc[c][0]);
          if (t < 2) stx1(pc + c * 64 + t * 8, v ? v : 0x80000000u);
        }
        TLS(0, 1 + pass);
      }
    } else if (warp >= 8 && j == 0) {
      const int wq = warp - 8;
      const uint32_t top = sb + MISC + 1024;
#pragma unroll 1
      for (uint32_t it = 0; it < SPIN_MAX; it++) {
        const uint4 v0 = ldx4(G.key + wq * 256 + lane * 4), v1 = ldx4(G.key + wq * 256 + 128 + lane * 4);
        uint32_t ok;
        asm volatile("{\n.reg .pred p, q;\nsetp.ne.u32 p, %1, 0;\nbar.red.and.pred q, 2, 256, p;\nselp.b32 %0, 1, 0, q;\n}" : "=r"(ok) : "r"((v0.x & v0.y & v0.z & v0.w & v1.x & v1.y & v1.z & v1.w) >> 27) : "memory");
        ok = __any_sync(~0u, ok);
        if (!ok && it) continue;
        TLS(256, 4);
        uint32_t np = 0u - (1u << 28), mine = 0;
#pragma unroll 1
        for (int r = 0; r < 8; r++) {
          const uint32_t m0 = __viaddmax_u32(v0.x, np, v0.y + np), m1 = __viaddmax_u32(v0.z, np, v0.w + np), m2 = __viaddmax_u32(v1.x, np, v1.y + np), m3 = __viaddmax_u32(v1.z, np, v1.w + np);
          np -= __reduce_max_sync(~0u, max(max(m0, m1), max(m2, m3)));
          if (g == r) mine = 0u - np;
        }
        if (t == 0) sts_u(top + (wq * 8 + g) * 4, mine);
        bar_sync<2, 256>();
        TLS(256, 5);
        int rk = 0;
#pragma unroll
        for (int i = 0; i < 4; i++) {
          const uint4 o = lds_u4(top + t * 64 + i * 16);
          rk += (o.x > mine) + (o.y > mine) + (o.z > mine) + (o.w > mine);
        }
        rk += __shfl_xor_sync(~0u, rk, 1);
        rk += __shfl_xor_sync(~0u, rk, 2);
        if (ok) { if (rk < 8) stx1(G.top + t * 32 + rk, mine); break; }
        __nanosleep(2500);
      }
      TLS(256, 7);
    } else if (warp == 4) {
      int s = 0, p = 1;
      if (SVD) __nanosleep(SVD);
#pragma unroll 1
      for (int i = 0; i < 48; i++) {
        mbar_wait(BAR(6 + s), p);
        if (j == 0 && i >= SV0A && i < SV0B) mbar_wait(BAR(s >= SV0 ? s - SV0 : s - SV0 + SVS), s >= SV0 ? p ^ 1 : p);
        if (elect_one()) {
          mbar_expect_tx(BAR(s), 2 * SLOT);
          const int ch = (i < 32 ? 16 + (i & 16) : 0) + j * 4, k0 = (i & 15) * 64;
          tma3d(sb + s * 2 * SLOT, &tmW, k0, ch, BAR(s));
          tma3d(sb + s * 2 * SLOT + SLOT, &tmW, k0, ch + 2, BAR(s));
        }
        if (++s == SVS) { s = 0; p ^= 1; }
      }
    }
    if (ltid == 0) cnt_wait(C_DONE, NCTA);
    __syncthreads();
    const uint4 zero = make_uint4(0, 0, 0, 0);
    if (ltid < 128) reinterpret_cast<uint4*>(G.key)[j * 128 + ltid] = zero;
    else if (ltid < 320) reinterpret_cast<uint4*>(G.cs)[j * 192 + ltid - 128] = zero;
    else if (ltid < 322) reinterpret_cast<uint4*>(G.top)[j * 8 + ltid - 320] = zero;
    if (ltid == 0) { cnt_done(); TLDUMP(); }
    return;
  }

  if (warp == 12) {
    if (elect_one()) {
#pragma unroll
      for (int i = 1; i < 7; i++) if (i != B_FKV) mbar_init(BAR(i), 1);
      if (R5) { mbar_init(BAR(B_FV + 1), 1); mbar_init(BAR(B_FV + 2), 1); }
      if (E1E) load_entry(1, 1);
      asm volatile("fence.mbarrier_init.release.cluster;" ::: "memory");
    }
  } else if (warp >= 13) {
    if (elect_one()) {
      if (warp == 15) {
#pragma unroll
        for (int i = B_FAUX; i < NBAR; i++) mbar_init(BAR(i), i < B_E || !MC ? 2 : 4);
        mbar_init(BAR(B_KV4), 4); mbar_init(BAR(B_MS), 2);
        if (R5) { mbar_init(BAR(B_EK), 4); mbar_init(BAR(B_EK + 1), 4); mbar_init(BAR(B_EK + 2), 4); }
      } else {
#pragma unroll
        for (int i = 0; i < 23; i++) mbar_init(BAR((warp == 13 ? 7 : 30) + i), 1);
      }
      asm volatile("fence.mbarrier_init.release.cluster;" ::: "memory");
    }
  }
  __syncthreads();
  if (MC) asm volatile("barrier.cluster.arrive.relaxed.aligned;" ::: "memory");

  const bool unit = u < NUNIT;
  const int dcol = (u & 15) * 64, drow = (u >> 4) * 448;
  if (warp >= 12) {
    asm volatile("setmaxnreg.dec.sync.aligned.u32 %0;" ::"n"(PROD_REGS));
    if (MC && warp != 12) asm volatile("barrier.cluster.wait.aligned;" ::: "memory");
    if (warp == 12) {
      int s = 1 + E1E, p = 1, pn = 3;
#pragma unroll 1
      for (int e = 1 + E1E; e < 16; e++) {
        if (MC && e == MC0) asm volatile("barrier.cluster.wait.aligned;" ::: "memory");
        if (e == GATE) mbar_wait(BAR(B_FXQ), 0);
        mbar_wait(BAR(B_E + s), p);
        if (elect_one()) {
          load_entry(e, s);
          if (NR == 4 && e == 11) mbar_arrive(BAR(B_ME + 3));
          if (e == ASTE) {
            mbar_expect_tx(BAR(B_AST), 2 * SLOT + 2048);
            bulk_ld(sb + 12 * SLOT, x + (size_t)b * 16 * DM, 2 * SLOT, BAR(B_AST));
            bulk_ld(sb + MISC + M_MOE, wr, 2048, BAR(B_AST));
          } else if (e >= 3) {
            if (e < 6) bulk_pf(wqkv + (size_t)((e - 2) * 256 + 2 * b) * 3 * DM, 2 * 3 * DM * 2);
            if (e < 7) bulk_pf(wo + (size_t)((e - 3) * 256 + 2 * b) * DM, 2 * DM * 2);
            if (NUNIT) {
#pragma unroll 1
              for (int i = (PFTAB >> (4 * (e - 3))) & 15; i > 0; i--, pn++) {
                if (pn >= 16) { if (!(MX & 8)) tma2d_pf(&tmD, dcol, drow + (pn - 16) * 64); }
                else if (unit && !(MX & 2)) tma2d_pf(rank ? &tmU : &tmG, (u >> 1) * 64, pn * 64);
              }
            }
          }
        }
        if (R5 && e >= 11) {
          mbar_wait(BAR(B_EK + (s == 2 ? 0 : s + 1)), e >= 14);
          if (elect_one()) {
            mbar_expect_tx(BAR(B_FV + s), SLOT);
            if (rank) tma3d_mc(sb + ((V_SLOTS >> (4 * (e - 10))) & 15u) * SLOT, &tmW, kstep1(e, hg) * 64, 32 + 2 * hg, BAR(B_FV + s));
          }
        }
        if (++s == 3) { s = 0; p ^= 1; }
      }
#pragma unroll 1
      for (int k = 0; k < NQ; k++) {
        if (k == 0) mbar_wait(BAR(B_E + 1), 0);
        if (k == 1) mbar_wait(BAR(B_EK + 2), 1);
        if (k == 2) mbar_wait(BAR(B_EK + 0), 0);
        if (k == 3) mbar_wait(BAR(B_STG), 0);
        if (k == 5) mbar_wait(BAR(B_EQ), 0);
        if (elect_one()) {
          const int k0 = kstep1(NF + k, hg) * 64;
          mbar_expect_tx(BAR(B_FQ + k), SLOT);
          if (!(MC & 2)) tma3d(sb + ((QW_SLOTS >> (4 * k)) & 15u) * SLOT, &tmW, k0, 2 * hg, BAR(B_FQ + k));
          else if ((k & 1) == rank) tma3d_mc(sb + ((QW_SLOTS >> (4 * k)) & 15u) * SLOT, &tmW, k0, 2 * hg, BAR(B_FQ + k));
        }
      }
#pragma unroll 1
      for (int i = 0; i < 16; i++) {
        mbar_wait(i < 7 ? BAR(B_EQ + ((i + WQ0) >> 1)) : (i < 9 ? BAR(B_DE) : BAR(B_EO + i - 9)), 0);
        if (i == WOK) mbar_wait(BAR(B_KVB), 0);
        mbar_wait(BAR(B_FWO + i - (i < WOK ? WOD1 : WOD)), 0);
        if (elect_one()) {
          mbar_expect_tx(BAR(B_FWO + i), SLOT);
#pragma unroll
          for (int hf = 0; hf < ((MC & 4) ? 1 : 2); hf++) {
            const int n = 2 * i + ((MC & 4) ? rank : hf), m = slab(n - 4, hg), hd = n < 4 ? 4 * hg + n : 4 * (m & 7) + (m >> 3);
            if (i < 2 + NDIR) tma5d(sb + wo_slot(i) * SLOT + (n & 1) * 8192, &tmWp, hd * 4, 2 * hg, BAR(B_FWO + i), MC & 4);
            else if (MC & 4) tma3d_mc(sb + wo_slot(i) * SLOT + rank * 8192, &tmWo, hd * 32, 2 * hg, BAR(B_FWO + i));
            else tma3d(sb + wo_slot(i) * SLOT + hf * 8192, &tmWo, hd * 32, 2 * hg, BAR(B_FWO + i));
          }
        }
      }
    } else if (warp == 13) {
      if (elect_one()) {
        map_pf(rank ? &tmU : &tmG); map_pf(&tmR); map_pf(&tmD); map_pf(&tmWo); map_pf(&tmWp); map_pf(&tmOut);
      }
      bar_sync<6, 64>();
      if (elect_one()) {
        cnt_wait(C_B, NCTA);
        fence_async_gmem();
        mbar_expect_tx(BAR(B_FAUX), 1024);
        bulk_ld(sb + A_ST, G.stats + tb * 128, 1024, BAR(B_FAUX));
      }
      __syncwarp();
      TLS(416, 68);
#pragma unroll 1
      for (int m = 1; m < 4; m++) {
        const int part = m == 3 ? 0 : m;
        uint4 c;
#pragma unroll 1
        for (uint32_t it = 0; it < SPIN_MAX; it++) {
          c = ldx4(G.cs + part * DM + hg * 128 + lane * 4);
          if (__all_sync(~0u, min(min(c.x, c.y), min(c.z, c.w)))) break;
          __nanosleep(POLLNS);
        }
        sts_u4(sb + A_CS + part * 512 + lane * 16, c);
        __syncwarp();
        if (m > 1 && lane == 0) mbar_arrive(BAR(m == 2 ? B_FAUX : B_CQ));
        TLS(416, 71 + m);
      }
      mbar_wait(BAR(B_XS), 1);
      if (elect_one()) asm volatile("red.relaxed.gpu.global.add.u32 [%0], 1;" ::"l"(&G.cnt[C_DONE]) : "memory");
    } else if (warp == 14) {
      const uint4 sent = make_uint4(SENT, SENT, SENT, SENT);
      uint4* ro = G.o + (tb * 32 + hg) * 512 + lane;
      uint4* rp = G.part + b * 544 + lane;
      if (RSL) bar_sync<5, 160>(); else mbar_wait(BAR(B_AST), 0);
#pragma unroll 1
      for (int i = RS0; i < 40; i++) {
        uint4* q = i < 32 ? ro + (i >> 3) * 4096 + (i & 7) * 64 : rp + (i - 32) * 64;
        q[0] = sent; q[32] = sent;
        __nanosleep(RSNS);
      }
      rp[512] = sent;
#pragma unroll
      for (int i = 0; i < 4; i++) G.y[u * 128 + i * 32 + lane] = sent;
      if (unit) reinterpret_cast<uint4*>(G.h)[u * 32 + lane] = sent;
      G.fin[hg * 640 + tb * 40 + lane] = sent;
      if (lane < 8) G.fin[hg * 640 + tb * 40 + 32 + lane] = sent;
      if (!RSL) bar_sync<5, 160>();
      __syncwarp();
      TLS(448, 67);
      if (lane == 0) cnt_arrive(C_B);
      __syncwarp();
      TLS(448, 32);
      asm volatile("bar.arrive 6, 64;" ::: "memory");
    } else {
      const uint32_t stg = sb + 12 * SLOT;
      auto load_a = [&](int n, int r) {
        mbar_expect_tx(BAR(B_MF + r), (MX & 2) ? 1024 : MT);
        if (!(MX & 2)) tma2d_ef(sb + m_off(r), rank ? &tmU : &tmG, (u >> 1) * 64, n * 64, BAR(B_MF + r));
      };
      mbar_wait(BAR(B_XS), 0);
      if (unit) {
#pragma unroll 1
        for (int i = 0; i < 3; i++) {
          if (elect_one()) load_a(i, i);
          __nanosleep(PFILL);
        }
      }
      uint32_t key;
#pragma unroll 1
      for (uint32_t it = 0; it < SPIN_MAX; it++) {
        key = ldx1(G.top + ((u >> 1) & 3) * 32 + (lane & 7));
        if (__all_sync(~0u, key)) break;
        __nanosleep(TPNS);
      }
      TLS(480, 66);
      if (lane < 8) sts_u(sb + MISC + M_IDX + lane * 4, key);
      __syncwarp();
      if (lane == 0) mbar_arrive(BAR(B_XS));
      if (unit) {
        int tok[8];
#pragma unroll
        for (int i = 0; i < 8; i++) tok[i] = ~__shfl_sync(~0u, key, i) & 2047;
        int r = 0, p = 0;
#pragma unroll 1
        for (int n = 0; n < 16; n++) {
          if (n >= 3) mbar_wait(BAR(B_ME + r), r == 3 ? p : p ^ 1);
          if (elect_one()) {
            if (n >= 3) load_a(n, r);
#pragma unroll
            for (int i = 0; i < 8; i++) tma2d(sb + m_off(r) + 8192 + i * 128, &tmR, n * 64, tok[i], BAR(B_MF + r));
          }
          if (++r == NR) { r = 0; p ^= 1; }
        }
      }
      if (NUNIT) {
        if (lane == 0) mbar_expect_tx(BAR(B_DF), (MX & 8) ? 0 : 7 * 8192);
#pragma unroll 1
        for (int i = 0; i < 7; i++) {
          if (NR == 4) {
            if (i >= 3) mbar_wait(i < 5 ? BAR(B_ME + 3) : (R5 ? BAR(B_EQ + 1) : BAR(B_STG)), 0);
            else if (unit) mbar_wait(BAR(B_ME + i), 1);
          } else {
            if (i >= 3) mbar_wait(BAR(B_EQ + ((i - 3) >> 1)), 0);
            else if (unit) mbar_wait(BAR(B_ME + (i == 2 ? 0 : i + 1)), i == 2);
          }
          if (!(MX & 8) && elect_one()) tma2d_ef(sb + d_off(i), &tmD, dcol, drow + i * 64, BAR(B_DF));
          if (DNS) __nanosleep(DNS);
        }
      }
    }
    if (warp == 14) {
      if (DPF && NUNIT && !(MX & 8)) {
        mbar_wait(DS ? BAR(B_MS) : (DPF == 1 ? BAR(B_FQ) : BAR(B_T0)), 0);
#pragma unroll 1
        for (int pf = 0; pf < 7; pf++) { pf256(sb + MISC + M_DUM, wd + (size_t)(drow + pf * 64 + rank * 32 + lane) * DM + (dcol & ~127)); __nanosleep(PFNS2); }
      }
      const uint32_t* src = reinterpret_cast<const uint32_t*>(G.part + ((lane >> 3) * 32 + hg) * 544 + 512) + tb * 8 + (lane & 7);
      mbar_wait(BAR(B_EQ + MRW), 0);
      if (MRD) __nanosleep(MRD);
      uint32_t z0, z1, z2, z3;
#pragma unroll 1
      for (uint32_t it = 0; it < SPIN_MAX; it++) {
        z0 = ldx1(src); z1 = ldx1(src + 8 * 2176); z2 = ldx1(src + 16 * 2176); z3 = ldx1(src + 24 * 2176);
        if (!__any_sync(~0u, max(max(z0, z1), max(z2, z3)) == SENT)) break;
      }
      if (MRED == 2 && elect_one()) mbar_arrive(BAR(B_ZOK));
      float zz = (__uint_as_float(z0) + __uint_as_float(z1)) + (__uint_as_float(z2) + __uint_as_float(z3));
      zz += __shfl_xor_sync(~0u, zz, 8);
      zz += __shfl_xor_sync(~0u, zz, 16);
      stx1(reinterpret_cast<uint32_t*>(G.fin + hg * 640) + (tb >> 2) * 640 + 512 + ((tb >> 1) & 1) * 64 + (lane & 1) * 32 + (tb & 1) * 16 + ((lane & 7) >> 1) * 4 + (lane >> 3),
           pack_bf16(zz, zz));
      TLS(448, 12);
    }
    if (!MFIN && (warp == 13 || warp == 14)) {
      mbar_wait(BAR(B_EQ + H2W), 0);
      if (H2D) __nanosleep(H2D);
#pragma unroll 1
      for (uint32_t it = 0; it < SPIN_MAX; it++) {
        if (warp == 14 && elect_one()) { mbar_expect_tx(BAR(B_FIN), 10240); bulk_ld(sb + S_KVB * SLOT, G.fin + hg * 640, 10240, BAR(B_FIN)); }
        mbar_wait(BAR(B_FIN), it & 1);
        uint32_t m = 0;
#pragma unroll
        for (int i = 0; i < 10; i++) m = max(m, lds_u(sb + S_KVB * SLOT + (i * 64 + ltid - 416) * 16 + (g >> 1) * 4));
        uint32_t bad;
        asm volatile("{\n.reg .pred p, q;\nsetp.eq.u32 p, %1, 0xFFFFFFFF;\nbar.red.or.pred q, 7, 64, p;\nselp.b32 %0, 1, 0, q;\n}" : "=r"(bad) : "r"(m) : "memory");
        if (!__any_sync(~0u, bad)) break;
      }
      if (warp == 14 && elect_one()) mbar_arrive(BAR(B_KVB));
      TLS(448, 14);
    }
    if (PH && (warp == 13 || warp == 14)) {
      bar_sync<3, 192>();
      mbar_wait(BAR(B_STG), 0);
#pragma unroll 1
      for (uint32_t it = 0; NUNIT && it < SPIN_MAX; it++) {
        if (elect_one()) {
          const uint32_t* ph = G.h + (u >> 4) * 7 * 256;
          if (warp == 13) { mbar_expect_tx(BAR(B_HF), 7168); bulk_ld(sb + h_off(3), ph + 768, 2048, BAR(B_HF)); bulk_ld(sb + h_off(5), ph + 1280, 2048, BAR(B_HF)); }
          else { bulk_ld(sb + h_off(0), ph, 1024, BAR(B_HF)); bulk_ld(sb + h_off(1), ph + 256, 1024, BAR(B_HF)); bulk_ld(sb + h_off(2), ph + 512, 1024, BAR(B_HF)); }
        }
        mbar_wait(BAR(B_HF), it & 1);
        uint32_t m = 0;
#pragma unroll
        for (int i = 0; i < 7; i++) m = max(m, lds_u(sb + h_off(i) + (ltid - 416) * 16 + (g >> 1) * 4));
        uint32_t bad;
        asm volatile("{\n.reg .pred p, q;\nsetp.eq.u32 p, %1, 0xFFFFFFFF;\nbar.red.or.pred q, 7, 64, p;\nselp.b32 %0, 1, 0, q;\n}" : "=r"(bad) : "r"(m) : "memory");
        if (!__any_sync(~0u, bad)) break;
        __nanosleep(POLLNS);
      }
      if (warp == 14 && elect_one()) mbar_arrive(BAR(B_KVB));
    }
    __syncwarp();
    if (warp >= 13) {
      const char* og = reinterpret_cast<const char*>(G.o + tb * 16384);
      auto probe = [&](uint32_t m) {
        const char* p = og + m * 8192u + (lane & 15) * 512 + 496;
#pragma unroll 1
        for (uint32_t it = 0; it < SPIN_MAX; it++)
          if (!__any_sync(~0u, ldx1(p) == SENT)) break;
      };
      if (warp == 15) {
        int r = 0, p = 1;
        mbar_wait(BAR(B_EAUX), 0);
#pragma unroll 1
        for (int i = I0; i < 16; i++) {
          const uint32_t dst = sb + ((A_SLOTS >> (4 * r)) & 15u) * SLOT, m0 = slab(2 * i - 4, hg), m1 = slab(2 * i - 3, hg);
          if (i == I0 + 3) mbar_wait(BAR(B_DE), 0);
          mbar_wait(BAR(B_EA + r), p);
          if ((PROBE >> i) & 1) probe(lane < 16 ? m0 : m1);
          if (elect_one()) {
            mbar_expect_tx(BAR(B_AF + r), SLOT);
            bulk_ld(dst, og + m0 * 8192u, 8192, BAR(B_AF + r)); bulk_ld(dst + 8192, og + m1 * 8192u, 8192, BAR(B_AF + r));
          }
          if (++r == NA) { r = 0; p ^= 1; }
        }
      } else {
        const uint32_t lo = lane * 32 + g * 4, hb = sb + (warp - 13) * 8192;
        uint32_t ph = 0;
        int r = 0, p = 0;
#pragma unroll 1
        for (int i = I0; i < 16; i++) {
          const uint32_t mine = hb + ((A_SLOTS >> (4 * r)) & 15u) * SLOT;
          auto bad = [&]() {
            uint32_t v[8];
#pragma unroll
            for (int j = 0; j < 8; j++) v[j] = lds_u(mine + lo + j * 1024);
            return __any_sync(~0u, max(max(max(v[0], v[1]), max(v[2], v[3])), max(max(v[4], v[5]), max(v[6], v[7]))) == SENT);
          };
          mbar_wait(BAR(B_AF + r), p);
          if (!NOVAL && bad()) {
            const uint32_t m = slab(2 * i - 17 + warp, hg);
#pragma unroll 1
            for (uint32_t it = 0; it < 64; it++) {
              probe(m);
              if (elect_one()) { mbar_expect_tx(BAR(B_AR + warp - 13), 8192); bulk_ld(mine, og + m * 8192u, 8192, BAR(B_AR + warp - 13)); }
              mbar_wait(BAR(B_AR + warp - 13), ph);
              ph ^= 1;
              if (!bad()) break;
            }
          }
          if (elect_one()) mbar_arrive(BAR(B_VAL + r));
          if (++r == NA) { r = 0; p ^= 1; }
        }
      }
    }
  } else if (warp >= 8) {
    asm volatile("setmaxnreg.dec.sync.aligned.u32 %0;" ::"n"(MOE_REGS));
    if (MC) asm volatile("barrier.cluster.wait.aligned;" ::: "memory");
    const int aw = warp - 8;
    const uint32_t mbuf = sb + MISC + M_MOE, stg = sb + 12 * SLOT;
    mbar_wait(BAR(B_AST), 0);
    TLS(288, 64);
    {
      float v[16];
#pragma unroll
      for (int r = 0; r < 16; r++) v[r] = 0.f;
      const uint32_t base = stg + aw * 4 * 2048 + lane * 8;
#pragma unroll 1
      for (int c = 0; c < 8; c++) {
        const float2 w2 = lds_f2(mbuf + c * 256 + lane * 8);
        const float w[4] = {bf_lo(__float_as_uint(w2.x)), bf_hi(__float_as_uint(w2.x)), bf_lo(__float_as_uint(w2.y)), bf_hi(__float_as_uint(w2.y))};
        v[12] += (w[0] + w[1]) + (w[2] + w[3]);
#pragma unroll
        for (int r = 0; r < 4; r++) {
          const float2 x2 = lds_f2(base + r * 2048 + c * 256);
#pragma unroll
          for (int e = 0; e < 2; e++) {
            const uint32_t xx = __float_as_uint(e ? x2.y : x2.x);
            const float lo = bf_lo(xx), hi = bf_hi(xx);
            v[r] += lo; v[4 + r] = fmaf(lo, lo, v[4 + r]); v[8 + r] = fmaf(lo, w[2 * e], v[8 + r]);
            v[r] += hi; v[4 + r] = fmaf(hi, hi, v[4 + r]); v[8 + r] = fmaf(hi, w[2 * e + 1], v[8 + r]);
          }
        }
      }
#pragma unroll
      for (int l = 0; l < 4; l++) {
        const int n = 8 >> l;
        const bool up = lane & (2 * n);
#pragma unroll
        for (int r = 0; r < 8; r++) {
          if (r < n) { const float a = v[r], c = v[n + r]; v[r] = (up ? c : a) + __shfl_xor_sync(~0u, up ? a : c, 2 * n); }
        }
      }
      v[0] += __shfl_xor_sync(~0u, v[0], 1);
      const float sx = __shfl_sync(~0u, v[0], 2 * t), sq = __shfl_sync(~0u, v[0], 8 + 2 * t), sw = __shfl_sync(~0u, v[0], 16 + 2 * t), ws = __shfl_sync(~0u, v[0], 24);
      if (lane < 4) {
        const int row = b * 16 + aw * 4 + lane;
        const float mean = sx * (1.f / DM);
        const float var = fmaxf(fmaf(-mean, mean, sq * (1.f / DM)), 0.f);
        float sd;
        asm("sqrt.approx.ftz.f32 %0, %1;" : "=f"(sd) : "f"(bf_round(bf_round(var) + 1e-5f)));
        const float rstd = rcp(bf_round(sd));
        const float mb = bf_round(mean);
        uint32_t rb = pack_bf16(fmaf(-mb, ws, sw) * rstd, 0.f) & 0xFFFFu;
        rb = (rb & 0x8000u) ? (~rb & 0xFFFFu) : (rb | 0x8000u);
        const uint32_t key = (1u << 27) | (rb << 11) | (uint32_t)(2047 - row);
        if (KEY1) sts_u(sb + MISC + M_KEY + (aw * 4 + lane) * 4, key); else stx1(G.key + row, key);
        G.stats[row] = make_float2(mb, rstd);
      }
    }
    bar_sync<2, 128>();
    if (KEY1 && ltid < 272) stx1(G.key + b * 16 + lane, lds_u(sb + MISC + M_KEY + lane * 4));
    TLS(288, 65);
    sts_u4(sb + A_ONES + (ltid - 256) * 16, make_uint4(0x3F803F80u, 0x3F803F80u, 0x3F803F80u, 0x3F803F80u));
    fence_async_smem();
    asm volatile("bar.arrive 5, 160;" ::: "memory");
    if (ltid == 256) { if (unit && rank == 0) mbar_expect_tx(BAR(B_UP), 2048); mbar_arrive(BAR(B_XS)); }
    bar_sync<2, 128>();
    mbar_wait(BAR(B_XS), 1);
    TLS(288, 70);
    if (NUNIT) {
      if (unit) {
        int r = 0, p = 0;
        uint32_t rel = 0;
        float acc[8];
        uint2 s0, s1;
#pragma unroll
        for (int i = 0; i < 8; i++) acc[i] = 0.f;
        if (MS == 16) mbar_wait(BAR(B_T0), 0); else if (MS) mbar_wait(BAR(B_MS), 0);
#pragma unroll 1
        for (int n = 0; n < 16; n++) {
          if (n == 15) {
            mbar_wait(BAR(B_FAUX), 0);
            s0 = ldx2(G.stats + (~lds_u(sb + MISC + M_IDX + t * 8) & 2047)); s1 = ldx2(G.stats + (~lds_u(sb + MISC + M_IDX + t * 8 + 4) & 2047));
          }
          mbar_wait(BAR(B_MF + r), p);
          if (!(n & 3)) TLS(288, 56 + (n >> 2));
          const uint32_t mo = m_off(r) >> 4, da = (d0 + mo) | (512u << 16), db = (d0 + mo + 512) | (1u << 16);
          const uint32_t hb = 0x40000000u | ((A_ONES >> 4) - 512 - mo);
          wg_fence();
#pragma unroll
          for (int kk = 0; kk < ((MX & 1) ? 1 : 4); kk++) wgmma_ss_n16<1, 0>(acc, mkdesc(da + kk * 128, HI_SW128), mkdesc(db + kk * 2, hb));
          wg_commit();
          wg_wait<1>();
          if (n > 0 && !rel && ltid == 256) mbar_arrive(BAR(B_ME + (r == 0 ? NR - 1 : r - 1)));
          rel = 0;
          const int r0 = r;
          if (++r == NR) { r = 0; p ^= 1; }
        }
        wg_wait<0>();
        reg_fence(acc);
        {
          if (!MW0 && !rel && ltid == 256) mbar_arrive(BAR(B_ME + 15 % NR));
          TLS(288, 71);
          const float v0 = bf_round(fmaf(-__uint_as_float(s0.x), acc[4], acc[0]) * __uint_as_float(s0.y));
          const float v1 = bf_round(fmaf(-__uint_as_float(s1.x), acc[4], acc[1]) * __uint_as_float(s1.y));
          const float v2 = bf_round(fmaf(-__uint_as_float(s0.x), acc[6], acc[2]) * __uint_as_float(s0.y));
          const float v3 = bf_round(fmaf(-__uint_as_float(s1.x), acc[6], acc[3]) * __uint_as_float(s1.y));
          if (rank) {
            asm volatile("{\n.reg .b32 ra, rb;\nmapa.shared::cluster.u32 ra, %0, 0;\nmapa.shared::cluster.u32 rb, %1, 0;\n"
                         "st.async.weak.shared::cluster.mbarrier::complete_tx::bytes.v4.f32 [ra], {%2, %3, %4, %5}, [rb];\n}"
                         ::"r"(mbuf + (ltid - 256) * 16), "r"(BAR(B_UP)), "f"(v0), "f"(v1), "f"(v2), "f"(v3) : "memory");
          } else {
            const float g0 = bf_round(v0 * sigmoid(v0)), g1 = bf_round(v1 * sigmoid(v1)), g2 = bf_round(v2 * sigmoid(v2)), g3 = bf_round(v3 * sigmoid(v3));
            mbar_wait(BAR(B_UP), 0);
            const uint4 uu = lds_u4(mbuf + (ltid - 256) * 16);
            const uint32_t h0 = movmat(pack_bf16(g0 * __uint_as_float(uu.x), g1 * __uint_as_float(uu.y)));
            const uint32_t h1 = movmat(pack_bf16(g2 * __uint_as_float(uu.z), g3 * __uint_as_float(uu.w)));
            uint32_t* ph = G.h + (u >> 1) * 256 + g * 32 + t;
            stx1(ph + ((2 * aw) ^ g) * 4, h0); stx1(ph + ((2 * aw + 1) ^ g) * 4, h1);
          }
          TLS(288, 60);
        }
      }
    }
    if (PH) asm volatile("bar.arrive 3, 192;" ::: "memory");
    {
      const int wd_ = ltid & 63;
      const uint32_t* src = reinterpret_cast<const uint32_t*>(G.part + hg * 544 + (aw >> 1) * 256 + tb * 16) + wd_;
      mbar_wait(MRED == 2 ? BAR(B_ZOK) : BAR(B_EQ + MRW), 0);
      if (MRD) __nanosleep(MRD);
      TLS(256, 48);
      uint32_t v[16];
#pragma unroll 1
      for (uint32_t it = 0; it < SPIN_MAX; it++) {
        uint32_t m = 0;
#pragma unroll
        for (int i = 0; i < 16; i++) v[i] = ldx1(src + i * 8 * 2176);
#pragma unroll
        for (int i = 0; i < 16; i++) m = max(m, v[i]);
        if (!__any_sync(~0u, m == SENT)) break;
      }
      TLS(256, 55);
      float lo[4], hi[4];
#pragma unroll
      for (int i = 0; i < 4; i++) {
        lo[i] = (bf_lo(v[4 * i]) + bf_lo(v[4 * i + 1])) + (bf_lo(v[4 * i + 2]) + bf_lo(v[4 * i + 3]));
        hi[i] = (bf_hi(v[4 * i]) + bf_hi(v[4 * i + 1])) + (bf_hi(v[4 * i + 2]) + bf_hi(v[4 * i + 3]));
      }
      stx1(reinterpret_cast<uint32_t*>(G.fin + hg * 640) + (tb >> 2) * 640 + ((tb >> 1) & 1) * 64 + (tb & 1) * 16 + (aw >> 1) * 32 + ((wd_ >> 2) & 3) * 128 + (wd_ >> 4) * 4 + (wd_ & 3),
           pack_bf16((lo[0] + lo[1]) + (lo[2] + lo[3]), (hi[0] + hi[1]) + (hi[2] + hi[3])));
      TLS(256, 5);
    }
    if (NUNIT) {
      mbar_wait(BAR(B_STG), 0);
      bar_sync<2, 128>();
      if (HW) __nanosleep(HW);
#pragma unroll 1
      for (uint32_t it = 0; it < SPIN_MAX; it++) {
        if (elect_one()) {
          const uint32_t* ph = G.h + (u >> 4) * 7 * 256;
          if (aw == 3) { mbar_expect_tx(BAR(B_HF), 7168); bulk_ld(sb + h_off(3), ph + 768, 2048, BAR(B_HF)); bulk_ld(sb + h_off(5), ph + 1280, 2048, BAR(B_HF)); }
          else bulk_ld(stg + aw * MT + 8192, ph + aw * 256, 1024, BAR(B_HF));
        }
        mbar_wait(BAR(B_HF), it & 1);
        const uint32_t o = (ltid & 63) * 16 + (g >> 1) * 4, o2 = o + (aw >> 1) * 1024;
        const uint32_t m = max(max(lds_u(sb + h_off(0) + (aw >> 1) * MT + o), lds_u(sb + h_off(2) + o)), max(lds_u(sb + h_off(3) + o2), lds_u(sb + h_off(5) + o2)));
        uint32_t bad;
        asm volatile("{\n.reg .pred p, q;\nsetp.eq.u32 p, %1, 0xFFFFFFFF;\nbar.red.or.pred q, 2, 128, p;\nselp.b32 %0, 1, 0, q;\n}" : "=r"(bad) : "r"(m) : "memory");
        if (!__any_sync(~0u, bad)) break;
        __nanosleep(POLLNS);
      }
      TLS(288, 62);
      float acc[4] = {0.f, 0.f, 0.f, 0.f};
      mbar_wait(BAR(B_DF), 0);
      TLS(288, 63);
#pragma unroll 1
      for (int i = 0; i < 7; i++) {
        const uint32_t da = (d0 + (d_off(i) >> 4)) | (512u << 16), db = (d0 + (h_off(i) >> 4)) | (1u << 16);
        wg_fence();
#pragma unroll
        for (int kk = 0; kk < ((MX & 4) ? 1 : 4); kk++) wgmma_ss_n8<1, 0>(acc, mkdesc(da + kk * 128, HI_SW128), mkdesc(db + kk * 2, HI_SW128));
        wg_commit();
      }
      wg_wait<0>();
      reg_fence(acc);
      if (ltid < 258) { if (MC) mbar_arrive_cta(BAR(B_DE), ltid & 1); else mbar_arrive(BAR(B_DE)); }
      {
        uint32_t* py = reinterpret_cast<uint32_t*>(G.y) + u * 512 + t * 128 + aw * 16 + g;
        stx1(py, f2x(acc[0])); stx1(py + 64, f2x(acc[1])); stx1(py + 8, f2x(acc[2])); stx1(py + 72, f2x(acc[3]));
      }
      TLS(288, 69);
      const uint32_t key = lds_u(sb + MISC + M_IDX + (lane & 7) * 4);
      uint32_t rb = (key >> 11) & 0xFFFFu;
      rb = (rb & 0x8000u) ? (rb & 0x7FFFu) : (~rb & 0xFFFFu);
      const float sg = bf_round(sigmoid(__uint_as_float(rb << 16)));
      uint32_t hits = __ballot_sync(~0u, ((~key >> 7) & 15) == tb) & 255u;
      const uint32_t* py = reinterpret_cast<const uint32_t*>(G.y) + (2 * hg + (aw >> 1)) * 512 + (ltid & 63);
      if (hits) {
        sts_u4(mbuf + (ltid - 256) * 16, make_uint4(0, 0, 0, 0));
        bar_sync<2, 128>();
        if (YW >= 0) mbar_wait(BAR(B_EO + YW), 0); else if (YW == -2) mbar_wait(BAR(B_EAUX), 0);
      }
#pragma unroll 1
      while (hits) {
        const int n0 = __ffs(hits) - 1;
        hits &= hits - 1;
        const int n1 = hits ? __ffs(hits) - 1 : n0;
        hits &= hits - 1;
        uint32_t v[16];
#pragma unroll 1
        for (uint32_t it = 0; it < SPIN_MAX; it++) {
          uint32_t m = 0;
#pragma unroll
          for (int i = 0; i < 8; i++) { v[i] = ldx1(py + n0 * 64 + i * 8192); v[8 + i] = ldx1(py + n1 * 64 + i * 8192); }
#pragma unroll
          for (int i = 0; i < 16; i++) m = max(m, v[i]);
          if (!__any_sync(~0u, m == SENT)) break;
          __nanosleep(POLLNS);
        }
#pragma unroll
        for (int e = 0; e < 2; e++) {
          const uint32_t* w8 = v + 8 * e;
          const float y = ((__uint_as_float(w8[0]) + __uint_as_float(w8[1])) + (__uint_as_float(w8[2]) + __uint_as_float(w8[3]))) +
                          ((__uint_as_float(w8[4]) + __uint_as_float(w8[5])) + (__uint_as_float(w8[6]) + __uint_as_float(w8[7])));
          const int n = e ? n1 : n0;
          sts_h(mbuf + (aw >> 1) * 1024 + n * 128 + ((((ltid >> 3) & 7) ^ n) << 4) + (lane & 7) * 2, bf_round(y) * __shfl_sync(~0u, sg, n));
        }
      }
    }
    if (!NUNIT && ltid < 258) mbar_arrive(BAR(B_DE));
    fence_async_smem();
    bar_sync<2, 128>();
    TLS(288, 33);
    if (ltid == 288) mbar_arrive(BAR(B_MOE));
  } else {
    asm volatile("setmaxnreg.inc.sync.aligned.u32 %0;" ::"n"(CON_REGS));
    if (MC) asm volatile("barrier.cluster.wait.aligned;" ::: "memory");
    const int w = warp >> 2, wq = warp & 3, tid = ltid;
    const bool lead = (tid & 127) == 0;
    const uint32_t dA = (d0 + w * 512) | (1u << 16);
    const uint32_t dB = d0 | (512u << 16);
    auto release = [&](int bar) { if (lead) mbar_arrive(BAR(bar)); };
    auto release2 = [&](int bar) {
      if (MC) { if ((tid & 127) < 2) mbar_arrive_cta(BAR(bar), tid & 1); } else release(bar);
    };
    float aq[64], ak[64], av[64];
#pragma unroll
    for (int i = 0; i < 64; i++) aq[i] = ak[i] = av[i] = 0.f;
    auto q_step = [&](uint32_t bar, int p, uint32_t xs, uint32_t qs) {
      mbar_wait_b(bar, p);
      wg_fence();
#pragma unroll
      for (int kk = 0; kk < 4; kk++)
        wgmma_ss_n128<0, 1>(aq, mkdesc(dA + xs * 1024 + kk * 2, HI_SW128), mkdesc(dB + qs * 1024 + kk * 128, HI_SW128));
      wg_commit();
    };
    const uint32_t dT = dB + w * 512, dX = d0 | (1u << 16);
    auto t_step = [&](float (&a)[64], uint32_t ws, uint32_t xs) {
      wg_fence();
#pragma unroll
      for (int kk = 0; kk < 4; kk++)
        wgmma_ss_n128<1, 0>(a, mkdesc(dT + ws * 1024 + kk * 128, HI_SW128), mkdesc(dX + xs * 1024 + kk * 2, HI_SW128));
      wg_commit();
    };
    {
      int s = 0, p = 0, sp = 2;
#pragma unroll 1
      for (int e = 0; e < NF; e++) {
        TLS(0, 16 + e);
        if (((MS && MS < NF) || (DS && DS < NF)) && e == (MS ? MS : DS)) release(B_MS);
        q_step(BAR(B_FXQ + s), p, s, 3 + s);
        wg_wait<1>();
        if (e > 0) release2(B_E + sp);
        mbar_wait(BAR(B_FKV + s), p);
        t_step(ak, 6 + 2 * s, s);
        if (R5) mbar_wait(BAR(B_FV + s), p);
        t_step(av, 7 + 2 * s, s);
        if (R5 && e == NF - 1) { wg_wait<1>(); release2(B_EK + s); }
        sp = s;
        if (++s == 3) { s = 0; p ^= 1; }
      }
#pragma unroll 1
      for (int e = NF; e < 16; e++) {
        TLS(0, 16 + e);
        if (((MS >= NF && MS < 16) || DS >= NF) && e == (MS ? MS : DS)) release(B_MS);
        mbar_wait(BAR(B_FXQ + s), p);
        mbar_wait(BAR(B_FKV + s), p);
        t_step(ak, R5 ? (K_SLOTS >> (4 * (e - 10))) & 15u : 6 + 2 * s, x_slot(e, s));
        wg_wait<1>();
        release2(B_E + sp);
        if (R5) mbar_wait(BAR(B_FV + s), p);
        t_step(av, R5 ? (V_SLOTS >> (4 * (e - 10))) & 15u : 7 + 2 * s, x_slot(e, s));
        if (R5) { wg_wait<1>(); release2(B_EK + s); }
        sp = s;
        if (++s == 3) { s = 0; p ^= 1; }
      }
    }
    const uint32_t aux = sb;
    mbar_wait(BAR(B_FAUX), 0);
    const int row0 = w * 64 + wq * 16 + g;
    const float ck0 = lds_f(aux + A_CS + 512 + row0 * 4), ck1 = lds_f(aux + A_CS + 512 + (row0 + 8) * 4);
    const float cv0 = lds_f(aux + A_CS + 1024 + row0 * 4), cv1 = lds_f(aux + A_CS + 1024 + (row0 + 8) * 4);
    const uint32_t moff = (uint32_t)(w * 64 + wq * 16 + (lane & 15)) * 128 + (((lane >> 4) ^ (lane & 7)) << 4);
    const uint32_t sta = aux + A_ST + t * 16;
    float kvp[36], ao[64];
    uint32_t xr[32];
    float nm0, nm1, rs0, rs1;
    auto row_stats = [&]() {
      const float2 st0 = lds_f2(aux + A_ST + row0 * 8), st1 = lds_f2(aux + A_ST + (row0 + 8) * 8);
      nm0 = -st0.x; nm1 = -st1.x; rs0 = st0.y; rs1 = st1.y;
    };
    auto ld_x = [&]() {
#pragma unroll
      for (int j = 0; j < 16; j += 2) ldsm4(sb + (j < 8 ? SX14 : SX15) * SLOT + (moff ^ ((j & 7) << 4)), xr[2 * j], xr[2 * j + 1], xr[2 * j + 2], xr[2 * j + 3]);
    };
    auto resid = [&]() {
      const float c0 = 1.f + rs0, c1 = 1.f + rs1, e0 = nm0 * rs0, e1 = nm1 * rs1;
#pragma unroll
      for (int j = 0; j < 16; j++) {
        ao[4 * j + 0] = fmaf(bf_lo(xr[2 * j]), c0, e0); ao[4 * j + 1] = fmaf(bf_hi(xr[2 * j]), c0, e0);
        ao[4 * j + 2] = fmaf(bf_lo(xr[2 * j + 1]), c1, e1); ao[4 * j + 3] = fmaf(bf_hi(xr[2 * j + 1]), c1, e1);
      }
    };
    {
      uint32_t pa[32];
      float4 st[16];
      auto ld = [&](int j) { st[j] = lds_f4(sta + j * 64); };
      auto k_blk = [&](int c) {
#pragma unroll
        for (int i = 0; i < 2; i++) {
          const float4 u = st[2 * c + i];
          const float l0 = u.y * 1.4426950408889634f, l1 = u.w * 1.4426950408889634f;
          const float* a = ak + 8 * c + 4 * i;
          pa[4 * c + 2 * i] = phi2(fmaf(-u.x, ck0, a[0]), u.y, l0, fmaf(-u.z, ck0, a[1]), u.w, l1);
          pa[4 * c + 2 * i + 1] = phi2(fmaf(-u.x, ck1, a[2]), u.y, l0, fmaf(-u.z, ck1, a[3]), u.w, l1);
        }
      };
      const uint32_t voff = sb + w * 8192 + (uint32_t)(8 * (lane >> 4) + (lane & 7)) * 128 + (((2 * wq + ((lane >> 3) & 1)) ^ (lane & 7)) << 4);
      auto v_blk = [&](int c) {
        uint32_t r[4];
#pragma unroll
        for (int i = 0; i < 2; i++) {
          const float4 u = st[2 * c + i];
          const float* a = av + 8 * c + 4 * i;
          r[2 * i] = pack_bf16(fmaf(-u.x, cv0, a[0]) * u.y, fmaf(-u.z, cv0, a[1]) * u.w);
          r[2 * i + 1] = pack_bf16(fmaf(-u.x, cv1, a[2]) * u.y, fmaf(-u.z, cv1, a[3]) * u.w);
        }
        stsm4t(voff + (c < 4 ? S_V0 : S_V1) * SLOT + (c & 3) * 2048, r[0], r[1], r[2], r[3]);
      };
      auto kv_mma = [&](int c) {
        const uint32_t bo = (c < 4 ? S_V0 : S_V1) * 1024 + w * 512 + (c & 3) * 128;
        const uint64_t bb = mkdesc((d0 + bo) | (((A_ONES >> 4) - bo) << 16), HI_SW128);
        if (c == 0) wgmma_rz_n72<1>(kvp, pa[4 * c], pa[4 * c + 1], pa[4 * c + 2], pa[4 * c + 3], bb);
        else wgmma_rs_n72<1>(kvp, pa[4 * c], pa[4 * c + 1], pa[4 * c + 2], pa[4 * c + 3], bb);
      };
      ld(0); ld(1);
      wg_wait<0>();
      reg_fence(ak); reg_fence(av);
      TLS(0, 2);
      if (!R5) release2(B_E);
      release(B_T0);
      if (LQ) { v_blk(0); ld(2); ld(3); } else { ld(2); ld(3); v_blk(0); }
      ld(4); ld(5); v_blk(1); k_blk(0);
      ld(6); ld(7); v_blk(2); ld(8); ld(9); v_blk(3); k_blk(1);
      ld(10); ld(11); v_blk(4); ld(12); ld(13); v_blk(5); k_blk(2);
      ld(14); ld(15); v_blk(6); v_blk(7); k_blk(3);
      if (RL) { ld(8); ld(9); }
      TLS(0, 3);
      fence_async_smem();
      asm volatile("bar.sync %0, 128;" ::"r"(3 + w) : "memory");
      if (XP == 0) ld_x();
      wg_fence();
      kv_mma(0); kv_mma(1); kv_mma(2); kv_mma(3);
      wg_commit();
#pragma unroll
      for (int c = 4; c < 8; c++) {
        if (RL && c < 7) { ld(2 * c + 2); ld(2 * c + 3); }
        k_blk(c);
        wg_fence();
        kv_mma(c);
        wg_commit();
      }
      if (XP == 3 && (RK == 0 || RK > 4)) ld_x();
      if (QE) { q_step(BAR(B_FQ), 0, SXQ0, QW_SLOTS & 15u); wg_wait<1>(); } else wg_wait<0>();
      reg_fence(kvp);
      auto hand_back = [&]() { release2(B_STG); __syncwarp(); };
      if (!SF) hand_back();
      TLS(0, 4);
      uint4* pp = G.part + b * 544;
      uint32_t pk[8];
#pragma unroll
      for (int j = 0; j < 8; j++) pk[j] = wq >= 2 ? pack_bf16(kvp[16 + 2 * j], kvp[17 + 2 * j]) : pack_bf16(kvp[2 * j], kvp[2 * j + 1]);
      stx4(pp + tid, pk[0], pk[2], pk[4], pk[6]);
      stx4(pp + 256 + tid, pk[1], pk[3], pk[5], pk[7]);
      if (t == 0) stx2(reinterpret_cast<uint2*>(pp + 512) + (tid >> 2), f2x(kvp[32]), f2x(kvp[34]));
      if (SF == 1) hand_back();
      if (XP == 1) ld_x();
      if (!QE) q_step(BAR(B_FQ), 0, SXQ0, QW_SLOTS & 15u);
      if (XP == 2) ld_x();
      if (SF == 2) hand_back();
      const int wd_ = wq * 16 + (lane & 15);
      const uint32_t* src = reinterpret_cast<const uint32_t*>(G.part + ((lane >> 4) * 64 + hg) * 544 + w * 256 + tb * 16) + wd_;
      uint32_t* fin = reinterpret_cast<uint32_t*>(G.fin + hg * 640) + (tb >> 2) * 640 + ((tb >> 1) & 1) * 64 + (tb & 1) * 16 + w * 32 + ((wd_ >> 2) & 3) * 128 + wq * 4 + (wd_ & 3);
      uint32_t v[8];
      auto part_load = [&]() {
#pragma unroll
        for (int i = 0; i < 8; i++) v[i] = ldx1(src + i * 8 * 2176);
      };
#pragma unroll
      for (int k = 1; k < NQ; k++) {
        q_step(BAR(B_FQ + k), 0, (QX_SLOTS >> (4 * k)) & 15u, (QW_SLOTS >> (4 * k)) & 15u);
        TLS(0, 48 + k);
        if (k == RK) { row_stats(); ld_x(); resid(); }
        if (!MRED && k == PLP) part_load();
        if (!MRED && k == PLC) {
#pragma unroll 1
          for (uint32_t it = 0; it < SPIN_MAX; it++) {
            if (!__any_sync(~0u, max(max(max(v[0], v[1]), max(v[2], v[3])), max(max(v[4], v[5]), max(v[6], v[7]))) == SENT)) break;
            part_load();
          }
          float lo = ((bf_lo(v[0]) + bf_lo(v[1])) + (bf_lo(v[2]) + bf_lo(v[3]))) + ((bf_lo(v[4]) + bf_lo(v[5])) + (bf_lo(v[6]) + bf_lo(v[7])));
          float hi = ((bf_hi(v[0]) + bf_hi(v[1])) + (bf_hi(v[2]) + bf_hi(v[3]))) + ((bf_hi(v[4]) + bf_hi(v[5])) + (bf_hi(v[6]) + bf_hi(v[7])));
          lo += __shfl_xor_sync(~0u, lo, 16); hi += __shfl_xor_sync(~0u, hi, 16);
          if (lane < 16) stx1(fin, pack_bf16(lo, hi));
          TLS(0, 5);
        }
        wg_wait<1>();
        release2(B_EQ + k - 1);
      }
      TLS(0, 13);
      mbar_wait(BAR(B_CQ), 0);
    }
    wg_wait<0>();
    reg_fence(aq);
    TLS(0, 15);
    if (RK == 0 || RK > 4) row_stats();
    const float rl0 = rs0 * 1.4426950408889634f, rl1 = rs1 * 1.4426950408889634f;
    uint32_t pq[32];
#pragma unroll
    for (int j = 0; j < 16; j++) {
      const float2 c = lds_f2(aux + A_CS + (j * 8 + 2 * t) * 4);
      const float* a = aq + 4 * j;
      pq[2 * j] = phi2(fmaf(nm0, c.x, a[0]), rs0, rl0, fmaf(nm0, c.y, a[1]), rs0, rl0);
      pq[2 * j + 1] = phi2(fmaf(nm1, c.x, a[2]), rs1, rl1, fmaf(nm1, c.y, a[3]), rs1, rl1);
    }
    TLS(0, 6);
    if (RK == 5) resid();
    mbar_wait_b(BAR(MFIN ? B_KV4 : B_KVB), 0);
    TLS(0, 7);
    uint32_t of[32];
    uint4* mine = G.o + (tb * 32 + hg) * 512 + warp * 64 + g * 4 + (t ^ (g >> 1));
    const uint32_t dW = d0 | (256u << 16);
    auto o_store = [&](int h) {
#pragma unroll
      for (int c = 0; c < 2; c++) stx4(mine + h * 4096 + c * 32, of[8 * h + c], of[8 * h + 2 + c], of[8 * h + 4 + c], of[8 * h + 6 + c]);
    };
    auto out_step = [&](uint32_t slot, const uint32_t* a) {
      const uint32_t d = dW + slot * 1024;
      wg_fence();
#pragma unroll
      for (int kk = 0; kk < 4; kk++) wgmma_rs_n128<1>(ao, a[4 * kk], a[4 * kk + 1], a[4 * kk + 2], a[4 * kk + 3], mkdesc(d + (kk >> 1) * 512 + (kk & 1) * 128, HI_SW128));
      wg_commit();
    };
    uint4 v[NDIR][4];
    auto ld_o = [&](int k) {
      const uint4* p0 = mine + (slab(2 * k, hg) - hg) * 512;
      const uint4* p1 = mine + (slab(2 * k + 1, hg) - hg) * 512;
      v[k][0] = ldx4(p0); v[k][1] = ldx4(p0 + 32); v[k][2] = ldx4(p1); v[k][3] = ldx4(p1 + 32);
    };
    auto ld_all = [&]() {
#pragma unroll
      for (int k = 0; k < NDIR; k++) ld_o(k);
    };
    {
      float oa[4][20];
      const uint32_t dK = (d0 + S_KVB * 1024) | (8u << 16);
      wg_fence();
#pragma unroll
      for (int h = 0; h < 4; h++) {
        wgmma_rz_n40<1>(oa[h], pq[8 * h], pq[8 * h + 1], pq[8 * h + 2], pq[8 * h + 3], mkdesc(dK + h * 160, HI_NOSW));
        wgmma_rs_n40<1>(oa[h], pq[8 * h + 4], pq[8 * h + 5], pq[8 * h + 6], pq[8 * h + 7], mkdesc(dK + h * 160 + 16, HI_NOSW));
        if (h == 0 || h == 3) wg_commit();
      }
      auto norm = [&](int h) {
        const float r0 = rcp(oa[h][16] + 1e-6f), r1 = rcp(oa[h][18] + 1e-6f);
#pragma unroll
        for (int j = 0; j < 4; j++) {
          of[8 * h + 2 * j] = pack_bf16(oa[h][4 * j] * r0, oa[h][4 * j + 1] * r0);
          of[8 * h + 2 * j + 1] = pack_bf16(oa[h][4 * j + 2] * r1, oa[h][4 * j + 3] * r1);
        }
      };
      wg_wait<1>();
      reg_fence(oa[0]);
      norm(0);
      if (LE == 4) ld_all();
      o_store(0);
      if (LE == 3) ld_all();
      TLS(0, 8);
      wg_wait<0>();
      reg_fence(oa[1]); reg_fence(oa[2]); reg_fence(oa[3]);
      TLP_(0);
      release(B_EAUX);
      norm(1);
      if (OS1 == 3) o_store(1);
      if (E7 && NP == 0 && SL7 && hg == 7) o_store(1);
      if (NP == 0) { norm(2); norm(3); }
      if (E7 && NP == 0 && SL7 && hg == 7) { o_store(2); o_store(3); }
      TLP_(1);
      mbar_wait_b(BAR(B_FWO), 0);
      TLP_(2);
      if (RK == 0) resid();
      if (LE == 2) ld_all();
      TLP_(3);
      out_step(WO_SLOTS & 15u, of);
      TLP_(4);
      if (NP == 1) { norm(2); norm(3); }
      if (LE == 1) ld_all();
    }
    if (OS1 == 0) o_store(1);
    mbar_wait(BAR(B_FWO + 1), 0);
    TLP_(5);
    out_step((WO_SLOTS >> 4) & 15u, of + 16);
    TLP_(6);
    const bool early = SL7 && hg == 7;
    if (OS1 == 1 && !(E7 && early)) o_store(1);
    TLP_(7);
    if (early && !E7) { o_store(2); o_store(3); }
    {
      if (DW) __nanosleep(DW);
      if (LE == 0) ld_all();
      if (OS1 == 2 && !(E7 && early)) o_store(1);
#pragma unroll
      for (int k = 0; k < NDIR; k++) {
#pragma unroll 1
        for (uint32_t it = 0; it < SPIN_MAX; it++) {
          if (!__any_sync(~0u, max(max(v[k][0].x, v[k][1].x), max(v[k][2].x, v[k][3].x)) == SENT)) break;
#pragma unroll
          for (int j = k; j < NDIR; j++) ld_o(j);
        }
        TLP_(8);
        const uint32_t a[16] = {v[k][0].x, v[k][1].x, v[k][0].y, v[k][1].y, v[k][0].z, v[k][1].z, v[k][0].w, v[k][1].w,
                                v[k][2].x, v[k][3].x, v[k][2].y, v[k][3].y, v[k][2].z, v[k][3].z, v[k][2].w, v[k][3].w};
        mbar_wait(BAR(B_FWO + 2 + k), 0);
        TLS(0, 34 + k);
        out_step((WO_SLOTS >> (8 + 4 * k)) & 15u, a);
        TLP_(9);
        if (k) { wg_wait<1>(); release2(B_EO); }
      }
      if (!early) o_store(2);
    }
    auto routed = [&]() {
      mbar_wait(BAR(B_MOE), 0);
      const float2 kk = lds_f2(sb + MISC + M_IDX + t * 8);
      const int k0 = (int)(~__float_as_uint(kk.x) & 2047u) - tb * 128, k1 = (int)(~__float_as_uint(kk.y) & 2047u) - tb * 128;
      if (NUNIT && __any_sync(~0u, (k0 >> 6) == w || (k1 >> 6) == w)) {
        const uint32_t a0 = (k0 == row0 ? 0x3F80u : 0u) | (k1 == row0 ? 0x3F800000u : 0u);
        const uint32_t a1 = (k0 == row0 + 8 ? 0x3F80u : 0u) | (k1 == row0 + 8 ? 0x3F800000u : 0u);
        wg_fence();
        wgmma_rs_n128<1>(ao, a0, a1, 0u, 0u, mkdesc((d0 + ((MISC + M_MOE) >> 4)) | (64u << 16), 0x40000000u));
        wg_commit();
      }
    };
    auto out_half = [&](int h, const float* v) {
      const uint32_t ost = sb + (w ? S_D1 : S_D0) * SLOT + wq * 4096 + h * 2048;
#pragma unroll
      for (int j = 0; j < 8; j += 2)
        stsm4(ost + ((moff & 2047) ^ (j << 4)), pack_bf16(v[4 * j], v[4 * j + 1]), pack_bf16(v[4 * j + 2], v[4 * j + 3]),
              pack_bf16(v[4 * j + 4], v[4 * j + 5]), pack_bf16(v[4 * j + 6], v[4 * j + 7]));
      fence_async_smem();
      __syncwarp();
      if (elect_one()) {
        asm volatile("cp.async.bulk.tensor.2d.global.shared::cta.bulk_group [%0, {%2, %3}], [%1];" ::"l"(&tmOut), "r"(ost), "r"(hg * 128 + h * 64), "r"(tb * 128 + warp * 16) : "memory");
        if (h) asm volatile("cp.async.bulk.commit_group;\ncp.async.bulk.wait_group.read 0;" ::: "memory");
      }
      __syncwarp();
    };
    bool done = false;
    {
      const uint32_t dO = (d0 + w * 256) | (1u << 16);
      auto step = [&](int i, int r, int p, uint32_t as, uint32_t ws) {
        mbar_wait(BAR(B_FWO + i), 0);
        mbar_wait(BAR(B_VAL + r), p);
        TLS(0, 32 + i);
        const uint32_t da = dO + as * 1024, db = dW + ws * 1024;
        wg_fence();
#pragma unroll
        for (int kk = 0; kk < 4; kk++)
          wgmma_ss_n128<0, 1>(ao, mkdesc(da + (kk >> 1) * 512 + (kk & 1) * 2, HI_SW64), mkdesc(db + (kk >> 1) * 512 + (kk & 1) * 128, HI_SW128));
        wg_commit();
      };
      uint64_t tbl = WO_SLOTS >> (4 * I0);
      int r = 0, p = 0, rp = 0;
#pragma unroll 1
      for (int i = I0; i < 12; i++) {
        step(i, r, p, (A_SLOTS >> (4 * r)) & 15u, (uint32_t)tbl & 15u);
        tbl >>= 4;
#pragma unroll
        for (int c = 0; c < 2; c++)
          if (i == OS3 + c && !early) stx4(mine + 3 * 4096 + c * 32, of[24 + c], of[26 + c], of[28 + c], of[30 + c]);
        wg_wait<1>();
        if (i > I0) release(B_EA + rp);
        rp = r;
        if (++r == NA) { r = 0; p ^= 1; }
        if (i >= 3 && i <= 9) release2(B_EO + i - 3);
      }
      if (SPL && w == 1) {
        float bl[32], bh[32];
        mbar_wait(BAR(B_GO), 0);
        routed();
#pragma unroll
        for (int h = 0; h < 2; h++) {
#pragma unroll
          for (int i = 12; i < 16; i++) {
            const int r_ = (i - I0) % NA;
            if (h == 0) { mbar_wait(BAR(B_FWO + i), 0); mbar_wait(BAR(B_VAL + r_), ((i - I0) / NA) & 1); }
            const uint32_t da = dO + ((A_SLOTS >> (4 * r_)) & 15u) * 1024, db = dW + ((uint32_t)(WO_SLOTS >> (4 * i)) & 15u) * 1024 + h * 256;
            if (h == 0 || i == 12) wg_fence();
#pragma unroll
            for (int kk = 0; kk < 4; kk++) {
              const uint64_t a = mkdesc(da + (kk >> 1) * 512 + (kk & 1) * 2, HI_SW64), bb = mkdesc(db + (kk >> 1) * 512 + (kk & 1) * 128, HI_SW128);
              if (i == 12 && kk == 0) wgmma_sz_n64<0, 1>(h ? bh : bl, a, bb); else wgmma_ss_n64<0, 1>(h ? bh : bl, a, bb);
            }
          }
          wg_commit();
        }
        wg_wait<1>();
        reg_fence(ao); reg_fence(bl);
#pragma unroll
        for (int j = 0; j < 32; j++) bl[j] += ao[j];
        out_half(0, bl);
        wg_wait<0>();
        reg_fence(bh);
#pragma unroll
        for (int j = 0; j < 32; j++) bh[j] += ao[32 + j];
        out_half(1, bh);
        done = true;
      } else
#pragma unroll
      for (int i = 12; i < 16; i++) {
        if (i == 16 - STAG && w == 1) mbar_wait(BAR(B_GO), 0);
        step(i, (i - I0) % NA, ((i - I0) / NA) & 1, (A_SLOTS >> (4 * ((i - I0) % NA))) & 15u, (uint32_t)(WO_SLOTS >> (4 * i)) & 15u);
        if (STAG && i == 15 - GOE && tid == 0) mbar_arrive(BAR(B_GO));
      }
    }
    if (!done) {
      routed();
      wg_wait<0>();
      reg_fence(ao);
      TLS(0, 10);
      out_half(0, ao);
      out_half(1, ao + 32);
    }
    TLS(0, 11);
    TLS(128, 9);
  }
}

typedef CUresult (*EncFn)(CUtensorMap*, CUtensorMapDataType, cuuint32_t, void*, const cuuint64_t*, const cuuint64_t*, const cuuint32_t*,
                          const cuuint32_t*, CUtensorMapInterleave, CUtensorMapSwizzle, CUtensorMapL2promotion, CUtensorMapFloatOOBfill);

void make_map2(EncFn enc, CUtensorMap* m, void* p, uint64_t rows, uint64_t cols, uint32_t brows, CUtensorMapL2promotion promo) {
  cuuint64_t gd[2] = {cols, rows}, gs[1] = {cols * 2};
  cuuint32_t bd[2] = {64, brows}, es[2] = {1, 1};
  enc(m, CU_TENSOR_MAP_DATA_TYPE_BFLOAT16, 2, p, gd, gs, bd, es, CU_TENSOR_MAP_INTERLEAVE_NONE, CU_TENSOR_MAP_SWIZZLE_128B, promo,
      CU_TENSOR_MAP_FLOAT_OOB_FILL_NONE);
}
void make_map3(EncFn enc, CUtensorMap* m, void* p, uint64_t rows, uint64_t cols, uint32_t brows) {
  cuuint64_t gd[3] = {64, rows, cols / 64}, gs[2] = {cols * 2, 128};
  cuuint32_t bd[3] = {64, brows, 2}, es[3] = {1, 1, 1};
  enc(m, CU_TENSOR_MAP_DATA_TYPE_BFLOAT16, 3, p, gd, gs, bd, es, CU_TENSOR_MAP_INTERLEAVE_NONE, CU_TENSOR_MAP_SWIZZLE_128B,
      CU_TENSOR_MAP_L2_PROMOTION_L2_256B, CU_TENSOR_MAP_FLOAT_OOB_FILL_NONE);
}

}

extern "C" void kernel_launch(void* const* d_in, const int* in_sizes, int n_in, void* d_out, int out_size) {
  static EncFn enc = nullptr;
  static int by_sm = 0;
  if (!enc) {
    void* fn = nullptr;
    cudaDriverEntryPointQueryResult qr;
    cudaGetDriverEntryPoint("cuTensorMapEncodeTiled", &fn, cudaEnableDefault, &qr);
    enc = (EncFn)fn;
    int dev = 0, sms = 0;
    cudaGetDevice(&dev);
    cudaDeviceGetAttribute(&sms, cudaDevAttrMultiProcessorCount, dev);
    by_sm = MAP == 2 && sms == NCTA + NSVC;
    cudaFuncSetAttribute(fused_kernel, cudaFuncAttributeMaxDynamicSharedMemorySize, SMEM_BYTES);
  }
  CUtensorMap tmX, tmW, tmWo, tmOut, tmG, tmU, tmD, tmR, tmWp;
  {
    cuuint64_t gd[5] = {64, 2, 128, 4, 16}, gs[4] = {2048, 16384, 4096, 128};
    cuuint32_t bd[5] = {64, 2, 4, 4, 2}, es[5] = {1, 1, 1, 1, 1};
    enc(&tmWp, CU_TENSOR_MAP_DATA_TYPE_BFLOAT16, 5, d_in[2], gd, gs, bd, es, CU_TENSOR_MAP_INTERLEAVE_NONE, CU_TENSOR_MAP_SWIZZLE_128B,
        CU_TENSOR_MAP_L2_PROMOTION_L2_256B, CU_TENSOR_MAP_FLOAT_OOB_FILL_NONE);
  }
  make_map2(enc, &tmR, d_in[0], SEQ, DM, 1, CU_TENSOR_MAP_L2_PROMOTION_L2_128B);
  make_map2(enc, &tmX, d_in[0], SEQ, DM, 128, XPROMO);
  make_map3(enc, &tmW, d_in[1], DM, 3 * DM, 64);
  make_map3(enc, &tmWo, d_in[2], DM, DM, 32);
  if (OUTV) make_map2(enc, &tmOut, d_out, SEQ, DM, 16, CU_TENSOR_MAP_L2_PROMOTION_L2_128B); else make_map3(enc, &tmOut, d_out, SEQ, DM, 64);
  make_map2(enc, &tmG, d_in[5], DM, FF, 64, MPROMO);
  make_map2(enc, &tmU, d_in[6], DM, FF, 64, MPROMO);
  make_map2(enc, &tmD, d_in[7], FF, DM, 64, MPROMO);
  typedef const __nv_bfloat16* P;
  cudaLaunchConfig_t cfg = {};
  cfg.gridDim = dim3(NCTA + NSVC); cfg.blockDim = dim3(512); cfg.dynamicSmemBytes = SMEM_BYTES; cfg.stream = cudaStreamPerThread;
  cudaLaunchAttribute at[1];
  at[0].id = cudaLaunchAttributeClusterDimension;
  at[0].val.clusterDim.x = 2; at[0].val.clusterDim.y = 1; at[0].val.clusterDim.z = 1;
  cfg.attrs = at; cfg.numAttrs = 1;
  cudaLaunchKernelEx(&cfg, fused_kernel, (P)d_in[0], (P)d_in[1], (P)d_in[2], (P)d_in[4], (P)d_in[7], by_sm, tmX, tmW, tmWo, tmOut, tmG, tmU, tmD, tmR, tmWp);
}
```

```cpp
#include <cuda_runtime.h>
#include <cuda.h>
#include <cuda_bf16.h>
#include <stdint.h>

namespace {

template <int TA, int TB> __device__ __forceinline__ void wgmma_ss_n128(float (&d)[64], uint64_t da, uint64_t db) {
  asm volatile("wgmma.mma_async.sync.aligned.m64n128k16.f32.bf16.bf16 "
  "{%0,%1,%2,%3,%4,%5,%6,%7,%8,%9,%10,%11,%12,%13,%14,%15,%16,%17,%18,%19,%20,%21,%22,%23,%24,%25,%26,%27,%28,%29,%30,%31,%32,%33,%34,%35,%36,%37,%38,%39,%40,%41,%42,%43,%44,%45,%46,%47,%48,%49,%50,%51,%52,%53,%54,%55,%56,%57,%58,%59,%60,%61,%62,%63}, "
  "%64, %65, 1, 1, 1, %66, %67;"
  : "+f"(d[0]),"+f"(d[1]),"+f"(d[2]),"+f"(d[3]),"+f"(d[4]),"+f"(d[5]),"+f"(d[6]),"+f"(d[7]),"+f"(d[8]),"+f"(d[9]),"+f"(d[10]),"+f"(d[11]),"+f"(d[12]),"+f"(d[13]),"+f"(d[14]),"+f"(d[15]),"+f"(d[16]),"+f"(d[17]),"+f"(d[18]),"+f"(d[19]),"+f"(d[20]),"+f"(d[21]),"+f"(d[22]),"+f"(d[23]),"+f"(d[24]),"+f"(d[25]),"+f"(d[26]),"+f"(d[27]),"+f"(d[28]),"+f"(d[29]),"+f"(d[30]),"+f"(d[31]),"+f"(d[32]),"+f"(d[33]),"+f"(d[34]),"+f"(d[35]),"+f"(d[36]),"+f"(d[37]),"+f"(d[38]),"+f"(d[39]),"+f"(d[40]),"+f"(d[41]),"+f"(d[42]),"+f"(d[43]),"+f"(d[44]),"+f"(d[45]),"+f"(d[46]),"+f"(d[47]),"+f"(d[48]),"+f"(d[49]),"+f"(d[50]),"+f"(d[51]),"+f"(d[52]),"+f"(d[53]),"+f"(d[54]),"+f"(d[55]),"+f"(d[56]),"+f"(d[57]),"+f"(d[58]),"+f"(d[59]),"+f"(d[60]),"+f"(d[61]),"+f"(d[62]),"+f"(d[63])
  : "l"(da), "l"(db), "n"(TA), "n"(TB));
}
template <int TA, int TB> __device__ __forceinline__ void wgmma_ss_n64(float (&d)[32], uint64_t da, uint64_t db) {
  asm volatile("wgmma.mma_async.sync.aligned.m64n64k16.f32.bf16.bf16 "
  "{%0,%1,%2,%3,%4,%5,%6,%7,%8,%9,%10,%11,%12,%13,%14,%15,%16,%17,%18,%19,%20,%21,%22,%23,%24,%25,%26,%27,%28,%29,%30,%31}, "
  "%32, %33, 1, 1, 1, %34, %35;"
  : "+f"(d[0]),"+f"(d[1]),"+f"(d[2]),"+f"(d[3]),"+f"(d[4]),"+f"(d[5]),"+f"(d[6]),"+f"(d[7]),"+f"(d[8]),"+f"(d[9]),"+f"(d[10]),"+f"(d[11]),"+f"(d[12]),"+f"(d[13]),"+f"(d[14]),"+f"(d[15]),"+f"(d[16]),"+f"(d[17]),"+f"(d[18]),"+f"(d[19]),"+f"(d[20]),"+f"(d[21]),"+f"(d[22]),"+f"(d[23]),"+f"(d[24]),"+f"(d[25]),"+f"(d[26]),"+f"(d[27]),"+f"(d[28]),"+f"(d[29]),"+f"(d[30]),"+f"(d[31])
  : "l"(da), "l"(db), "n"(TA), "n"(TB));
}
template <int TA, int TB> __device__ __forceinline__ void wgmma_sz_n64(float (&d)[32], uint64_t da, uint64_t db) {
  asm volatile("wgmma.mma_async.sync.aligned.m64n64k16.f32.bf16.bf16 "
  "{%0,%1,%2,%3,%4,%5,%6,%7,%8,%9,%10,%11,%12,%13,%14,%15,%16,%17,%18,%19,%20,%21,%22,%23,%24,%25,%26,%27,%28,%29,%30,%31}, "
  "%32, %33, 0, 1, 1, %34, %35;"
  : "=f"(d[0]),"=f"(d[1]),"=f"(d[2]),"=f"(d[3]),"=f"(d[4]),"=f"(d[5]),"=f"(d[6]),"=f"(d[7]),"=f"(d[8]),"=f"(d[9]),"=f"(d[10]),"=f"(d[11]),"=f"(d[12]),"=f"(d[13]),"=f"(d[14]),"=f"(d[15]),"=f"(d[16]),"=f"(d[17]),"=f"(d[18]),"=f"(d[19]),"=f"(d[20]),"=f"(d[21]),"=f"(d[22]),"=f"(d[23]),"=f"(d[24]),"=f"(d[25]),"=f"(d[26]),"=f"(d[27]),"=f"(d[28]),"=f"(d[29]),"=f"(d[30]),"=f"(d[31])
  : "l"(da), "l"(db), "n"(TA), "n"(TB));
}
template <int TB> __device__ __forceinline__ void wgmma_rs_n72(float (&d)[36], uint32_t a0, uint32_t a1, uint32_t a2, uint32_t a3, uint64_t db) {
  asm volatile("wgmma.mma_async.sync.aligned.m64n72k16.f32.bf16.bf16 "
  "{%0,%1,%2,%3,%4,%5,%6,%7,%8,%9,%10,%11,%12,%13,%14,%15,%16,%17,%18,%19,%20,%21,%22,%23,%24,%25,%26,%27,%28,%29,%30,%31,%32,%33,%34,%35}, "
  "{%36,%37,%38,%39}, %40, 1, 1, 1, %41;"
  : "+f"(d[0]),"+f"(d[1]),"+f"(d[2]),"+f"(d[3]),"+f"(d[4]),"+f"(d[5]),"+f"(d[6]),"+f"(d[7]),"+f"(d[8]),"+f"(d[9]),"+f"(d[10]),"+f"(d[11]),"+f"(d[12]),"+f"(d[13]),"+f"(d[14]),"+f"(d[15]),"+f"(d[16]),"+f"(d[17]),"+f"(d[18]),"+f"(d[19]),"+f"(d[20]),"+f"(d[21]),"+f"(d[22]),"+f"(d[23]),"+f"(d[24]),"+f"(d[25]),"+f"(d[26]),"+f"(d[27]),"+f"(d[28]),"+f"(d[29]),"+f"(d[30]),"+f"(d[31]),"+f"(d[32]),"+f"(d[33]),"+f"(d[34]),"+f"(d[35])
  : "r"(a0), "r"(a1), "r"(a2), "r"(a3), "l"(db), "n"(TB));
}
template <int TB> __device__ __forceinline__ void wgmma_rz_n72(float (&d)[36], uint32_t a0, uint32_t a1, uint32_t a2, uint32_t a3, uint64_t db) {
  asm volatile("wgmma.mma_async.sync.aligned.m64n72k16.f32.bf16.bf16 "
  "{%0,%1,%2,%3,%4,%5,%6,%7,%8,%9,%10,%11,%12,%13,%14,%15,%16,%17,%18,%19,%20,%21,%22,%23,%24,%25,%26,%27,%28,%29,%30,%31,%32,%33,%34,%35}, "
  "{%36,%37,%38,%39}, %40, 0, 1, 1, %41;"
  : "=f"(d[0]),"=f"(d[1]),"=f"(d[2]),"=f"(d[3]),"=f"(d[4]),"=f"(d[5]),"=f"(d[6]),"=f"(d[7]),"=f"(d[8]),"=f"(d[9]),"=f"(d[10]),"=f"(d[11]),"=f"(d[12]),"=f"(d[13]),"=f"(d[14]),"=f"(d[15]),"=f"(d[16]),"=f"(d[17]),"=f"(d[18]),"=f"(d[19]),"=f"(d[20]),"=f"(d[21]),"=f"(d[22]),"=f"(d[23]),"=f"(d[24]),"=f"(d[25]),"=f"(d[26]),"=f"(d[27]),"=f"(d[28]),"=f"(d[29]),"=f"(d[30]),"=f"(d[31]),"=f"(d[32]),"=f"(d[33]),"=f"(d[34]),"=f"(d[35])
  : "r"(a0), "r"(a1), "r"(a2), "r"(a3), "l"(db), "n"(TB));
}
template <int TB> __device__ __forceinline__ void wgmma_rs_n40(float (&d)[20], uint32_t a0, uint32_t a1, uint32_t a2, uint32_t a3, uint64_t db) {
  asm volatile("wgmma.mma_async.sync.aligned.m64n40k16.f32.bf16.bf16 "
  "{%0,%1,%2,%3,%4,%5,%6,%7,%8,%9,%10,%11,%12,%13,%14,%15,%16,%17,%18,%19}, "
  "{%20,%21,%22,%23}, %24, 1, 1, 1, %25;"
  : "+f"(d[0]),"+f"(d[1]),"+f"(d[2]),"+f"(d[3]),"+f"(d[4]),"+f"(d[5]),"+f"(d[6]),"+f"(d[7]),"+f"(d[8]),"+f"(d[9]),"+f"(d[10]),"+f"(d[11]),"+f"(d[12]),"+f"(d[13]),"+f"(d[14]),"+f"(d[15]),"+f"(d[16]),"+f"(d[17]),"+f"(d[18]),"+f"(d[19])
  : "r"(a0), "r"(a1), "r"(a2), "r"(a3), "l"(db), "n"(TB));
}
template <int TB> __device__ __forceinline__ void wgmma_rz_n40(float (&d)[20], uint32_t a0, uint32_t a1, uint32_t a2, uint32_t a3, uint64_t db) {
  asm volatile("wgmma.mma_async.sync.aligned.m64n40k16.f32.bf16.bf16 "
  "{%0,%1,%2,%3,%4,%5,%6,%7,%8,%9,%10,%11,%12,%13,%14,%15,%16,%17,%18,%19}, "
  "{%20,%21,%22,%23}, %24, 0, 1, 1, %25;"
  : "=f"(d[0]),"=f"(d[1]),"=f"(d[2]),"=f"(d[3]),"=f"(d[4]),"=f"(d[5]),"=f"(d[6]),"=f"(d[7]),"=f"(d[8]),"=f"(d[9]),"=f"(d[10]),"=f"(d[11]),"=f"(d[12]),"=f"(d[13]),"=f"(d[14]),"=f"(d[15]),"=f"(d[16]),"=f"(d[17]),"=f"(d[18]),"=f"(d[19])
  : "r"(a0), "r"(a1), "r"(a2), "r"(a3), "l"(db), "n"(TB));
}
template <int TB> __device__ __forceinline__ void wgmma_rs_n128(float (&d)[64], uint32_t a0, uint32_t a1, uint32_t a2, uint32_t a3, uint64_t db) {
  asm volatile("wgmma.mma_async.sync.aligned.m64n128k16.f32.bf16.bf16 "
  "{%0,%1,%2,%3,%4,%5,%6,%7,%8,%9,%10,%11,%12,%13,%14,%15,%16,%17,%18,%19,%20,%21,%22,%23,%24,%25,%26,%27,%28,%29,%30,%31,%32,%33,%34,%35,%36,%37,%38,%39,%40,%41,%42,%43,%44,%45,%46,%47,%48,%49,%50,%51,%52,%53,%54,%55,%56,%57,%58,%59,%60,%61,%62,%63}, "
  "{%64,%65,%66,%67}, %68, 1, 1, 1, %69;"
  : "+f"(d[0]),"+f"(d[1]),"+f"(d[2]),"+f"(d[3]),"+f"(d[4]),"+f"(d[5]),"+f"(d[6]),"+f"(d[7]),"+f"(d[8]),"+f"(d[9]),"+f"(d[10]),"+f"(d[11]),"+f"(d[12]),"+f"(d[13]),"+f"(d[14]),"+f"(d[15]),"+f"(d[16]),"+f"(d[17]),"+f"(d[18]),"+f"(d[19]),"+f"(d[20]),"+f"(d[21]),"+f"(d[22]),"+f"(d[23]),"+f"(d[24]),"+f"(d[25]),"+f"(d[26]),"+f"(d[27]),"+f"(d[28]),"+f"(d[29]),"+f"(d[30]),"+f"(d[31]),"+f"(d[32]),"+f"(d[33]),"+f"(d[34]),"+f"(d[35]),"+f"(d[36]),"+f"(d[37]),"+f"(d[38]),"+f"(d[39]),"+f"(d[40]),"+f"(d[41]),"+f"(d[42]),"+f"(d[43]),"+f"(d[44]),"+f"(d[45]),"+f"(d[46]),"+f"(d[47]),"+f"(d[48]),"+f"(d[49]),"+f"(d[50]),"+f"(d[51]),"+f"(d[52]),"+f"(d[53]),"+f"(d[54]),"+f"(d[55]),"+f"(d[56]),"+f"(d[57]),"+f"(d[58]),"+f"(d[59]),"+f"(d[60]),"+f"(d[61]),"+f"(d[62]),"+f"(d[63])
  : "r"(a0), "r"(a1), "r"(a2), "r"(a3), "l"(db), "n"(TB));
}
template <int TA, int TB> __device__ __forceinline__ void wgmma_ss_n8(float (&d)[4], uint64_t da, uint64_t db) {
  asm volatile("wgmma.mma_async.sync.aligned.m64n8k16.f32.bf16.bf16 "
  "{%0,%1,%2,%3}, "
  "%4, %5, 1, 1, 1, %6, %7;"
  : "+f"(d[0]),"+f"(d[1]),"+f"(d[2]),"+f"(d[3])
  : "l"(da), "l"(db), "n"(TA), "n"(TB));
}
template <int TA, int TB> __device__ __forceinline__ void wgmma_ss_n16(float (&d)[8], uint64_t da, uint64_t db) {
  asm volatile("wgmma.mma_async.sync.aligned.m64n16k16.f32.bf16.bf16 "
  "{%0,%1,%2,%3,%4,%5,%6,%7}, "
  "%8, %9, 1, 1, 1, %10, %11;"
  : "+f"(d[0]),"+f"(d[1]),"+f"(d[2]),"+f"(d[3]),"+f"(d[4]),"+f"(d[5]),"+f"(d[6]),"+f"(d[7])
  : "l"(da), "l"(db), "n"(TA), "n"(TB));
}

constexpr int SEQ = 2048, DM = 1024, FF = 3584;
constexpr int NCTA = 128, NSVC = 4;
constexpr int NUNIT = 112;
constexpr uint32_t SLOT = 16384;
constexpr uint32_t MISC = 14 * SLOT;
constexpr uint32_t SMEM_BYTES = MISC + 3072;
constexpr uint32_t M_MOE = 0;
constexpr uint32_t M_BAR = 2048;
constexpr uint32_t M_DUM = 2048 + 1020;
constexpr uint32_t M_IDX = 2048 + 768;
constexpr uint32_t M_KEY = 2048 + 960;
#define R5 1
#define NQ (R5 ? 6 : 5)
constexpr int NF = 16 - NQ, NR = (NQ == 5 || R5) ? 4 : 3;
constexpr int B_FXQ = 0, B_FKV = 3, B_AST = 6, B_MOE = 7, B_MF = 8  , B_CQ = 12, B_XS = 13, B_DF = 14, B_ZOK = 15, B_FWO = 21  , B_FQ = B_FWO - NQ,
              B_UP = 37, B_FIN = 38, B_KVB = 39, B_ME = 40  , B_HF = 44, B_AF = 45  , B_AR = 50  , B_GO = 52,
              B_FAUX = 53, B_EAUX = 54, B_T0 = 55, B_DE = 56, B_EA = 57  , B_VAL = 62  ,
              B_E = 67  , B_STG = 70, B_EQ = 71  , B_EO = 76  , NBAR = 83, B_KV4 = 83, B_MS = 84,
              B_FV = 85  , B_EK = 88  , B_GQ = 91;
constexpr uint32_t MT = 9216, A_ONES = 12 * SLOT + 3 * MT, A_CS = A_ONES + 2048, A_ST = A_CS + 1536;
constexpr uint32_t A_TL = MISC + 2048 + 808;
constexpr int S_V0 = R5 ? 7 : 11, S_V1 = R5 ? 9 : 7;
constexpr uint32_t K_SLOTS = 0x8697A8u, V_SLOTS = 0x97A869u;
constexpr int C_B = 0, C_DONE = 32, NCNT = 2;
constexpr uint32_t QX_SLOTS = NQ == 5 ? 0x43102u : 0x354021u;
constexpr uint32_t QW_SLOTS = R5 ? 0xA9786Au : 0xB76A98u;
constexpr uint32_t qx(int k) { return (QX_SLOTS >> (4 * k)) & 15u; }
constexpr uint32_t qw(int k) { return (QW_SLOTS >> (4 * k)) & 15u; }
constexpr uint32_t S_KVB = R5 ? 1 : 8, S_D0 = R5 ? 11 : (NQ == 5 ? 5 : 1), S_D1 = R5 ? 2 : (NQ == 5 ? 11 : 2);
constexpr uint32_t S_M3 = R5 ? 11 : 5;
constexpr int WQ0 = NQ == 5 ? 1 : 3;
constexpr uint32_t wo_slot_c(int i) { return i >= 9 ? wo_slot_c(i - 9) : (i == 7 ? S_D0 : (i == 8 ? S_D1 : (((i & 1) || i + WQ0 == 1) ? qx((i + WQ0) >> 1) : qw((i + WQ0) >> 1)))); }
constexpr uint64_t wo_slots() { uint64_t t = 0; for (int i = 0; i < 16; i++) t |= (uint64_t)wo_slot_c(i) << (4 * i); return t; }
constexpr uint64_t WO_SLOTS = wo_slots();
constexpr uint32_t A_SLOTS = 0xDC000u | (S_KVB << 8) | (qw(NQ - 1) << 4) | qx(NQ - 1);
constexpr uint32_t SX14 = qx(NQ - 2), SX15 = qx(NQ - 1), SXQ0 = qx(0);
#define WOD 2
#define PLC 3
#define PFG1 10
#define PFNS1 150
#define PFG0 3
#define RS0 0
#define WPF 1
#define POLLNS 150
#define SVNS 100
#define MPROMO CU_TENSOR_MAP_L2_PROMOTION_L2_128B
#define MW0 0
#define PFILL 0
#define H2W (NQ - 3)
#define TOPW 1000
#define PFT 0
#define SV0 2
#define SV0A 14
#define SV0B 22
#define ASTE 2
#define PFS 1
#define PFTAB 0x0012222220000ull
#define HW 0
#define DPF 1
#define PROBE 0x8
#define OS1 0
#define YW 0
#define OS2 3
#define NOVAL 0
#define NDIR 1
#define I0 (2 + NDIR)
#define DW 0
#define OSP 1
#define NA 5
#define STAG 4
#define GOE 0
#define SVP 99
#define KEY1 0
#define HYB 0
#define DV 0
#define DVJ 4
#define DVK 10
#define FW 0
#define E1E 0
#define GATE 0
#define SVD 0
#define XPROMO CU_TENSOR_MAP_L2_PROMOTION_L2_128B
#define MC0 3
#define MX 0
#define OUTV 1
#define BW0 2
#define QL 1
#define NP 0
#define FINCP 0
#define DNS 0
#define WOK 99
#define WOD1 2
#define SVT 64
#define MRED 1
#define MRW -1
#define SQ 2
#define H2D 400
#define MRD 300
#define STP 0
#define TPNS 50
#define DLP 0
#define MFIN 0
#define MFD 300
#define SF 1
#define PH MFIN
#define RSL 0
#define PFW 3000
#define KVE 1
#define P2NS 0
#define OS3 4
#define PLP 2
#define FINJ 9
#define PFD 0
#define PFG 3
#define PFNS2 150
#define PFNS 250
#define MAP 2
#define RSNS 60
#define SVS 6
#define PRODLATE 0
#define MC 7
#define QE 0
#define TMP 1
#define TMPW 4
#define DS 14
#define RL 0
#define EV 0
#define LQ 0
#define SPL 0
#define HALFST 0
#define PHI2 1
#define E7 1
#define RK 1
#define LE 0
#define SL7 0
#define XP 3
#define VR 4
#define KEEP 1
#define KP 4
#define KC 1
#define MS 0
constexpr int CON_REGS = 224, MOE_REGS = 40, PROD_REGS = 24;
constexpr uint32_t SPIN_MAX = 2000000;
constexpr uint32_t SENT = 0xFFFFFFFFu;

struct __align__(128) Scratch {
  uint4 o[NCTA * 2048];
  uint4 part[NCTA * 544];
  uint4 fin[8 * 640];
  float2 stats[SEQ];
  uint32_t key[SEQ];
  uint32_t cs[3 * DM];
  uint4 y[NCTA * 128];
  uint32_t h[56 * 256];
  uint32_t top[128];
  uint32_t cnt[NCNT * 32];
};
__device__ Scratch G;
#define TLS(th, i)
#define TLP_(i)
#define TLG(i)
#define TLDUMP()

__device__ __forceinline__ bool elect_one() {
  uint32_t p;
  asm volatile("{\n.reg .pred P;\nelect.sync _|P, 0xffffffff;\nselp.b32 %0, 1, 0, P;\n}" : "=r"(p));
  return p;
}
__device__ __forceinline__ void mbar_init(uint32_t b, uint32_t c) { asm volatile("mbarrier.init.shared::cta.b64 [%0], %1;" ::"r"(b), "r"(c) : "memory"); }
__device__ __forceinline__ void mbar_expect_tx(uint32_t b, uint32_t bytes) { asm volatile("mbarrier.arrive.expect_tx.shared::cta.b64 _, [%0], %1;" ::"r"(b), "r"(bytes) : "memory"); }
__device__ __forceinline__ void mbar_arrive(uint32_t b) { asm volatile("mbarrier.arrive.shared::cta.b64 _, [%0];" ::"r"(b) : "memory"); }
__device__ __forceinline__ void mbar_wait_b(uint32_t b, uint32_t parity) {
  asm volatile(
      "{\n.reg .pred p;\n.reg .u32 cnt;\nmov.u32 cnt, 0;\n"
      "LW:\nmbarrier.try_wait.parity.shared::cta.b64 p, [%0], %1;\n@p bra LD;\n"
      "add.u32 cnt, cnt, 1;\nsetp.lt.u32 p, cnt, 4000000;\n@p bra LW;\ntrap;\nLD:\n}" ::"r"(b), "r"(parity) : "memory");
}
__device__ __forceinline__ void mbar_wait(uint32_t b, uint32_t parity) {
  asm volatile("{\n.reg .pred p;\nLW:\nmbarrier.try_wait.parity.shared::cta.b64 p, [%0], %1;\n@!p bra LW;\n}" ::"r"(b), "r"(parity) : "memory");
}
__device__ __forceinline__ bool mbar_test(uint32_t b, uint32_t parity) {
  uint32_t r;
  asm volatile("{\n.reg .pred p;\nmbarrier.test_wait.parity.shared::cta.b64 p, [%1], %2;\nselp.b32 %0, 1, 0, p;\n}" : "=r"(r) : "r"(b), "r"(parity) : "memory");
  return r;
}
__device__ __forceinline__ uint32_t ev_arrive(uint32_t a) { uint32_t r; asm volatile("atom.shared.add.u32 %0, [%1], 1;" : "=r"(r) : "r"(a) : "memory"); return r; }
__device__ __forceinline__ void tma2d(uint32_t dst, const CUtensorMap* m, int c0, int c1, uint32_t bar) {
  asm volatile("cp.async.bulk.tensor.2d.shared::cluster.global.mbarrier::complete_tx::bytes [%0], [%1, {%3, %4}], [%2];" ::"r"(dst), "l"(m), "r"(bar), "r"(c0), "r"(c1) : "memory");
}
__device__ __forceinline__ void tma3d(uint32_t dst, const CUtensorMap* m, int c1, int c2, uint32_t bar) {
  asm volatile("cp.async.bulk.tensor.3d.shared::cluster.global.mbarrier::complete_tx::bytes [%0], [%1, {%3, %4, %5}], [%2];" ::"r"(dst), "l"(m), "r"(bar), "r"(0), "r"(c1), "r"(c2) : "memory");
}
__device__ __forceinline__ void tma3d_mc(uint32_t dst, const CUtensorMap* m, int c1, int c2, uint32_t bar) {
  asm volatile("cp.async.bulk.tensor.3d.shared::cluster.global.mbarrier::complete_tx::bytes.multicast::cluster [%0], [%1, {%3, %4, %5}], [%2], %6;" ::"r"(dst), "l"(m), "r"(bar), "r"(0), "r"(c1), "r"(c2), "h"((uint16_t)3) : "memory");
}
__device__ __forceinline__ void tma5d(uint32_t dst, const CUtensorMap* m, int c2, int c4, uint32_t bar, bool mc) {
  if (mc) asm volatile("cp.async.bulk.tensor.5d.shared::cluster.global.mbarrier::complete_tx::bytes.multicast::cluster [%0], [%1, {%3, %3, %4, %3, %5}], [%2], %6;" ::"r"(dst), "l"(m), "r"(bar), "r"(0), "r"(c2), "r"(c4), "h"((uint16_t)3) : "memory");
  else asm volatile("cp.async.bulk.tensor.5d.shared::cluster.global.mbarrier::complete_tx::bytes [%0], [%1, {%3, %3, %4, %3, %5}], [%2];" ::"r"(dst), "l"(m), "r"(bar), "r"(0), "r"(c2), "r"(c4) : "memory");
}
__device__ __forceinline__ void mbar_arrive_cta(uint32_t b, uint32_t cta) {
  asm volatile("{\n.reg .b32 ra;\nmapa.shared::cluster.u32 ra, %0, %1;\nmbarrier.arrive.shared::cluster.b64 _, [ra];\n}" ::"r"(b), "r"(cta) : "memory");
}
constexpr uint64_t POL_FIRST = 0x12F0000000000000ull;
__device__ __forceinline__ void tma2d_ef(uint32_t dst, const CUtensorMap* m, int c0, int c1, uint32_t bar) {
  asm volatile("cp.async.bulk.tensor.2d.shared::cluster.global.mbarrier::complete_tx::bytes.L2::cache_hint [%0], [%1, {%3, %4}], [%2], %5;" ::"r"(dst), "l"(m), "r"(bar), "r"(c0), "r"(c1), "l"(POL_FIRST) : "memory");
}
__device__ __forceinline__ void bulk_ld(uint32_t dst, const void* src, uint32_t bytes, uint32_t bar) {
  asm volatile("cp.async.bulk.shared::cluster.global.mbarrier::complete_tx::bytes [%0], [%1], %2, [%3];" ::"r"(dst), "l"(src), "r"(bytes), "r"(bar) : "memory");
}
__device__ __forceinline__ void bulk_pf(const void* src, uint32_t bytes) { asm volatile("cp.async.bulk.prefetch.L2.global [%0], %1;" ::"l"(src), "r"(bytes) : "memory"); }
__device__ __forceinline__ void tma2d_pf(const CUtensorMap* m, int c0, int c1) {
  asm volatile("cp.async.bulk.prefetch.tensor.2d.L2.global [%0, {%1, %2}];" ::"l"(m), "r"(c0), "r"(c1) : "memory");
}
__device__ __forceinline__ void map_pf(const CUtensorMap* m) { asm volatile("prefetch.tensormap [%0];" ::"l"(m) : "memory"); }
__device__ __forceinline__ void line_pf(const void* p) { asm volatile("prefetch.global.L2 [%0];" ::"l"(p)); }
__device__ __forceinline__ void pf128(uint32_t dummy, const void* src) { asm volatile("cp.async.ca.shared.global.L2::128B [%0], [%1], 4;" ::"r"(dummy), "l"(src) : "memory"); }
__device__ __forceinline__ void pf256(uint32_t dummy, const void* src) { asm volatile("cp.async.ca.shared.global.L2::256B [%0], [%1], 4;" ::"r"(dummy), "l"(src) : "memory"); }
__device__ __forceinline__ void cp16x2(uint32_t dst, const void* src) {
  asm volatile("cp.async.cg.shared.global [%0], [%1], 16;\ncp.async.cg.shared.global [%0+4096], [%1+512], 16;" ::"r"(dst), "l"(src) : "memory");
}
constexpr uint32_t HI_SW128 = 0x40000000u | (1024 >> 4), HI_SW64 = 0x80000000u | (512 >> 4), HI_NOSW = 512 >> 4;
__device__ __forceinline__ uint64_t mkdesc(uint32_t lo, uint32_t hi) { uint64_t d; asm("mov.b64 %0, {%1, %2};" : "=l"(d) : "r"(lo), "r"(hi)); return d; }
__device__ __forceinline__ void wg_fence() { asm volatile("wgmma.fence.sync.aligned;" ::: "memory"); }
__device__ __forceinline__ void wg_commit() { asm volatile("wgmma.commit_group.sync.aligned;" ::: "memory"); }
template <int N> __device__ __forceinline__ void wg_wait() { asm volatile("wgmma.wait_group.sync.aligned %0;" ::"n"(N) : "memory"); }
template <int N> __device__ __forceinline__ void reg_fence(float (&a)[N]) {
#pragma unroll
  for (int i = 0; i < N; i++) asm volatile("" : "+f"(a[i])::"memory");
}
template <int ID, int N> __device__ __forceinline__ void bar_sync() { asm volatile("bar.sync %0, %1;" ::"n"(ID), "n"(N) : "memory"); }
__device__ __forceinline__ void fence_async_smem() { asm volatile("fence.proxy.async.shared::cta;" ::: "memory"); }
__device__ __forceinline__ void fence_async_gmem() { asm volatile("fence.proxy.async.global;" ::: "memory"); }
__device__ __forceinline__ uint32_t pack_bf16(float lo, float hi) { uint32_t r; asm("cvt.rn.bf16x2.f32 %0, %1, %2;" : "=r"(r) : "f"(hi), "f"(lo)); return r; }
__device__ __forceinline__ float bf_lo(uint32_t v) { return __uint_as_float(v << 16); }
__device__ __forceinline__ float bf_hi(uint32_t v) { return __uint_as_float(v & 0xFFFF0000u); }
__device__ __forceinline__ float bf_round(float v) { return bf_lo(pack_bf16(v, v)); }
__device__ __forceinline__ uint32_t bf_sub2(uint32_t a, uint32_t b) { uint32_t r; asm("sub.rn.bf16x2 %0, %1, %2;" : "=r"(r) : "r"(a), "r"(b)); return r; }
__device__ __forceinline__ float rcp(float v) { float r; asm("rcp.approx.ftz.f32 %0, %1;" : "=f"(r) : "f"(v)); return r; }
__device__ __forceinline__ float ex2(float v) { float r; asm("ex2.approx.ftz.f32 %0, %1;" : "=f"(r) : "f"(v)); return r; }
__device__ __forceinline__ float sigmoid(float v) { return rcp(1.f + ex2(v * -1.4426950408889634f)); }
__device__ __forceinline__ void stsm4(uint32_t a, uint32_t r0, uint32_t r1, uint32_t r2, uint32_t r3) {
  asm volatile("stmatrix.sync.aligned.m8n8.x4.shared.b16 [%0], {%1,%2,%3,%4};" ::"r"(a), "r"(r0), "r"(r1), "r"(r2), "r"(r3) : "memory");
}
__device__ __forceinline__ void stsm4t(uint32_t a, uint32_t r0, uint32_t r1, uint32_t r2, uint32_t r3) {
  asm volatile("stmatrix.sync.aligned.m8n8.x4.trans.shared.b16 [%0], {%1,%2,%3,%4};" ::"r"(a), "r"(r0), "r"(r1), "r"(r2), "r"(r3) : "memory");
}
__device__ __forceinline__ void ldsm4(uint32_t a, uint32_t& r0, uint32_t& r1, uint32_t& r2, uint32_t& r3) {
  asm volatile("ldmatrix.sync.aligned.m8n8.x4.shared.b16 {%0,%1,%2,%3}, [%4];" : "=r"(r0), "=r"(r1), "=r"(r2), "=r"(r3) : "r"(a) : "memory");
}
__device__ __forceinline__ uint32_t movmat(uint32_t a) { uint32_t d; asm volatile("movmatrix.sync.aligned.m8n8.trans.b16 %0, %1;" : "=r"(d) : "r"(a)); return d; }
__device__ __forceinline__ void sts_h(uint32_t a, float v) { asm volatile("st.shared.u16 [%0], %1;" ::"r"(a), "h"((uint16_t)pack_bf16(v, v)) : "memory"); }
__device__ __forceinline__ float2 lds_f2(uint32_t a) { float2 v; asm volatile("ld.shared.v2.f32 {%0,%1}, [%2];" : "=f"(v.x), "=f"(v.y) : "r"(a)); return v; }
__device__ __forceinline__ float lds_f(uint32_t a) { float v; asm volatile("ld.shared.f32 %0, [%1];" : "=f"(v) : "r"(a)); return v; }
__device__ __forceinline__ float4 lds_f4(uint32_t a) { float4 v; asm volatile("ld.shared.v4.f32 {%0,%1,%2,%3}, [%4];" : "=f"(v.x), "=f"(v.y), "=f"(v.z), "=f"(v.w) : "r"(a)); return v; }
__device__ __forceinline__ uint32_t lds_u(uint32_t a) { uint32_t v; asm volatile("ld.shared.u32 %0, [%1];" : "=r"(v) : "r"(a) : "memory"); return v; }
__device__ __forceinline__ uint4 lds_u4(uint32_t a) { uint4 v; asm volatile("ld.shared.v4.u32 {%0,%1,%2,%3}, [%4];" : "=r"(v.x), "=r"(v.y), "=r"(v.z), "=r"(v.w) : "r"(a) : "memory"); return v; }
__device__ __forceinline__ void sts_u(uint32_t a, uint32_t v) { asm volatile("st.shared.u32 [%0], %1;" ::"r"(a), "r"(v) : "memory"); }
__device__ __forceinline__ void sts_u4(uint32_t a, uint4 v) { asm volatile("st.shared.v4.u32 [%0], {%1,%2,%3,%4};" ::"r"(a), "r"(v.x), "r"(v.y), "r"(v.z), "r"(v.w) : "memory"); }
__device__ __forceinline__ uint4 ldx4(const void* p) { uint4 v; asm volatile("ld.relaxed.gpu.global.v4.u32 {%0,%1,%2,%3}, [%4];" : "=r"(v.x), "=r"(v.y), "=r"(v.z), "=r"(v.w) : "l"(p) : "memory"); return v; }
__device__ __forceinline__ uint2 ldx2(const void* p) { uint2 v; asm volatile("ld.relaxed.gpu.global.v2.u32 {%0,%1}, [%2];" : "=r"(v.x), "=r"(v.y) : "l"(p) : "memory"); return v; }
__device__ __forceinline__ uint32_t ldx1(const void* p) { uint32_t v; asm volatile("ld.relaxed.gpu.global.u32 %0, [%1];" : "=r"(v) : "l"(p) : "memory"); return v; }
__device__ __forceinline__ void stx4(void* p, uint32_t a, uint32_t b, uint32_t c, uint32_t d) { asm volatile("st.relaxed.gpu.global.v4.u32 [%0], {%1,%2,%3,%4};" ::"l"(p), "r"(a), "r"(b), "r"(c), "r"(d) : "memory"); }
__device__ __forceinline__ void stx2(void* p, uint32_t a, uint32_t b) { asm volatile("st.relaxed.gpu.global.v2.u32 [%0], {%1,%2};" ::"l"(p), "r"(a), "r"(b) : "memory"); }
__device__ __forceinline__ void stx1(void* p, uint32_t a) { asm volatile("st.relaxed.gpu.global.u32 [%0], %1;" ::"l"(p), "r"(a) : "memory"); }
__device__ __forceinline__ uint32_t umax4(uint4 v) { return max(max(v.x, v.y), max(v.z, v.w)); }
__device__ __forceinline__ uint32_t f2x(float f) { return min(__float_as_uint(f), 0xFFFFFFFEu); }
__device__ __forceinline__ void red4(float* p, float a, float b, float c, float d) { asm volatile("red.relaxed.gpu.global.add.v4.f32 [%0], {%1,%2,%3,%4};" ::"l"(p), "f"(a), "f"(b), "f"(c), "f"(d) : "memory"); }
__device__ __forceinline__ void cnt_arrive(int c) { asm volatile("red.release.gpu.global.add.u32 [%0], 1;" ::"l"(&G.cnt[c]) : "memory"); }
__device__ __forceinline__ void cnt_wait(int c, uint32_t target) {
#pragma unroll 1
  for (uint32_t it = 0; it < SPIN_MAX; it++) {
    uint32_t v;
    asm volatile("ld.acquire.gpu.global.u32 %0, [%1];" : "=r"(v) : "l"(&G.cnt[c]) : "memory");
    if (v >= target) break;
    __nanosleep(POLLNS);
  }
}
__device__ __forceinline__ void cnt_done() {
  uint32_t t;
  asm volatile("atom.acq_rel.gpu.global.add.u32 %0, [%1], 1;" : "=r"(t) : "l"(&G.cnt[C_DONE]) : "memory");
  if (t == NCTA + NSVC - 1) {
#pragma unroll 1
    for (int i = 0; i < NCNT; i++) G.cnt[i * 32] = 0;
  }
}
__device__ __forceinline__ float phi(float u, float rs, float rl) {
  float a = fmaf(u, rs, 1.000001f), e = ex2(u * rl), r;
  asm("add.sat.f32 %0, %1, 0f358637BD;" : "=f"(e) : "f"(e));
  asm("max.NaN.f32 %0, %1, %2;" : "=f"(r) : "f"(a), "f"(e));
  return r;
}

__device__ __forceinline__ uint32_t phi2(float u0, float rs0, float rl0, float u1, float rs1, float rl1) {
  float e0, e1;
  asm("{\n.reg .f32 t;\nabs.f32 t, %1;\nneg.f32 t, t;\nex2.approx.ftz.f32 %0, t;\n}" : "=f"(e0) : "f"(u0 * rl0));
  asm("{\n.reg .f32 t;\nabs.f32 t, %1;\nneg.f32 t, t;\nex2.approx.ftz.f32 %0, t;\n}" : "=f"(e1) : "f"(u1 * rl1));
  uint32_t e = pack_bf16(e0, e1), r;
  const uint32_t a = pack_bf16(fmaf(u0, rs0, 1.000001f), fmaf(u1, rs1, 1.000001f));
  asm("add.rn.bf16x2 %0, %0, %1;" : "+r"(e) : "r"(0x35863586u));
  asm("max.NaN.bf16x2 %0, %1, %2;" : "=r"(r) : "r"(a), "r"(e));
  return r;
}

__device__ __forceinline__ int kstep1(int e, int hg) { return e < 14 ? (e < 2 * hg ? e : e + 2) : 2 * hg + e - 14; }
__device__ __forceinline__ int slab(int n, int hg) {
  return n + (((n + 7 - hg) * 37) >> 8);
}
__host__ __device__ constexpr uint32_t d_off(int i) { return i < 3 ? 12 * SLOT + (NR == 4 ? i : (i == 2 ? 0 : i + 1)) * MT : (i < 5 ? S_D0 * SLOT + (i - 3) * 8192 : S_D1 * SLOT + (i - 5) * 8192); }
__host__ __device__ constexpr uint32_t h_off(int i) { return i < 3 ? 12 * SLOT + i * MT + 8192 : (i < 5 ? A_ONES + (i - 3) * 1024 : MISC + M_MOE + (i - 5) * 1024); }
__device__ __forceinline__ uint32_t m_off(int r) { return r < 3 ? 12 * SLOT + r * MT : S_M3 * SLOT; }
__device__ __forceinline__ int x_slot(int e, int s) { return NQ == 5 ? (e < 14 ? s : e - 11) : (e < 13 ? s : 3 + s); }
__device__ __forceinline__ uint32_t wo_slot(int i) { return (uint32_t)(WO_SLOTS >> (4 * i)) & 15u; }

__global__ void __launch_bounds__(512, 1)
fused_kernel(const __nv_bfloat16* __restrict__ x, const __nv_bfloat16* __restrict__ wqkv, const __nv_bfloat16* __restrict__ wo,
             const __nv_bfloat16* __restrict__ wr, const __nv_bfloat16* __restrict__ wd, const int by_sm,
             const __grid_constant__ CUtensorMap tmX, const __grid_constant__ CUtensorMap tmW,
             const __grid_constant__ CUtensorMap tmWo, const __grid_constant__ CUtensorMap tmOut,
             const __grid_constant__ CUtensorMap tmG, const __grid_constant__ CUtensorMap tmU,
             const __grid_constant__ CUtensorMap tmD, const __grid_constant__ CUtensorMap tmR,
             const __grid_constant__ CUtensorMap tmWp) {
  if (TMP && threadIdx.x == 32 * TMPW) { map_pf(&tmX); map_pf(&tmW); }
  extern __shared__ __align__(1024) uint8_t smem_raw[];
  const uint32_t sb = (uint32_t)__cvta_generic_to_shared(smem_raw);
  const uint32_t bars = sb + MISC + M_BAR;
  uint32_t smid;
  asm("mov.u32 %0, %%smid;" : "=r"(smid));
  const int tpc = smid >> 1;
  int cl = tpc + max(((tpc - 25) * 37) >> 8, 0);
  cl = tpc < 60 ? cl : cl - 1;
  cl = tpc < 62 ? cl : (tpc - 58) * 8;
  const int u = by_sm ? 2 * cl + (blockIdx.x & 1) : blockIdx.x;
  const int hg = (u >> 4) & 7, tb = u & 15;
  const int b = tb * 8 + hg;
  const int lane = threadIdx.x & 31;
  const int warp = __shfl_sync(~0u, threadIdx.x >> 5, 0);
  const int ltid = threadIdx.x;
  const int g = lane >> 2, t = lane & 3;
  const uint32_t d0 = (sb & 0x3FFFF) >> 4;
#define BAR(i) (bars + 8 * (i))
  TLS(0, 0);

  const int rank = u & 1;
  auto load_entry = [&](int e, int s) {
    const int k0 = kstep1(e, hg) * 64;
    mbar_expect_tx(BAR(B_FXQ + s), e < NF ? 2 * SLOT : SLOT);
    mbar_expect_tx(BAR(B_FKV + s), R5 ? SLOT : 2 * SLOT);
    if (R5 && e < 11) mbar_expect_tx(BAR(B_FV + s), SLOT);
    const uint32_t vb = R5 ? BAR(B_FV + s) : BAR(B_FKV + s);
    tma2d(sb + x_slot(e, s) * SLOT, &tmX, k0, tb * 128, BAR(B_FXQ + s));
    if (e < MC0 || !(MC & 1)) {
      if (e < NF) tma3d(sb + (3 + s) * SLOT, &tmW, k0, 2 * hg, BAR(B_FXQ + s));
      tma3d(sb + (6 + 2 * s) * SLOT, &tmW, k0, 16 + 2 * hg, BAR(B_FKV + s));
      tma3d(sb + (7 + 2 * s) * SLOT, &tmW, k0, 32 + 2 * hg, vb);
    } else {
      if (e < NF && (e & 1) == rank) tma3d_mc(sb + (3 + s) * SLOT, &tmW, k0, 2 * hg, BAR(B_FXQ + s));
      if (R5 && e >= 11) { if (rank == 0) tma3d_mc(sb + ((K_SLOTS >> (4 * (e - 10))) & 15u) * SLOT, &tmW, k0, 16 + 2 * hg, BAR(B_FKV + s)); }
      else tma3d_mc(sb + (6 + 2 * s + rank) * SLOT, &tmW, k0, 16 + 16 * rank + 2 * hg, rank ? vb : BAR(B_FKV + s));
    }
  };
  if (warp == FW && u < NCTA) {
    if (elect_one()) {
      mbar_init(BAR(B_FXQ), 1); mbar_init(BAR(B_FKV), 1);
      if (R5) mbar_init(BAR(B_FV), 1);
      load_entry(0, 0);
      asm volatile("fence.mbarrier_init.release.cluster;" ::: "memory");
      TLS(FW * 32, 61);
    }
    __syncwarp();
  }
  if (u >= NCTA) {
    const int j = u - NCTA;
    if (warp == 8 && elect_one()) {
#pragma unroll
      for (int i = 0; i < 13; i++) mbar_init(BAR(i), 1);
    }
    if (ltid < 64) sts_u4(sb + MISC + ltid * 16, make_uint4(0x3F803F80u, 0x3F803F80u, 0x3F803F80u, 0x3F803F80u));
    fence_async_smem();
    __syncthreads();
    if (warp < 4) {
      int s = 0, p = 0;
#pragma unroll 1
      for (int pass = 0; pass < 3; pass++) {
        float acc[4][4];
#pragma unroll
        for (int c = 0; c < 4; c++) acc[c][0] = acc[c][1] = acc[c][2] = acc[c][3] = 0.f;
#pragma unroll 1
        for (int k = 0; k < 16; k++) {
          mbar_wait(BAR(s), p);
          wg_fence();
#pragma unroll
          for (int c = 0; c < 4; c++)
#pragma unroll
            for (int kk = 0; kk < 4; kk++)
              wgmma_ss_n8<1, 0>(acc[c], mkdesc((d0 + s * 2048 + c * 512 + kk * 128) | (512u << 16), HI_SW128), mkdesc((d0 + (MISC >> 4)) | (1u << 16), HI_SW128));
          wg_commit();
          wg_wait<0>();
          if (ltid == 0) mbar_arrive(BAR(6 + s));
          if (++s == SVS) { s = 0; p ^= 1; }
        }
        uint32_t* pc = G.cs + (pass < 2 ? DM + pass * DM : 0) + j * 256 + warp * 16 + g;
#pragma unroll
        for (int c = 0; c < 4; c++) {
          reg_fence(acc[c]);
          const uint32_t v = __float_as_uint((t & 1) ? acc[c][2] : acc[c][0]);
          if (t < 2) stx1(pc + c * 64 + t * 8, v ? v : 0x80000000u);
        }
        TLS(0, 1 + pass);
      }
    } else if (warp >= 8 && j == 0) {
      const int wq = warp - 8;
      const uint32_t top = sb + MISC + 1024;
#pragma unroll 1
      for (uint32_t it = 0; it < SPIN_MAX; it++) {
        const uint4 v0 = ldx4(G.key + wq * 256 + lane * 4), v1 = ldx4(G.key + wq * 256 + 128 + lane * 4);
        uint32_t ok;
        asm volatile("{\n.reg .pred p, q;\nsetp.ne.u32 p, %1, 0;\nbar.red.and.pred q, 2, 256, p;\nselp.b32 %0, 1, 0, q;\n}" : "=r"(ok) : "r"((v0.x & v0.y & v0.z & v0.w & v1.x & v1.y & v1.z & v1.w) >> 27) : "memory");
        ok = __any_sync(~0u, ok);
        if (!ok && it) continue;
        TLS(256, 4);
        uint32_t np = 0u - (1u << 28), mine = 0;
#pragma unroll 1
        for (int r = 0; r < 8; r++) {
          const uint32_t m0 = __viaddmax_u32(v0.x, np, v0.y + np), m1 = __viaddmax_u32(v0.z, np, v0.w + np), m2 = __viaddmax_u32(v1.x, np, v1.y + np), m3 = __viaddmax_u32(v1.z, np, v1.w + np);
          np -= __reduce_max_sync(~0u, max(max(m0, m1), max(m2, m3)));
          if (g == r) mine = 0u - np;
        }
        if (t == 0) sts_u(top + (wq * 8 + g) * 4, mine);
        bar_sync<2, 256>();
        TLS(256, 5);
        int rk = 0;
#pragma unroll
        for (int i = 0; i < 4; i++) {
          const uint4 o = lds_u4(top + t * 64 + i * 16);
          rk += (o.x > mine) + (o.y > mine) + (o.z > mine) + (o.w > mine);
        }
        rk += __shfl_xor_sync(~0u, rk, 1);
        rk += __shfl_xor_sync(~0u, rk, 2);
        if (ok) { if (rk < 8) stx1(G.top + t * 32 + rk, mine); break; }
        __nanosleep(2500);
      }
      TLS(256, 7);
    } else if (warp == 4) {
      int s = 0, p = 1;
      if (SVD) __nanosleep(SVD);
#pragma unroll 1
      for (int i = 0; i < 48; i++) {
        mbar_wait(BAR(6 + s), p);
        if (j == 0 && i >= SV0A && i < SV0B) mbar_wait(BAR(s >= SV0 ? s - SV0 : s - SV0 + SVS), s >= SV0 ? p ^ 1 : p);
        if (elect_one()) {
          mbar_expect_tx(BAR(s), 2 * SLOT);
          const int ch = (i < 32 ? 16 + (i & 16) : 0) + j * 4, k0 = (i & 15) * 64;
          tma3d(sb + s * 2 * SLOT, &tmW, k0, ch, BAR(s));
          tma3d(sb + s * 2 * SLOT + SLOT, &tmW, k0, ch + 2, BAR(s));
        }
        if (++s == SVS) { s = 0; p ^= 1; }
      }
    }
    if (ltid == 0) cnt_wait(C_DONE, NCTA);
    __syncthreads();
    const uint4 zero = make_uint4(0, 0, 0, 0);
    if (ltid < 128) reinterpret_cast<uint4*>(G.key)[j * 128 + ltid] = zero;
    else if (ltid < 320) reinterpret_cast<uint4*>(G.cs)[j * 192 + ltid - 128] = zero;
    else if (ltid < 322) reinterpret_cast<uint4*>(G.top)[j * 8 + ltid - 320] = zero;
    if (ltid == 0) { cnt_done(); TLDUMP(); }
    return;
  }

  if (warp == 12) {
    if (elect_one()) {
#pragma unroll
      for (int i = 1; i < 7; i++) if (i != B_FKV) mbar_init(BAR(i), 1);
      if (R5) { mbar_init(BAR(B_FV + 1), 1); mbar_init(BAR(B_FV + 2), 1); }
      if (E1E) load_entry(1, 1);
      asm volatile("fence.mbarrier_init.release.cluster;" ::: "memory");
    }
  } else if (warp >= 13) {
    if (elect_one()) {
      if (warp == 15) {
#pragma unroll
        for (int i = B_FAUX; i < NBAR; i++) mbar_init(BAR(i), i < B_E || !MC ? 2 : 4);
        mbar_init(BAR(B_KV4), 4); mbar_init(BAR(B_MS), 2); mbar_init(BAR(B_GQ), 1);
        if (R5) { mbar_init(BAR(B_EK), 4); mbar_init(BAR(B_EK + 1), 4); mbar_init(BAR(B_EK + 2), 4); }
      } else {
#pragma unroll
        for (int i = 0; i < 23; i++) mbar_init(BAR((warp == 13 ? 7 : 30) + i), 1);
      }
      asm volatile("fence.mbarrier_init.release.cluster;" ::: "memory");
    }
  }
  __syncthreads();
  if (MC) asm volatile("barrier.cluster.arrive.relaxed.aligned;" ::: "memory");

  const bool unit = u < NUNIT;
  const int dcol = (u & 15) * 64, drow = (u >> 4) * 448;
  if (warp >= 12) {
    asm volatile("setmaxnreg.dec.sync.aligned.u32 %0;" ::"n"(PROD_REGS));
    if (MC && warp != 12) asm volatile("barrier.cluster.wait.aligned;" ::: "memory");
    if (warp == 12) {
      int s = 1 + E1E, p = 1, pn = 3;
#pragma unroll 1
      for (int e = 1 + E1E; e < 16; e++) {
        if (MC && e == MC0) asm volatile("barrier.cluster.wait.aligned;" ::: "memory");
        if (e == GATE) mbar_wait(BAR(B_FXQ), 0);
        mbar_wait(BAR(B_E + s), p);
        if (elect_one()) {
          load_entry(e, s);
          if (NR == 4 && e == 11) mbar_arrive(BAR(B_ME + 3));
          if (e == ASTE) {
            mbar_expect_tx(BAR(B_AST), 2 * SLOT + 2048);
            bulk_ld(sb + 12 * SLOT, x + (size_t)b * 16 * DM, 2 * SLOT, BAR(B_AST));
            bulk_ld(sb + MISC + M_MOE, wr, 2048, BAR(B_AST));
          } else if (e >= 3) {
            if (e < 6) bulk_pf(wqkv + (size_t)((e - 2) * 256 + 2 * b) * 3 * DM, 2 * 3 * DM * 2);
            if (e < 7) bulk_pf(wo + (size_t)((e - 3) * 256 + 2 * b) * DM, 2 * DM * 2);
            if (NUNIT) {
#pragma unroll 1
              for (int i = (PFTAB >> (4 * (e - 3))) & 15; i > 0; i--, pn++) {
                if (pn >= 16) { if (!(MX & 8)) tma2d_pf(&tmD, dcol, drow + (pn - 16) * 64); }
                else if (unit && !(MX & 2)) tma2d_pf(rank ? &tmU : &tmG, (u >> 1) * 64, pn * 64);
              }
            }
          }
        }
        if (R5 && e >= 11) {
          mbar_wait(BAR(B_EK + (s == 2 ? 0 : s + 1)), e >= 14);
          if (elect_one()) {
            mbar_expect_tx(BAR(B_FV + s), SLOT);
            if (rank) tma3d_mc(sb + ((V_SLOTS >> (4 * (e - 10))) & 15u) * SLOT, &tmW, kstep1(e, hg) * 64, 32 + 2 * hg, BAR(B_FV + s));
          }
        }
        if (++s == 3) { s = 0; p ^= 1; }
      }
#pragma unroll 1
      for (int k = 0; k < NQ; k++) {
        if (k == 0) mbar_wait(BAR(B_E + 1), 0);
        if (k == 1) mbar_wait(BAR(B_EK + 2), 1);
        if (k == 2) mbar_wait(BAR(B_EK + 0), 0);
        if (k == 3) mbar_wait(BAR(B_STG), 0);
        if (k == 5) mbar_wait(BAR(B_EQ), 0);
        if (elect_one()) {
          const int k0 = kstep1(NF + k, hg) * 64;
          mbar_expect_tx(BAR(B_FQ + k), SLOT);
          if (!(MC & 2)) tma3d(sb + ((QW_SLOTS >> (4 * k)) & 15u) * SLOT, &tmW, k0, 2 * hg, BAR(B_FQ + k));
          else if ((k & 1) == rank) tma3d_mc(sb + ((QW_SLOTS >> (4 * k)) & 15u) * SLOT, &tmW, k0, 2 * hg, BAR(B_FQ + k));
        }
      }
#pragma unroll 1
      for (int i = 0; i < 16; i++) {
        mbar_wait(i < 7 ? BAR(B_EQ + ((i + WQ0) >> 1)) : (i < 9 ? BAR(B_DE) : BAR(B_EO + i - 9)), 0);
        if (i == WOK) mbar_wait(BAR(B_KVB), 0);
        mbar_wait(BAR(B_FWO + i - (i < WOK ? WOD1 : WOD)), 0);
        if (elect_one()) {
          mbar_expect_tx(BAR(B_FWO + i), SLOT);
#pragma unroll
          for (int hf = 0; hf < ((MC & 4) ? 1 : 2); hf++) {
            const int n = 2 * i + ((MC & 4) ? rank : hf), m = slab(n - 4, hg), hd = n < 4 ? 4 * hg + n : 4 * (m & 7) + (m >> 3);
            if (i < 2 + NDIR) tma5d(sb + wo_slot(i) * SLOT + (n & 1) * 8192, &tmWp, hd * 4, 2 * hg, BAR(B_FWO + i), MC & 4);
            else if (MC & 4) tma3d_mc(sb + wo_slot(i) * SLOT + rank * 8192, &tmWo, hd * 32, 2 * hg, BAR(B_FWO + i));
            else tma3d(sb + wo_slot(i) * SLOT + hf * 8192, &tmWo, hd * 32, 2 * hg, BAR(B_FWO + i));
          }
        }
      }
    } else if (warp == 13) {
      if (elect_one()) {
        map_pf(rank ? &tmU : &tmG); map_pf(&tmR); map_pf(&tmD); map_pf(&tmWo); map_pf(&tmWp); map_pf(&tmOut);
      }
      bar_sync<6, 64>();
      if (elect_one()) {
        cnt_wait(C_B, NCTA);
        fence_async_gmem();
        mbar_expect_tx(BAR(B_FAUX), 1024);
        bulk_ld(sb + A_ST, G.stats + tb * 128, 1024, BAR(B_FAUX));
      }
      __syncwarp();
      TLS(416, 68);
#pragma unroll 1
      for (int m = 1; m < 4; m++) {
        const int part = m == 3 ? 0 : m;
        uint4 c;
#pragma unroll 1
        for (uint32_t it = 0; it < SPIN_MAX; it++) {
          c = ldx4(G.cs + part * DM + hg * 128 + lane * 4);
          if (__all_sync(~0u, min(min(c.x, c.y), min(c.z, c.w)))) break;
          __nanosleep(POLLNS);
        }
        sts_u4(sb + A_CS + part * 512 + lane * 16, c);
        __syncwarp();
        if (m > 1 && lane == 0) mbar_arrive(BAR(m == 2 ? B_FAUX : B_CQ));
        TLS(416, 71 + m);
      }
      mbar_wait(BAR(B_XS), 1);
      if (elect_one()) asm volatile("red.relaxed.gpu.global.add.u32 [%0], 1;" ::"l"(&G.cnt[C_DONE]) : "memory");
    } else if (warp == 14) {
      const uint4 sent = make_uint4(SENT, SENT, SENT, SENT);
      uint4* ro = G.o + (tb * 32 + hg) * 512 + lane;
      uint4* rp = G.part + b * 544 + lane;
      if (RSL) bar_sync<5, 160>(); else mbar_wait(BAR(B_AST), 0);
#pragma unroll 1
      for (int i = RS0; i < 40; i++) {
        uint4* q = i < 32 ? ro + (i >> 3) * 4096 + (i & 7) * 64 : rp + (i - 32) * 64;
        q[0] = sent; q[32] = sent;
        __nanosleep(RSNS);
      }
      rp[512] = sent;
#pragma unroll
      for (int i = 0; i < 4; i++) G.y[u * 128 + i * 32 + lane] = sent;
      if (unit) reinterpret_cast<uint4*>(G.h)[u * 32 + lane] = sent;
      G.fin[hg * 640 + tb * 40 + lane] = sent;
      if (lane < 8) G.fin[hg * 640 + tb * 40 + 32 + lane] = sent;
      if (!RSL) bar_sync<5, 160>();
      __syncwarp();
      TLS(448, 67);
      if (lane == 0) cnt_arrive(C_B);
      __syncwarp();
      TLS(448, 32);
      asm volatile("bar.arrive 6, 64;" ::: "memory");
    } else {
      const uint32_t stg = sb + 12 * SLOT;
      auto load_a = [&](int n, int r) {
        mbar_expect_tx(BAR(B_MF + r), (MX & 2) ? 1024 : MT);
        if (!(MX & 2)) tma2d_ef(sb + m_off(r), rank ? &tmU : &tmG, (u >> 1) * 64, n * 64, BAR(B_MF + r));
      };
      mbar_wait(BAR(B_XS), 0);
      if (unit) {
#pragma unroll 1
        for (int i = 0; i < 3; i++) {
          if (elect_one()) load_a(i, i);
          __nanosleep(PFILL);
        }
      }
      uint32_t key;
#pragma unroll 1
      for (uint32_t it = 0; it < SPIN_MAX; it++) {
        key = ldx1(G.top + ((u >> 1) & 3) * 32 + (lane & 7));
        if (__all_sync(~0u, key)) break;
        __nanosleep(TPNS);
      }
      TLS(480, 66);
      if (lane < 8) sts_u(sb + MISC + M_IDX + lane * 4, key);
      __syncwarp();
      if (lane == 0) mbar_arrive(BAR(B_XS));
      if (unit) {
        int tok[8];
#pragma unroll
        for (int i = 0; i < 8; i++) tok[i] = ~__shfl_sync(~0u, key, i) & 2047;
        int r = 0, p = 0;
#pragma unroll 1
        for (int n = 0; n < 16; n++) {
          if (n >= 3) mbar_wait(BAR(B_ME + r), r == 3 ? p : p ^ 1);
          if (elect_one()) {
            if (n >= 3) load_a(n, r);
#pragma unroll
            for (int i = 0; i < 8; i++) tma2d(sb + m_off(r) + 8192 + i * 128, &tmR, n * 64, tok[i], BAR(B_MF + r));
          }
          if (++r == NR) { r = 0; p ^= 1; }
        }
      }
      if (NUNIT) {
        if (lane == 0) mbar_expect_tx(BAR(B_DF), (MX & 8) ? 0 : 7 * 8192);
#pragma unroll 1
        for (int i = 0; i < 7; i++) {
          if (NR == 4) {
            if (i >= 3) mbar_wait(i < 5 ? BAR(B_ME + 3) : (R5 ? BAR(B_EQ + 1) : BAR(B_STG)), 0);
            else if (unit) mbar_wait(BAR(B_ME + i), 1);
          } else {
            if (i >= 3) mbar_wait(BAR(B_EQ + ((i - 3) >> 1)), 0);
            else if (unit) mbar_wait(BAR(B_ME + (i == 2 ? 0 : i + 1)), i == 2);
          }
          if (!(MX & 8) && elect_one()) tma2d_ef(sb + d_off(i), &tmD, dcol, drow + i * 64, BAR(B_DF));
          if (DNS) __nanosleep(DNS);
        }
      }
    }
    if (warp == 14) {
      if (DPF && NUNIT && !(MX & 8)) {
        mbar_wait(DS ? BAR(B_MS) : (DPF == 1 ? BAR(B_FQ) : BAR(B_T0)), 0);
#pragma unroll 1
        for (int pf = 0; pf < 7; pf++) { pf256(sb + MISC + M_DUM, wd + (size_t)(drow + pf * 64 + rank * 32 + lane) * DM + (dcol & ~127)); __nanosleep(PFNS2); }
      }
      const uint32_t* src = reinterpret_cast<const uint32_t*>(G.part + ((lane >> 3) * 32 + hg) * 544 + 512) + tb * 8 + (lane & 7);
      mbar_wait(BAR(B_EQ + MRW), 0);
      if (MRD) __nanosleep(MRD);
      uint32_t z0, z1, z2, z3;
#pragma unroll 1
      for (uint32_t it = 0; it < SPIN_MAX; it++) {
        z0 = ldx1(src); z1 = ldx1(src + 8 * 2176); z2 = ldx1(src + 16 * 2176); z3 = ldx1(src + 24 * 2176);
        if (!__any_sync(~0u, max(max(z0, z1), max(z2, z3)) == SENT)) break;
      }
      if (MRED == 2 && elect_one()) mbar_arrive(BAR(B_ZOK));
      float zz = (__uint_as_float(z0) + __uint_as_float(z1)) + (__uint_as_float(z2) + __uint_as_float(z3));
      zz += __shfl_xor_sync(~0u, zz, 8);
      zz += __shfl_xor_sync(~0u, zz, 16);
      stx1(reinterpret_cast<uint32_t*>(G.fin + hg * 640) + (tb >> 2) * 640 + 512 + ((tb >> 1) & 1) * 64 + (lane & 1) * 32 + (tb & 1) * 16 + ((lane & 7) >> 1) * 4 + (lane >> 3),
           pack_bf16(zz, zz));
      TLS(448, 12);
    }
    if (!MFIN && (warp == 13 || warp == 14)) {
      mbar_wait(BAR(B_EQ + H2W), 0);
      if (H2D) __nanosleep(H2D);
#pragma unroll 1
      for (uint32_t it = 0; it < SPIN_MAX; it++) {
        if (warp == 14 && elect_one()) { mbar_expect_tx(BAR(B_FIN), 10240); bulk_ld(sb + S_KVB * SLOT, G.fin + hg * 640, 10240, BAR(B_FIN)); }
        mbar_wait(BAR(B_FIN), it & 1);
        uint32_t m = 0;
#pragma unroll
        for (int i = 0; i < 10; i++) m = max(m, lds_u(sb + S_KVB * SLOT + (i * 64 + ltid - 416) * 16 + (g >> 1) * 4));
        uint32_t bad;
        asm volatile("{\n.reg .pred p, q;\nsetp.eq.u32 p, %1, 0xFFFFFFFF;\nbar.red.or.pred q, 7, 64, p;\nselp.b32 %0, 1, 0, q;\n}" : "=r"(bad) : "r"(m) : "memory");
        if (!__any_sync(~0u, bad)) break;
      }
      if (warp == 14 && elect_one()) mbar_arrive(BAR(B_KVB));
      TLS(448, 14);
    }
    if (PH && (warp == 13 || warp == 14)) {
      bar_sync<3, 192>();
      mbar_wait(BAR(B_STG), 0);
#pragma unroll 1
      for (uint32_t it = 0; NUNIT && it < SPIN_MAX; it++) {
        if (elect_one()) {
          const uint32_t* ph = G.h + (u >> 4) * 7 * 256;
          if (warp == 13) { mbar_expect_tx(BAR(B_HF), 7168); bulk_ld(sb + h_off(3), ph + 768, 2048, BAR(B_HF)); bulk_ld(sb + h_off(5), ph + 1280, 2048, BAR(B_HF)); }
          else { bulk_ld(sb + h_off(0), ph, 1024, BAR(B_HF)); bulk_ld(sb + h_off(1), ph + 256, 1024, BAR(B_HF)); bulk_ld(sb + h_off(2), ph + 512, 1024, BAR(B_HF)); }
        }
        mbar_wait(BAR(B_HF), it & 1);
        uint32_t m = 0;
#pragma unroll
        for (int i = 0; i < 7; i++) m = max(m, lds_u(sb + h_off(i) + (ltid - 416) * 16 + (g >> 1) * 4));
        uint32_t bad;
        asm volatile("{\n.reg .pred p, q;\nsetp.eq.u32 p, %1, 0xFFFFFFFF;\nbar.red.or.pred q, 7, 64, p;\nselp.b32 %0, 1, 0, q;\n}" : "=r"(bad) : "r"(m) : "memory");
        if (!__any_sync(~0u, bad)) break;
        __nanosleep(POLLNS);
      }
      if (warp == 14 && elect_one()) mbar_arrive(BAR(B_KVB));
    }
    __syncwarp();
    if (warp >= 13) {
      const char* og = reinterpret_cast<const char*>(G.o + tb * 16384);
      auto probe = [&](uint32_t m) {
        const char* p = og + m * 8192u + (lane & 15) * 512 + 496;
#pragma unroll 1
        for (uint32_t it = 0; it < SPIN_MAX; it++)
          if (!__any_sync(~0u, ldx1(p) == SENT)) break;
      };
      if (warp == 15) {
        int r = 0, p = 1;
        mbar_wait(BAR(B_EAUX), 0);
#pragma unroll 1
        for (int i = I0; i < 16; i++) {
          const uint32_t dst = sb + ((A_SLOTS >> (4 * r)) & 15u) * SLOT, m0 = slab(2 * i - 4, hg), m1 = slab(2 * i - 3, hg);
          if (i == I0 + 3) mbar_wait(BAR(B_DE), 0);
          mbar_wait(BAR(B_EA + r), p);
          if ((PROBE >> i) & 1) probe(lane < 16 ? m0 : m1);
          if (elect_one()) {
            mbar_expect_tx(BAR(B_AF + r), SLOT);
            bulk_ld(dst, og + m0 * 8192u, 8192, BAR(B_AF + r)); bulk_ld(dst + 8192, og + m1 * 8192u, 8192, BAR(B_AF + r));
          }
          if (++r == NA) { r = 0; p ^= 1; }
        }
      } else {
        const uint32_t lo = lane * 32 + g * 4, hb = sb + (warp - 13) * 8192;
        uint32_t ph = 0;
        int r = 0, p = 0;
#pragma unroll 1
        for (int i = I0; i < 16; i++) {
          const uint32_t mine = hb + ((A_SLOTS >> (4 * r)) & 15u) * SLOT;
          auto bad = [&]() {
            uint32_t v[8];
#pragma unroll
            for (int j = 0; j < 8; j++) v[j] = lds_u(mine + lo + j * 1024);
            return __any_sync(~0u, max(max(max(v[0], v[1]), max(v[2], v[3])), max(max(v[4], v[5]), max(v[6], v[7]))) == SENT);
          };
          mbar_wait(BAR(B_AF + r), p);
          if (!NOVAL && bad()) {
            const uint32_t m = slab(2 * i - 17 + warp, hg);
#pragma unroll 1
            for (uint32_t it = 0; it < 64; it++) {
              probe(m);
              if (elect_one()) { mbar_expect_tx(BAR(B_AR + warp - 13), 8192); bulk_ld(mine, og + m * 8192u, 8192, BAR(B_AR + warp - 13)); }
              mbar_wait(BAR(B_AR + warp - 13), ph);
              ph ^= 1;
              if (!bad()) break;
            }
          }
          if (elect_one()) mbar_arrive(BAR(B_VAL + r));
          if (++r == NA) { r = 0; p ^= 1; }
        }
      }
    }
  } else if (warp >= 8) {
    asm volatile("setmaxnreg.dec.sync.aligned.u32 %0;" ::"n"(MOE_REGS));
    if (MC) asm volatile("barrier.cluster.wait.aligned;" ::: "memory");
    const int aw = warp - 8;
    const uint32_t mbuf = sb + MISC + M_MOE, stg = sb + 12 * SLOT;
    mbar_wait(BAR(B_AST), 0);
    TLS(288, 64);
    {
      float v[16];
#pragma unroll
      for (int r = 0; r < 16; r++) v[r] = 0.f;
      const uint32_t base = stg + aw * 4 * 2048 + lane * 8;
#pragma unroll 1
      for (int c = 0; c < 8; c++) {
        const float2 w2 = lds_f2(mbuf + c * 256 + lane * 8);
        const float w[4] = {bf_lo(__float_as_uint(w2.x)), bf_hi(__float_as_uint(w2.x)), bf_lo(__float_as_uint(w2.y)), bf_hi(__float_as_uint(w2.y))};
        v[12] += (w[0] + w[1]) + (w[2] + w[3]);
#pragma unroll
        for (int r = 0; r < 4; r++) {
          const float2 x2 = lds_f2(base + r * 2048 + c * 256);
#pragma unroll
          for (int e = 0; e < 2; e++) {
            const uint32_t xx = __float_as_uint(e ? x2.y : x2.x);
            const float lo = bf_lo(xx), hi = bf_hi(xx);
            v[r] += lo; v[4 + r] = fmaf(lo, lo, v[4 + r]); v[8 + r] = fmaf(lo, w[2 * e], v[8 + r]);
            v[r] += hi; v[4 + r] = fmaf(hi, hi, v[4 + r]); v[8 + r] = fmaf(hi, w[2 * e + 1], v[8 + r]);
          }
        }
      }
#pragma unroll
      for (int l = 0; l < 4; l++) {
        const int n = 8 >> l;
        const bool up = lane & (2 * n);
#pragma unroll
        for (int r = 0; r < 8; r++) {
          if (r < n) { const float a = v[r], c = v[n + r]; v[r] = (up ? c : a) + __shfl_xor_sync(~0u, up ? a : c, 2 * n); }
        }
      }
      v[0] += __shfl_xor_sync(~0u, v[0], 1);
      const float sx = __shfl_sync(~0u, v[0], 2 * t), sq = __shfl_sync(~0u, v[0], 8 + 2 * t), sw = __shfl_sync(~0u, v[0], 16 + 2 * t), ws = __shfl_sync(~0u, v[0], 24);
      if (lane < 4) {
        const int row = b * 16 + aw * 4 + lane;
        const float mean = sx * (1.f / DM);
        const float var = fmaxf(fmaf(-mean, mean, sq * (1.f / DM)), 0.f);
        float sd;
        asm("sqrt.approx.ftz.f32 %0, %1;" : "=f"(sd) : "f"(bf_round(bf_round(var) + 1e-5f)));
        const float rstd = rcp(bf_round(sd));
        const float mb = bf_round(mean);
        uint32_t rb = pack_bf16(fmaf(-mb, ws, sw) * rstd, 0.f) & 0xFFFFu;
        rb = (rb & 0x8000u) ? (~rb & 0xFFFFu) : (rb | 0x8000u);
        const uint32_t key = (1u << 27) | (rb << 11) | (uint32_t)(2047 - row);
        if (KEY1) sts_u(sb + MISC + M_KEY + (aw * 4 + lane) * 4, key); else stx1(G.key + row, key);
        G.stats[row] = make_float2(mb, rstd);
      }
    }
    bar_sync<2, 128>();
    if (KEY1 && ltid < 272) stx1(G.key + b * 16 + lane, lds_u(sb + MISC + M_KEY + lane * 4));
    TLS(288, 65);
    sts_u4(sb + A_ONES + (ltid - 256) * 16, make_uint4(0x3F803F80u, 0x3F803F80u, 0x3F803F80u, 0x3F803F80u));
    fence_async_smem();
    asm volatile("bar.arrive 5, 160;" ::: "memory");
    if (ltid == 256) { if (unit && rank == 0) mbar_expect_tx(BAR(B_UP), 2048); mbar_arrive(BAR(B_XS)); }
    bar_sync<2, 128>();
    mbar_wait(BAR(B_XS), 1);
    TLS(288, 70);
    if (NUNIT) {
      if (unit) {
        int r = 0, p = 0;
        uint32_t rel = 0;
        float acc[8];
        uint2 s0, s1;
#pragma unroll
        for (int i = 0; i < 8; i++) acc[i] = 0.f;
        if (MS == 16) mbar_wait(BAR(B_T0), 0); else if (MS) mbar_wait(BAR(B_MS), 0);
#pragma unroll 1
        for (int n = 0; n < 16; n++) {
          if (n == 15) {
            mbar_wait(BAR(B_FAUX), 0);
            s0 = ldx2(G.stats + (~lds_u(sb + MISC + M_IDX + t * 8) & 2047)); s1 = ldx2(G.stats + (~lds_u(sb + MISC + M_IDX + t * 8 + 4) & 2047));
          }
          mbar_wait(BAR(B_MF + r), p);
          if (!(n & 3)) TLS(288, 56 + (n >> 2));
          const uint32_t mo = m_off(r) >> 4, da = (d0 + mo) | (512u << 16), db = (d0 + mo + 512) | (1u << 16);
          const uint32_t hb = 0x40000000u | ((A_ONES >> 4) - 512 - mo);
          wg_fence();
#pragma unroll
          for (int kk = 0; kk < ((MX & 1) ? 1 : 4); kk++) wgmma_ss_n16<1, 0>(acc, mkdesc(da + kk * 128, HI_SW128), mkdesc(db + kk * 2, hb));
          wg_commit();
          wg_wait<1>();
          if (n > 0 && !rel && ltid == 256) mbar_arrive(BAR(B_ME + (r == 0 ? NR - 1 : r - 1)));
          rel = 0;
          const int r0 = r;
          if (++r == NR) { r = 0; p ^= 1; }
        }
        wg_wait<0>();
        reg_fence(acc);
        {
          if (!MW0 && !rel && ltid == 256) mbar_arrive(BAR(B_ME + 15 % NR));
          TLS(288, 71);
          const float v0 = bf_round(fmaf(-__uint_as_float(s0.x), acc[4], acc[0]) * __uint_as_float(s0.y));
          const float v1 = bf_round(fmaf(-__uint_as_float(s1.x), acc[4], acc[1]) * __uint_as_float(s1.y));
          const float v2 = bf_round(fmaf(-__uint_as_float(s0.x), acc[6], acc[2]) * __uint_as_float(s0.y));
          const float v3 = bf_round(fmaf(-__uint_as_float(s1.x), acc[6], acc[3]) * __uint_as_float(s1.y));
          if (rank) {
            asm volatile("{\n.reg .b32 ra, rb;\nmapa.shared::cluster.u32 ra, %0, 0;\nmapa.shared::cluster.u32 rb, %1, 0;\n"
                         "st.async.weak.shared::cluster.mbarrier::complete_tx::bytes.v4.f32 [ra], {%2, %3, %4, %5}, [rb];\n}"
                         ::"r"(mbuf + (ltid - 256) * 16), "r"(BAR(B_UP)), "f"(v0), "f"(v1), "f"(v2), "f"(v3) : "memory");
          } else {
            const float g0 = bf_round(v0 * sigmoid(v0)), g1 = bf_round(v1 * sigmoid(v1)), g2 = bf_round(v2 * sigmoid(v2)), g3 = bf_round(v3 * sigmoid(v3));
            mbar_wait(BAR(B_UP), 0);
            const uint4 uu = lds_u4(mbuf + (ltid - 256) * 16);
            const uint32_t h0 = movmat(pack_bf16(g0 * __uint_as_float(uu.x), g1 * __uint_as_float(uu.y)));
            const uint32_t h1 = movmat(pack_bf16(g2 * __uint_as_float(uu.z), g3 * __uint_as_float(uu.w)));
            uint32_t* ph = G.h + (u >> 1) * 256 + g * 32 + t;
            stx1(ph + ((2 * aw) ^ g) * 4, h0); stx1(ph + ((2 * aw + 1) ^ g) * 4, h1);
          }
          TLS(288, 60);
        }
      }
    }
    if (PH) asm volatile("bar.arrive 3, 192;" ::: "memory");
    {
      const int wd_ = ltid & 63;
      const uint32_t* src = reinterpret_cast<const uint32_t*>(G.part + hg * 544 + (aw >> 1) * 256 + tb * 16) + wd_;
      mbar_wait(MRED == 2 ? BAR(B_ZOK) : BAR(B_EQ + MRW), 0);
      if (MRD) __nanosleep(MRD);
      TLS(256, 48);
      uint32_t v[16];
#pragma unroll 1
      for (uint32_t it = 0; it < SPIN_MAX; it++) {
        uint32_t m = 0;
#pragma unroll
        for (int i = 0; i < 16; i++) v[i] = ldx1(src + i * 8 * 2176);
#pragma unroll
        for (int i = 0; i < 16; i++) m = max(m, v[i]);
        if (!__any_sync(~0u, m == SENT)) break;
      }
      TLS(256, 55);
      float lo[4], hi[4];
#pragma unroll
      for (int i = 0; i < 4; i++) {
        lo[i] = (bf_lo(v[4 * i]) + bf_lo(v[4 * i + 1])) + (bf_lo(v[4 * i + 2]) + bf_lo(v[4 * i + 3]));
        hi[i] = (bf_hi(v[4 * i]) + bf_hi(v[4 * i + 1])) + (bf_hi(v[4 * i + 2]) + bf_hi(v[4 * i + 3]));
      }
      stx1(reinterpret_cast<uint32_t*>(G.fin + hg * 640) + (tb >> 2) * 640 + ((tb >> 1) & 1) * 64 + (tb & 1) * 16 + (aw >> 1) * 32 + ((wd_ >> 2) & 3) * 128 + (wd_ >> 4) * 4 + (wd_ & 3),
           pack_bf16((lo[0] + lo[1]) + (lo[2] + lo[3]), (hi[0] + hi[1]) + (hi[2] + hi[3])));
      TLS(256, 5);
    }
    if (NUNIT) {
      mbar_wait(BAR(B_STG), 0);
      bar_sync<2, 128>();
      if (HW) __nanosleep(HW);
#pragma unroll 1
      for (uint32_t it = 0; it < SPIN_MAX; it++) {
        if (elect_one()) {
          const uint32_t* ph = G.h + (u >> 4) * 7 * 256;
          if (aw == 3) { mbar_expect_tx(BAR(B_HF), 7168); bulk_ld(sb + h_off(3), ph + 768, 2048, BAR(B_HF)); bulk_ld(sb + h_off(5), ph + 1280, 2048, BAR(B_HF)); }
          else bulk_ld(stg + aw * MT + 8192, ph + aw * 256, 1024, BAR(B_HF));
        }
        mbar_wait(BAR(B_HF), it & 1);
        const uint32_t o = (ltid & 63) * 16 + (g >> 1) * 4, o2 = o + (aw >> 1) * 1024;
        const uint32_t m = max(max(lds_u(sb + h_off(0) + (aw >> 1) * MT + o), lds_u(sb + h_off(2) + o)), max(lds_u(sb + h_off(3) + o2), lds_u(sb + h_off(5) + o2)));
        uint32_t bad;
        asm volatile("{\n.reg .pred p, q;\nsetp.eq.u32 p, %1, 0xFFFFFFFF;\nbar.red.or.pred q, 2, 128, p;\nselp.b32 %0, 1, 0, q;\n}" : "=r"(bad) : "r"(m) : "memory");
        if (!__any_sync(~0u, bad)) break;
        __nanosleep(POLLNS);
      }
      TLS(288, 62);
      float acc[4] = {0.f, 0.f, 0.f, 0.f};
      mbar_wait(BAR(B_DF), 0);
      TLS(288, 63);
#pragma unroll 1
      for (int i = 0; i < 7; i++) {
        const uint32_t da = (d0 + (d_off(i) >> 4)) | (512u << 16), db = (d0 + (h_off(i) >> 4)) | (1u << 16);
        wg_fence();
#pragma unroll
        for (int kk = 0; kk < ((MX & 4) ? 1 : 4); kk++) wgmma_ss_n8<1, 0>(acc, mkdesc(da + kk * 128, HI_SW128), mkdesc(db + kk * 2, HI_SW128));
        wg_commit();
      }
      wg_wait<0>();
      reg_fence(acc);
      if (ltid < 258) { if (MC) mbar_arrive_cta(BAR(B_DE), ltid & 1); else mbar_arrive(BAR(B_DE)); }
      {
        uint32_t* py = reinterpret_cast<uint32_t*>(G.y) + u * 512 + t * 128 + aw * 16 + g;
        stx1(py, f2x(acc[0])); stx1(py + 64, f2x(acc[1])); stx1(py + 8, f2x(acc[2])); stx1(py + 72, f2x(acc[3]));
      }
      TLS(288, 69);
      const uint32_t key = lds_u(sb + MISC + M_IDX + (lane & 7) * 4);
      uint32_t rb = (key >> 11) & 0xFFFFu;
      rb = (rb & 0x8000u) ? (rb & 0x7FFFu) : (~rb & 0xFFFFu);
      const float sg = bf_round(sigmoid(__uint_as_float(rb << 16)));
      uint32_t hits = __ballot_sync(~0u, ((~key >> 7) & 15) == tb) & 255u;
      const uint32_t* py = reinterpret_cast<const uint32_t*>(G.y) + (2 * hg + (aw >> 1)) * 512 + (ltid & 63);
      if (hits) {
        sts_u4(mbuf + (ltid - 256) * 16, make_uint4(0, 0, 0, 0));
        bar_sync<2, 128>();
        if (YW >= 0) mbar_wait(BAR(B_EO + YW), 0); else if (YW == -2) mbar_wait(BAR(B_EAUX), 0);
      }
#pragma unroll 1
      while (hits) {
        const int n0 = __ffs(hits) - 1;
        hits &= hits - 1;
        const int n1 = hits ? __ffs(hits) - 1 : n0;
        hits &= hits - 1;
        uint32_t v[16];
#pragma unroll 1
        for (uint32_t it = 0; it < SPIN_MAX; it++) {
          uint32_t m = 0;
#pragma unroll
          for (int i = 0; i < 8; i++) { v[i] = ldx1(py + n0 * 64 + i * 8192); v[8 + i] = ldx1(py + n1 * 64 + i * 8192); }
#pragma unroll
          for (int i = 0; i < 16; i++) m = max(m, v[i]);
          if (!__any_sync(~0u, m == SENT)) break;
          __nanosleep(POLLNS);
        }
#pragma unroll
        for (int e = 0; e < 2; e++) {
          const uint32_t* w8 = v + 8 * e;
          const float y = ((__uint_as_float(w8[0]) + __uint_as_float(w8[1])) + (__uint_as_float(w8[2]) + __uint_as_float(w8[3]))) +
                          ((__uint_as_float(w8[4]) + __uint_as_float(w8[5])) + (__uint_as_float(w8[6]) + __uint_as_float(w8[7])));
          const int n = e ? n1 : n0;
          sts_h(mbuf + (aw >> 1) * 1024 + n * 128 + ((((ltid >> 3) & 7) ^ n) << 4) + (lane & 7) * 2, bf_round(y) * __shfl_sync(~0u, sg, n));
        }
      }
    }
    if (!NUNIT && ltid < 258) mbar_arrive(BAR(B_DE));
    fence_async_smem();
    bar_sync<2, 128>();
    TLS(288, 33);
    if (ltid == 288) mbar_arrive(BAR(B_MOE));
  } else {
    asm volatile("setmaxnreg.inc.sync.aligned.u32 %0;" ::"n"(CON_REGS));
    if (MC) asm volatile("barrier.cluster.wait.aligned;" ::: "memory");
    const int w = warp >> 2, wq = warp & 3, tid = ltid;
    const bool lead = (tid & 127) == 0;
    const uint32_t dA = (d0 + w * 512) | (1u << 16);
    const uint32_t dB = d0 | (512u << 16);
    auto release = [&](int bar) { if (lead) mbar_arrive(BAR(bar)); };
    auto release2 = [&](int bar) {
      if (MC) { if ((tid & 127) < 2) mbar_arrive_cta(BAR(bar), tid & 1); } else release(bar);
    };
    float aq[64], ak[64], av[64];
#pragma unroll
    for (int i = 0; i < 64; i++) aq[i] = ak[i] = av[i] = 0.f;
    auto q_step = [&](uint32_t bar, int p, uint32_t xs, uint32_t qs) {
      mbar_wait_b(bar, p);
      wg_fence();
#pragma unroll
      for (int kk = 0; kk < 4; kk++)
        wgmma_ss_n128<0, 1>(aq, mkdesc(dA + xs * 1024 + kk * 2, HI_SW128), mkdesc(dB + qs * 1024 + kk * 128, HI_SW128));
      wg_commit();
    };
    const uint32_t dT = dB + w * 512, dX = d0 | (1u << 16);
    auto t_step = [&](float (&a)[64], uint32_t ws, uint32_t xs) {
      wg_fence();
#pragma unroll
      for (int kk = 0; kk < 4; kk++)
        wgmma_ss_n128<1, 0>(a, mkdesc(dT + ws * 1024 + kk * 128, HI_SW128), mkdesc(dX + xs * 1024 + kk * 2, HI_SW128));
      wg_commit();
    };
    {
      int s = 0, p = 0, sp = 2;
#pragma unroll 1
      for (int e = 0; e < NF; e++) {
        TLS(0, 16 + e);
        if (((MS && MS < NF) || (DS && DS < NF)) && e == (MS ? MS : DS)) release(B_MS);
        q_step(BAR(B_FXQ + s), p, s, 3 + s);
        wg_wait<1>();
        if (e > 0) release2(B_E + sp);
        mbar_wait(BAR(B_FKV + s), p);
        t_step(ak, 6 + 2 * s, s);
        if (R5) mbar_wait(BAR(B_FV + s), p);
        t_step(av, 7 + 2 * s, s);
        if (R5 && e == NF - 1) { wg_wait<1>(); release2(B_EK + s); }
        sp = s;
        if (++s == 3) { s = 0; p ^= 1; }
      }
#pragma unroll 1
      for (int e = NF; e < 16; e++) {
        TLS(0, 16 + e);
        if (((MS >= NF && MS < 16) || DS >= NF) && e == (MS ? MS : DS)) release(B_MS);
        mbar_wait(BAR(B_FXQ + s), p);
        mbar_wait(BAR(B_FKV + s), p);
        t_step(ak, R5 ? (K_SLOTS >> (4 * (e - 10))) & 15u : 6 + 2 * s, x_slot(e, s));
        wg_wait<1>();
        release2(B_E + sp);
        if (R5) mbar_wait(BAR(B_FV + s), p);
        t_step(av, R5 ? (V_SLOTS >> (4 * (e - 10))) & 15u : 7 + 2 * s, x_slot(e, s));
        if (R5) { wg_wait<1>(); release2(B_EK + s); }
        sp = s;
        if (++s == 3) { s = 0; p ^= 1; }
      }
    }
    const uint32_t aux = sb;
    mbar_wait(BAR(B_FAUX), 0);
    const int row0 = w * 64 + wq * 16 + g;
    const float ck0 = lds_f(aux + A_CS + 512 + row0 * 4), ck1 = lds_f(aux + A_CS + 512 + (row0 + 8) * 4);
    const float cv0 = lds_f(aux + A_CS + 1024 + row0 * 4), cv1 = lds_f(aux + A_CS + 1024 + (row0 + 8) * 4);
    const uint32_t moff = (uint32_t)(w * 64 + wq * 16 + (lane & 15)) * 128 + (((lane >> 4) ^ (lane & 7)) << 4);
    const uint32_t sta = aux + A_ST + t * 16;
    float kvp[36], ao[64];
    uint32_t xr[32];
    float nm0, nm1, rs0, rs1;
    auto row_stats = [&]() {
      const float2 st0 = lds_f2(aux + A_ST + row0 * 8), st1 = lds_f2(aux + A_ST + (row0 + 8) * 8);
      nm0 = -st0.x; nm1 = -st1.x; rs0 = st0.y; rs1 = st1.y;
    };
    auto ld_x = [&]() {
#pragma unroll
      for (int j = 0; j < 16; j += 2) ldsm4(sb + (j < 8 ? SX14 : SX15) * SLOT + (moff ^ ((j & 7) << 4)), xr[2 * j], xr[2 * j + 1], xr[2 * j + 2], xr[2 * j + 3]);
    };
    auto resid = [&]() {
      const float c0 = 1.f + rs0, c1 = 1.f + rs1, e0 = nm0 * rs0, e1 = nm1 * rs1;
#pragma unroll
      for (int j = 0; j < 16; j++) {
        ao[4 * j + 0] = fmaf(bf_lo(xr[2 * j]), c0, e0); ao[4 * j + 1] = fmaf(bf_hi(xr[2 * j]), c0, e0);
        ao[4 * j + 2] = fmaf(bf_lo(xr[2 * j + 1]), c1, e1); ao[4 * j + 3] = fmaf(bf_hi(xr[2 * j + 1]), c1, e1);
      }
    };
    {
      uint32_t pa[32];
      float4 st[16];
      auto ld = [&](int j) { st[j] = lds_f4(sta + j * 64); };
      auto k_blk = [&](int c) {
#pragma unroll
        for (int i = 0; i < 2; i++) {
          const float4 u = st[2 * c + i];
          const float l0 = u.y * 1.4426950408889634f, l1 = u.w * 1.4426950408889634f;
          const float* a = ak + 8 * c + 4 * i;
          pa[4 * c + 2 * i] = phi2(fmaf(-u.x, ck0, a[0]), u.y, l0, fmaf(-u.z, ck0, a[1]), u.w, l1);
          pa[4 * c + 2 * i + 1] = phi2(fmaf(-u.x, ck1, a[2]), u.y, l0, fmaf(-u.z, ck1, a[3]), u.w, l1);
        }
      };
      const uint32_t voff = sb + w * 8192 + (uint32_t)(8 * (lane >> 4) + (lane & 7)) * 128 + (((2 * wq + ((lane >> 3) & 1)) ^ (lane & 7)) << 4);
      auto v_blk = [&](int c) {
        uint32_t r[4];
#pragma unroll
        for (int i = 0; i < 2; i++) {
          const float4 u = st[2 * c + i];
          const float* a = av + 8 * c + 4 * i;
          r[2 * i] = pack_bf16(fmaf(-u.x, cv0, a[0]) * u.y, fmaf(-u.z, cv0, a[1]) * u.w);
          r[2 * i + 1] = pack_bf16(fmaf(-u.x, cv1, a[2]) * u.y, fmaf(-u.z, cv1, a[3]) * u.w);
        }
        stsm4t(voff + (c < 4 ? S_V0 : S_V1) * SLOT + (c & 3) * 2048, r[0], r[1], r[2], r[3]);
      };
      auto kv_mma = [&](int c) {
        const uint32_t bo = (c < 4 ? S_V0 : S_V1) * 1024 + w * 512 + (c & 3) * 128;
        const uint64_t bb = mkdesc((d0 + bo) | (((A_ONES >> 4) - bo) << 16), HI_SW128);
        if (c == 0) wgmma_rz_n72<1>(kvp, pa[4 * c], pa[4 * c + 1], pa[4 * c + 2], pa[4 * c + 3], bb);
        else wgmma_rs_n72<1>(kvp, pa[4 * c], pa[4 * c + 1], pa[4 * c + 2], pa[4 * c + 3], bb);
      };
      ld(0); ld(1);
      wg_wait<0>();
      reg_fence(ak); reg_fence(av);
      TLS(0, 2);
      if (!R5) release2(B_E);
      release(B_T0);
      if (LQ) { v_blk(0); ld(2); ld(3); } else { ld(2); ld(3); v_blk(0); }
      ld(4); ld(5); v_blk(1); k_blk(0);
      ld(6); ld(7); v_blk(2); ld(8); ld(9); v_blk(3); k_blk(1);
      ld(10); ld(11); v_blk(4); ld(12); ld(13); v_blk(5); k_blk(2);
      ld(14); ld(15); v_blk(6); v_blk(7); k_blk(3);
      if (RL) { ld(8); ld(9); }
      TLS(0, 3);
      fence_async_smem();
      asm volatile("bar.sync %0, 128;" ::"r"(3 + w) : "memory");
      if (XP == 0) ld_x();
      wg_fence();
      kv_mma(0); kv_mma(1); kv_mma(2); kv_mma(3);
      wg_commit();
#pragma unroll
      for (int c = 4; c < 8; c++) {
        if (RL && c < 7) { ld(2 * c + 2); ld(2 * c + 3); }
        k_blk(c);
        wg_fence();
        kv_mma(c);
        wg_commit();
      }
      if (XP == 3 && (RK == 0 || RK > 4)) ld_x();
      if (QE) { q_step(BAR(B_FQ), 0, SXQ0, QW_SLOTS & 15u); wg_wait<1>(); } else wg_wait<0>();
      reg_fence(kvp);
      auto hand_back = [&]() { release2(B_STG); __syncwarp(); };
      if (!SF) hand_back();
      TLS(0, 4);
      uint4* pp = G.part + b * 544;
      uint32_t pk[8];
#pragma unroll
      for (int j = 0; j < 8; j++) pk[j] = wq >= 2 ? pack_bf16(kvp[16 + 2 * j], kvp[17 + 2 * j]) : pack_bf16(kvp[2 * j], kvp[2 * j + 1]);
      stx4(pp + tid, pk[0], pk[2], pk[4], pk[6]);
      stx4(pp + 256 + tid, pk[1], pk[3], pk[5], pk[7]);
      if (t == 0) stx2(reinterpret_cast<uint2*>(pp + 512) + (tid >> 2), f2x(kvp[32]), f2x(kvp[34]));
      if (SF == 1) hand_back();
      if (XP == 1) ld_x();
      if (!QE) q_step(BAR(B_FQ), 0, SXQ0, QW_SLOTS & 15u);
      if (XP == 2) ld_x();
      if (SF == 2) hand_back();
      const int wd_ = wq * 16 + (lane & 15);
      const uint32_t* src = reinterpret_cast<const uint32_t*>(G.part + ((lane >> 4) * 64 + hg) * 544 + w * 256 + tb * 16) + wd_;
      uint32_t* fin = reinterpret_cast<uint32_t*>(G.fin + hg * 640) + (tb >> 2) * 640 + ((tb >> 1) & 1) * 64 + (tb & 1) * 16 + w * 32 + ((wd_ >> 2) & 3) * 128 + wq * 4 + (wd_ & 3);
      uint32_t v[8];
      auto part_load = [&]() {
#pragma unroll
        for (int i = 0; i < 8; i++) v[i] = ldx1(src + i * 8 * 2176);
      };
#pragma unroll
      for (int k = 1; k < NQ; k++) {
        if (SQ && k == NQ - SQ && w == 1) mbar_wait(BAR(B_GQ), 0);
        q_step(BAR(B_FQ + k), 0, (QX_SLOTS >> (4 * k)) & 15u, (QW_SLOTS >> (4 * k)) & 15u);
        if (SQ && k == NQ - 1 && tid == 0) mbar_arrive(BAR(B_GQ));
        TLS(0, 48 + k);
        if (k == RK) { row_stats(); ld_x(); resid(); }
        if (!MRED && k == PLP) part_load();
        if (!MRED && k == PLC) {
#pragma unroll 1
          for (uint32_t it = 0; it < SPIN_MAX; it++) {
            if (!__any_sync(~0u, max(max(max(v[0], v[1]), max(v[2], v[3])), max(max(v[4], v[5]), max(v[6], v[7]))) == SENT)) break;
            part_load();
          }
          float lo = ((bf_lo(v[0]) + bf_lo(v[1])) + (bf_lo(v[2]) + bf_lo(v[3]))) + ((bf_lo(v[4]) + bf_lo(v[5])) + (bf_lo(v[6]) + bf_lo(v[7])));
          float hi = ((bf_hi(v[0]) + bf_hi(v[1])) + (bf_hi(v[2]) + bf_hi(v[3]))) + ((bf_hi(v[4]) + bf_hi(v[5])) + (bf_hi(v[6]) + bf_hi(v[7])));
          lo += __shfl_xor_sync(~0u, lo, 16); hi += __shfl_xor_sync(~0u, hi, 16);
          if (lane < 16) stx1(fin, pack_bf16(lo, hi));
          TLS(0, 5);
        }
        wg_wait<1>();
        release2(B_EQ + k - 1);
      }
      TLS(0, 13);
      mbar_wait(BAR(B_CQ), 0);
    }
    wg_wait<0>();
    reg_fence(aq);
    TLS(0, 15);
    if (RK == 0 || RK > 4) row_stats();
    const float rl0 = rs0 * 1.4426950408889634f, rl1 = rs1 * 1.4426950408889634f;
    uint32_t pq[32];
#pragma unroll
    for (int j = 0; j < 16; j++) {
      const float2 c = lds_f2(aux + A_CS + (j * 8 + 2 * t) * 4);
      const float* a = aq + 4 * j;
      pq[2 * j] = phi2(fmaf(nm0, c.x, a[0]), rs0, rl0, fmaf(nm0, c.y, a[1]), rs0, rl0);
      pq[2 * j + 1] = phi2(fmaf(nm1, c.x, a[2]), rs1, rl1, fmaf(nm1, c.y, a[3]), rs1, rl1);
    }
    TLS(0, 6);
    if (RK == 5) resid();
    mbar_wait_b(BAR(MFIN ? B_KV4 : B_KVB), 0);
    TLS(0, 7);
    uint32_t of[32];
    uint4* mine = G.o + (tb * 32 + hg) * 512 + warp * 64 + g * 4 + (t ^ (g >> 1));
    const uint32_t dW = d0 | (256u << 16);
    auto o_store = [&](int h) {
#pragma unroll
      for (int c = 0; c < 2; c++) stx4(mine + h * 4096 + c * 32, of[8 * h + c], of[8 * h + 2 + c], of[8 * h + 4 + c], of[8 * h + 6 + c]);
    };
    auto out_step = [&](uint32_t slot, const uint32_t* a) {
      const uint32_t d = dW + slot * 1024;
      wg_fence();
#pragma unroll
      for (int kk = 0; kk < 4; kk++) wgmma_rs_n128<1>(ao, a[4 * kk], a[4 * kk + 1], a[4 * kk + 2], a[4 * kk + 3], mkdesc(d + (kk >> 1) * 512 + (kk & 1) * 128, HI_SW128));
      wg_commit();
    };
    uint4 v[NDIR][4];
    auto ld_o = [&](int k) {
      const uint4* p0 = mine + (slab(2 * k, hg) - hg) * 512;
      const uint4* p1 = mine + (slab(2 * k + 1, hg) - hg) * 512;
      v[k][0] = ldx4(p0); v[k][1] = ldx4(p0 + 32); v[k][2] = ldx4(p1); v[k][3] = ldx4(p1 + 32);
    };
    auto ld_all = [&]() {
#pragma unroll
      for (int k = 0; k < NDIR; k++) ld_o(k);
    };
    {
      float oa[4][20];
      const uint32_t dK = (d0 + S_KVB * 1024) | (8u << 16);
      wg_fence();
#pragma unroll
      for (int h = 0; h < 4; h++) {
        wgmma_rz_n40<1>(oa[h], pq[8 * h], pq[8 * h + 1], pq[8 * h + 2], pq[8 * h + 3], mkdesc(dK + h * 160, HI_NOSW));
        wgmma_rs_n40<1>(oa[h], pq[8 * h + 4], pq[8 * h + 5], pq[8 * h + 6], pq[8 * h + 7], mkdesc(dK + h * 160 + 16, HI_NOSW));
        if (h == 0 || h == 3) wg_commit();
      }
      auto norm = [&](int h) {
        const float r0 = rcp(oa[h][16] + 1e-6f), r1 = rcp(oa[h][18] + 1e-6f);
#pragma unroll
        for (int j = 0; j < 4; j++) {
          of[8 * h + 2 * j] = pack_bf16(oa[h][4 * j] * r0, oa[h][4 * j + 1] * r0);
          of[8 * h + 2 * j + 1] = pack_bf16(oa[h][4 * j + 2] * r1, oa[h][4 * j + 3] * r1);
        }
      };
      wg_wait<1>();
      reg_fence(oa[0]);
      norm(0);
      if (LE == 4) ld_all();
      o_store(0);
      if (LE == 3) ld_all();
      TLS(0, 8);
      wg_wait<0>();
      reg_fence(oa[1]); reg_fence(oa[2]); reg_fence(oa[3]);
      TLP_(0);
      release(B_EAUX);
      norm(1);
      if (OS1 == 3) o_store(1);
      if (E7 && NP == 0 && SL7 && hg == 7) o_store(1);
      if (NP == 0) { norm(2); norm(3); }
      if (E7 && NP == 0 && SL7 && hg == 7) { o_store(2); o_store(3); }
      TLP_(1);
      mbar_wait_b(BAR(B_FWO), 0);
      TLP_(2);
      if (RK == 0) resid();
      if (LE == 2) ld_all();
      TLP_(3);
      out_step(WO_SLOTS & 15u, of);
      TLP_(4);
      if (NP == 1) { norm(2); norm(3); }
      if (LE == 1) ld_all();
    }
    if (OS1 == 0) o_store(1);
    mbar_wait(BAR(B_FWO + 1), 0);
    TLP_(5);
    out_step((WO_SLOTS >> 4) & 15u, of + 16);
    TLP_(6);
    const bool early = SL7 && hg == 7;
    if (OS1 == 1 && !(E7 && early)) o_store(1);
    TLP_(7);
    if (early && !E7) { o_store(2); o_store(3); }
    {
      if (DW) __nanosleep(DW);
      if (LE == 0) ld_all();
      if (OS1 == 2 && !(E7 && early)) o_store(1);
#pragma unroll
      for (int k = 0; k < NDIR; k++) {
#pragma unroll 1
        for (uint32_t it = 0; it < SPIN_MAX; it++) {
          if (!__any_sync(~0u, max(max(v[k][0].x, v[k][1].x), max(v[k][2].x, v[k][3].x)) == SENT)) break;
#pragma unroll
          for (int j = k; j < NDIR; j++) ld_o(j);
        }
        TLP_(8);
        const uint32_t a[16] = {v[k][0].x, v[k][1].x, v[k][0].y, v[k][1].y, v[k][0].z, v[k][1].z, v[k][0].w, v[k][1].w,
                                v[k][2].x, v[k][3].x, v[k][2].y, v[k][3].y, v[k][2].z, v[k][3].z, v[k][2].w, v[k][3].w};
        mbar_wait(BAR(B_FWO + 2 + k), 0);
        TLS(0, 34 + k);
        out_step((WO_SLOTS >> (8 + 4 * k)) & 15u, a);
        TLP_(9);
        if (k) { wg_wait<1>(); release2(B_EO); }
      }
      if (!early) o_store(2);
    }
    auto routed = [&]() {
      mbar_wait(BAR(B_MOE), 0);
      const float2 kk = lds_f2(sb + MISC + M_IDX + t * 8);
      const int k0 = (int)(~__float_as_uint(kk.x) & 2047u) - tb * 128, k1 = (int)(~__float_as_uint(kk.y) & 2047u) - tb * 128;
      if (NUNIT && __any_sync(~0u, (k0 >> 6) == w || (k1 >> 6) == w)) {
        const uint32_t a0 = (k0 == row0 ? 0x3F80u : 0u) | (k1 == row0 ? 0x3F800000u : 0u);
        const uint32_t a1 = (k0 == row0 + 8 ? 0x3F80u : 0u) | (k1 == row0 + 8 ? 0x3F800000u : 0u);
        wg_fence();
        wgmma_rs_n128<1>(ao, a0, a1, 0u, 0u, mkdesc((d0 + ((MISC + M_MOE) >> 4)) | (64u << 16), 0x40000000u));
        wg_commit();
      }
    };
    auto out_half = [&](int h, const float* v) {
      const uint32_t ost = sb + (w ? S_D1 : S_D0) * SLOT + wq * 4096 + h * 2048;
#pragma unroll
      for (int j = 0; j < 8; j += 2)
        stsm4(ost + ((moff & 2047) ^ (j << 4)), pack_bf16(v[4 * j], v[4 * j + 1]), pack_bf16(v[4 * j + 2], v[4 * j + 3]),
              pack_bf16(v[4 * j + 4], v[4 * j + 5]), pack_bf16(v[4 * j + 6], v[4 * j + 7]));
      fence_async_smem();
      __syncwarp();
      if (elect_one()) {
        asm volatile("cp.async.bulk.tensor.2d.global.shared::cta.bulk_group [%0, {%2, %3}], [%1];" ::"l"(&tmOut), "r"(ost), "r"(hg * 128 + h * 64), "r"(tb * 128 + warp * 16) : "memory");
        if (h) asm volatile("cp.async.bulk.commit_group;\ncp.async.bulk.wait_group.read 0;" ::: "memory");
      }
      __syncwarp();
    };
    bool done = false;
    {
      const uint32_t dO = (d0 + w * 256) | (1u << 16);
      auto step = [&](int i, int r, int p, uint32_t as, uint32_t ws) {
        mbar_wait(BAR(B_FWO + i), 0);
        mbar_wait(BAR(B_VAL + r), p);
        TLS(0, 32 + i);
        const uint32_t da = dO + as * 1024, db = dW + ws * 1024;
        wg_fence();
#pragma unroll
        for (int kk = 0; kk < 4; kk++)
          wgmma_ss_n128<0, 1>(ao, mkdesc(da + (kk >> 1) * 512 + (kk & 1) * 2, HI_SW64), mkdesc(db + (kk >> 1) * 512 + (kk & 1) * 128, HI_SW128));
        wg_commit();
      };
      uint64_t tbl = WO_SLOTS >> (4 * I0);
      int r = 0, p = 0, rp = 0;
#pragma unroll 1
      for (int i = I0; i < 12; i++) {
        step(i, r, p, (A_SLOTS >> (4 * r)) & 15u, (uint32_t)tbl & 15u);
        tbl >>= 4;
#pragma unroll
        for (int c = 0; c < 2; c++)
          if (i == OS3 + c && !early) stx4(mine + 3 * 4096 + c * 32, of[24 + c], of[26 + c], of[28 + c], of[30 + c]);
        wg_wait<1>();
        if (i > I0) release(B_EA + rp);
        rp = r;
        if (++r == NA) { r = 0; p ^= 1; }
        if (i >= 3 && i <= 9) release2(B_EO + i - 3);
      }
      if (SPL && w == 1) {
        float bl[32], bh[32];
        mbar_wait(BAR(B_GO), 0);
        routed();
#pragma unroll
        for (int h = 0; h < 2; h++) {
#pragma unroll
          for (int i = 12; i < 16; i++) {
            const int r_ = (i - I0) % NA;
            if (h == 0) { mbar_wait(BAR(B_FWO + i), 0); mbar_wait(BAR(B_VAL + r_), ((i - I0) / NA) & 1); }
            const uint32_t da = dO + ((A_SLOTS >> (4 * r_)) & 15u) * 1024, db = dW + ((uint32_t)(WO_SLOTS >> (4 * i)) & 15u) * 1024 + h * 256;
            if (h == 0 || i == 12) wg_fence();
#pragma unroll
            for (int kk = 0; kk < 4; kk++) {
              const uint64_t a = mkdesc(da + (kk >> 1) * 512 + (kk & 1) * 2, HI_SW64), bb = mkdesc(db + (kk >> 1) * 512 + (kk & 1) * 128, HI_SW128);
              if (i == 12 && kk == 0) wgmma_sz_n64<0, 1>(h ? bh : bl, a, bb); else wgmma_ss_n64<0, 1>(h ? bh : bl, a, bb);
            }
          }
          wg_commit();
        }
        wg_wait<1>();
        reg_fence(ao); reg_fence(bl);
#pragma unroll
        for (int j = 0; j < 32; j++) bl[j] += ao[j];
        out_half(0, bl);
        wg_wait<0>();
        reg_fence(bh);
#pragma unroll
        for (int j = 0; j < 32; j++) bh[j] += ao[32 + j];
        out_half(1, bh);
        done = true;
      } else
#pragma unroll
      for (int i = 12; i < 16; i++) {
        if (i == 16 - STAG && w == 1) mbar_wait(BAR(B_GO), 0);
        step(i, (i - I0) % NA, ((i - I0) / NA) & 1, (A_SLOTS >> (4 * ((i - I0) % NA))) & 15u, (uint32_t)(WO_SLOTS >> (4 * i)) & 15u);
        if (STAG && i == 15 - GOE && tid == 0) mbar_arrive(BAR(B_GO));
      }
    }
    if (!done) {
      routed();
      wg_wait<0>();
      reg_fence(ao);
      TLS(0, 10);
      out_half(0, ao);
      out_half(1, ao + 32);
    }
    TLS(0, 11);
    TLS(128, 9);
  }
}

typedef CUresult (*EncFn)(CUtensorMap*, CUtensorMapDataType, cuuint32_t, void*, const cuuint64_t*, const cuuint64_t*, const cuuint32_t*,
                          const cuuint32_t*, CUtensorMapInterleave, CUtensorMapSwizzle, CUtensorMapL2promotion, CUtensorMapFloatOOBfill);

void make_map2(EncFn enc, CUtensorMap* m, void* p, uint64_t rows, uint64_t cols, uint32_t brows, CUtensorMapL2promotion promo) {
  cuuint64_t gd[2] = {cols, rows}, gs[1] = {cols * 2};
  cuuint32_t bd[2] = {64, brows}, es[2] = {1, 1};
  enc(m, CU_TENSOR_MAP_DATA_TYPE_BFLOAT16, 2, p, gd, gs, bd, es, CU_TENSOR_MAP_INTERLEAVE_NONE, CU_TENSOR_MAP_SWIZZLE_128B, promo,
      CU_TENSOR_MAP_FLOAT_OOB_FILL_NONE);
}
void make_map3(EncFn enc, CUtensorMap* m, void* p, uint64_t rows, uint64_t cols, uint32_t brows) {
  cuuint64_t gd[3] = {64, rows, cols / 64}, gs[2] = {cols * 2, 128};
  cuuint32_t bd[3] = {64, brows, 2}, es[3] = {1, 1, 1};
  enc(m, CU_TENSOR_MAP_DATA_TYPE_BFLOAT16, 3, p, gd, gs, bd, es, CU_TENSOR_MAP_INTERLEAVE_NONE, CU_TENSOR_MAP_SWIZZLE_128B,
      CU_TENSOR_MAP_L2_PROMOTION_L2_256B, CU_TENSOR_MAP_FLOAT_OOB_FILL_NONE);
}

}

extern "C" void kernel_launch(void* const* d_in, const int* in_sizes, int n_in, void* d_out, int out_size) {
  static EncFn enc = nullptr;
  static int by_sm = 0;
  if (!enc) {
    void* fn = nullptr;
    cudaDriverEntryPointQueryResult qr;
    cudaGetDriverEntryPoint("cuTensorMapEncodeTiled", &fn, cudaEnableDefault, &qr);
    enc = (EncFn)fn;
    int dev = 0, sms = 0;
    cudaGetDevice(&dev);
    cudaDeviceGetAttribute(&sms, cudaDevAttrMultiProcessorCount, dev);
    by_sm = MAP == 2 && sms == NCTA + NSVC;
    cudaFuncSetAttribute(fused_kernel, cudaFuncAttributeMaxDynamicSharedMemorySize, SMEM_BYTES);
  }
  CUtensorMap tmX, tmW, tmWo, tmOut, tmG, tmU, tmD, tmR, tmWp;
  {
    cuuint64_t gd[5] = {64, 2, 128, 4, 16}, gs[4] = {2048, 16384, 4096, 128};
    cuuint32_t bd[5] = {64, 2, 4, 4, 2}, es[5] = {1, 1, 1, 1, 1};
    enc(&tmWp, CU_TENSOR_MAP_DATA_TYPE_BFLOAT16, 5, d_in[2], gd, gs, bd, es, CU_TENSOR_MAP_INTERLEAVE_NONE, CU_TENSOR_MAP_SWIZZLE_128B,
        CU_TENSOR_MAP_L2_PROMOTION_L2_256B, CU_TENSOR_MAP_FLOAT_OOB_FILL_NONE);
  }
  make_map2(enc, &tmR, d_in[0], SEQ, DM, 1, CU_TENSOR_MAP_L2_PROMOTION_L2_128B);
  make_map2(enc, &tmX, d_in[0], SEQ, DM, 128, XPROMO);
  make_map3(enc, &tmW, d_in[1], DM, 3 * DM, 64);
  make_map3(enc, &tmWo, d_in[2], DM, DM, 32);
  if (OUTV) make_map2(enc, &tmOut, d_out, SEQ, DM, 16, CU_TENSOR_MAP_L2_PROMOTION_L2_128B); else make_map3(enc, &tmOut, d_out, SEQ, DM, 64);
  make_map2(enc, &tmG, d_in[5], DM, FF, 64, MPROMO);
  make_map2(enc, &tmU, d_in[6], DM, FF, 64, MPROMO);
  make_map2(enc, &tmD, d_in[7], FF, DM, 64, MPROMO);
  typedef const __nv_bfloat16* P;
  cudaLaunchConfig_t cfg = {};
  cfg.gridDim = dim3(NCTA + NSVC); cfg.blockDim = dim3(512); cfg.dynamicSmemBytes = SMEM_BYTES; cfg.stream = cudaStreamPerThread;
  cudaLaunchAttribute at[1];
  at[0].id = cudaLaunchAttributeClusterDimension;
  at[0].val.clusterDim.x = 2; at[0].val.clusterDim.y = 1; at[0].val.clusterDim.z = 1;
  cfg.attrs = at; cfg.numAttrs = 1;
  cudaLaunchKernelEx(&cfg, fused_kernel, (P)d_in[0], (P)d_in[1], (P)d_in[2], (P)d_in[4], (P)d_in[7], by_sm, tmX, tmW, tmWo, tmOut, tmG, tmU, tmD, tmR, tmWp);
}
```

```cpp
#include <cuda_runtime.h>
#include <cuda.h>
#include <cuda_bf16.h>
#include <stdint.h>

namespace {

template <int TA, int TB> __device__ __forceinline__ void wgmma_ss_n128(float (&d)[64], uint64_t da, uint64_t db) {
  asm volatile("wgmma.mma_async.sync.aligned.m64n128k16.f32.bf16.bf16 "
  "{%0,%1,%2,%3,%4,%5,%6,%7,%8,%9,%10,%11,%12,%13,%14,%15,%16,%17,%18,%19,%20,%21,%22,%23,%24,%25,%26,%27,%28,%29,%30,%31,%32,%33,%34,%35,%36,%37,%38,%39,%40,%41,%42,%43,%44,%45,%46,%47,%48,%49,%50,%51,%52,%53,%54,%55,%56,%57,%58,%59,%60,%61,%62,%63}, "
  "%64, %65, 1, 1, 1, %66, %67;"
  : "+f"(d[0]),"+f"(d[1]),"+f"(d[2]),"+f"(d[3]),"+f"(d[4]),"+f"(d[5]),"+f"(d[6]),"+f"(d[7]),"+f"(d[8]),"+f"(d[9]),"+f"(d[10]),"+f"(d[11]),"+f"(d[12]),"+f"(d[13]),"+f"(d[14]),"+f"(d[15]),"+f"(d[16]),"+f"(d[17]),"+f"(d[18]),"+f"(d[19]),"+f"(d[20]),"+f"(d[21]),"+f"(d[22]),"+f"(d[23]),"+f"(d[24]),"+f"(d[25]),"+f"(d[26]),"+f"(d[27]),"+f"(d[28]),"+f"(d[29]),"+f"(d[30]),"+f"(d[31]),"+f"(d[32]),"+f"(d[33]),"+f"(d[34]),"+f"(d[35]),"+f"(d[36]),"+f"(d[37]),"+f"(d[38]),"+f"(d[39]),"+f"(d[40]),"+f"(d[41]),"+f"(d[42]),"+f"(d[43]),"+f"(d[44]),"+f"(d[45]),"+f"(d[46]),"+f"(d[47]),"+f"(d[48]),"+f"(d[49]),"+f"(d[50]),"+f"(d[51]),"+f"(d[52]),"+f"(d[53]),"+f"(d[54]),"+f"(d[55]),"+f"(d[56]),"+f"(d[57]),"+f"(d[58]),"+f"(d[59]),"+f"(d[60]),"+f"(d[61]),"+f"(d[62]),"+f"(d[63])
  : "l"(da), "l"(db), "n"(TA), "n"(TB));
}
template <int TA, int TB> __device__ __forceinline__ void wgmma_ss_n64(float (&d)[32], uint64_t da, uint64_t db) {
  asm volatile("wgmma.mma_async.sync.aligned.m64n64k16.f32.bf16.bf16 "
  "{%0,%1,%2,%3,%4,%5,%6,%7,%8,%9,%10,%11,%12,%13,%14,%15,%16,%17,%18,%19,%20,%21,%22,%23,%24,%25,%26,%27,%28,%29,%30,%31}, "
  "%32, %33, 1, 1, 1, %34, %35;"
  : "+f"(d[0]),"+f"(d[1]),"+f"(d[2]),"+f"(d[3]),"+f"(d[4]),"+f"(d[5]),"+f"(d[6]),"+f"(d[7]),"+f"(d[8]),"+f"(d[9]),"+f"(d[10]),"+f"(d[11]),"+f"(d[12]),"+f"(d[13]),"+f"(d[14]),"+f"(d[15]),"+f"(d[16]),"+f"(d[17]),"+f"(d[18]),"+f"(d[19]),"+f"(d[20]),"+f"(d[21]),"+f"(d[22]),"+f"(d[23]),"+f"(d[24]),"+f"(d[25]),"+f"(d[26]),"+f"(d[27]),"+f"(d[28]),"+f"(d[29]),"+f"(d[30]),"+f"(d[31])
  : "l"(da), "l"(db), "n"(TA), "n"(TB));
}
template <int TA, int TB> __device__ __forceinline__ void wgmma_sz_n64(float (&d)[32], uint64_t da, uint64_t db) {
  asm volatile("wgmma.mma_async.sync.aligned.m64n64k16.f32.bf16.bf16 "
  "{%0,%1,%2,%3,%4,%5,%6,%7,%8,%9,%10,%11,%12,%13,%14,%15,%16,%17,%18,%19,%20,%21,%22,%23,%24,%25,%26,%27,%28,%29,%30,%31}, "
  "%32, %33, 0, 1, 1, %34, %35;"
  : "=f"(d[0]),"=f"(d[1]),"=f"(d[2]),"=f"(d[3]),"=f"(d[4]),"=f"(d[5]),"=f"(d[6]),"=f"(d[7]),"=f"(d[8]),"=f"(d[9]),"=f"(d[10]),"=f"(d[11]),"=f"(d[12]),"=f"(d[13]),"=f"(d[14]),"=f"(d[15]),"=f"(d[16]),"=f"(d[17]),"=f"(d[18]),"=f"(d[19]),"=f"(d[20]),"=f"(d[21]),"=f"(d[22]),"=f"(d[23]),"=f"(d[24]),"=f"(d[25]),"=f"(d[26]),"=f"(d[27]),"=f"(d[28]),"=f"(d[29]),"=f"(d[30]),"=f"(d[31])
  : "l"(da), "l"(db), "n"(TA), "n"(TB));
}
template <int TB> __device__ __forceinline__ void wgmma_rs_n72(float (&d)[36], uint32_t a0, uint32_t a1, uint32_t a2, uint32_t a3, uint64_t db) {
  asm volatile("wgmma.mma_async.sync.aligned.m64n72k16.f32.bf16.bf16 "
  "{%0,%1,%2,%3,%4,%5,%6,%7,%8,%9,%10,%11,%12,%13,%14,%15,%16,%17,%18,%19,%20,%21,%22,%23,%24,%25,%26,%27,%28,%29,%30,%31,%32,%33,%34,%35}, "
  "{%36,%37,%38,%39}, %40, 1, 1, 1, %41;"
  : "+f"(d[0]),"+f"(d[1]),"+f"(d[2]),"+f"(d[3]),"+f"(d[4]),"+f"(d[5]),"+f"(d[6]),"+f"(d[7]),"+f"(d[8]),"+f"(d[9]),"+f"(d[10]),"+f"(d[11]),"+f"(d[12]),"+f"(d[13]),"+f"(d[14]),"+f"(d[15]),"+f"(d[16]),"+f"(d[17]),"+f"(d[18]),"+f"(d[19]),"+f"(d[20]),"+f"(d[21]),"+f"(d[22]),"+f"(d[23]),"+f"(d[24]),"+f"(d[25]),"+f"(d[26]),"+f"(d[27]),"+f"(d[28]),"+f"(d[29]),"+f"(d[30]),"+f"(d[31]),"+f"(d[32]),"+f"(d[33]),"+f"(d[34]),"+f"(d[35])
  : "r"(a0), "r"(a1), "r"(a2), "r"(a3), "l"(db), "n"(TB));
}
template <int TB> __device__ __forceinline__ void wgmma_rz_n72(float (&d)[36], uint32_t a0, uint32_t a1, uint32_t a2, uint32_t a3, uint64_t db) {
  asm volatile("wgmma.mma_async.sync.aligned.m64n72k16.f32.bf16.bf16 "
  "{%0,%1,%2,%3,%4,%5,%6,%7,%8,%9,%10,%11,%12,%13,%14,%15,%16,%17,%18,%19,%20,%21,%22,%23,%24,%25,%26,%27,%28,%29,%30,%31,%32,%33,%34,%35}, "
  "{%36,%37,%38,%39}, %40, 0, 1, 1, %41;"
  : "=f"(d[0]),"=f"(d[1]),"=f"(d[2]),"=f"(d[3]),"=f"(d[4]),"=f"(d[5]),"=f"(d[6]),"=f"(d[7]),"=f"(d[8]),"=f"(d[9]),"=f"(d[10]),"=f"(d[11]),"=f"(d[12]),"=f"(d[13]),"=f"(d[14]),"=f"(d[15]),"=f"(d[16]),"=f"(d[17]),"=f"(d[18]),"=f"(d[19]),"=f"(d[20]),"=f"(d[21]),"=f"(d[22]),"=f"(d[23]),"=f"(d[24]),"=f"(d[25]),"=f"(d[26]),"=f"(d[27]),"=f"(d[28]),"=f"(d[29]),"=f"(d[30]),"=f"(d[31]),"=f"(d[32]),"=f"(d[33]),"=f"(d[34]),"=f"(d[35])
  : "r"(a0), "r"(a1), "r"(a2), "r"(a3), "l"(db), "n"(TB));
}
template <int TB> __device__ __forceinline__ void wgmma_rs_n40(float (&d)[20], uint32_t a0, uint32_t a1, uint32_t a2, uint32_t a3, uint64_t db) {
  asm volatile("wgmma.mma_async.sync.aligned.m64n40k16.f32.bf16.bf16 "
  "{%0,%1,%2,%3,%4,%5,%6,%7,%8,%9,%10,%11,%12,%13,%14,%15,%16,%17,%18,%19}, "
  "{%20,%21,%22,%23}, %24, 1, 1, 1, %25;"
  : "+f"(d[0]),"+f"(d[1]),"+f"(d[2]),"+f"(d[3]),"+f"(d[4]),"+f"(d[5]),"+f"(d[6]),"+f"(d[7]),"+f"(d[8]),"+f"(d[9]),"+f"(d[10]),"+f"(d[11]),"+f"(d[12]),"+f"(d[13]),"+f"(d[14]),"+f"(d[15]),"+f"(d[16]),"+f"(d[17]),"+f"(d[18]),"+f"(d[19])
  : "r"(a0), "r"(a1), "r"(a2), "r"(a3), "l"(db), "n"(TB));
}
template <int TB> __device__ __forceinline__ void wgmma_rz_n40(float (&d)[20], uint32_t a0, uint32_t a1, uint32_t a2, uint32_t a3, uint64_t db) {
  asm volatile("wgmma.mma_async.sync.aligned.m64n40k16.f32.bf16.bf16 "
  "{%0,%1,%2,%3,%4,%5,%6,%7,%8,%9,%10,%11,%12,%13,%14,%15,%16,%17,%18,%19}, "
  "{%20,%21,%22,%23}, %24, 0, 1, 1, %25;"
  : "=f"(d[0]),"=f"(d[1]),"=f"(d[2]),"=f"(d[3]),"=f"(d[4]),"=f"(d[5]),"=f"(d[6]),"=f"(d[7]),"=f"(d[8]),"=f"(d[9]),"=f"(d[10]),"=f"(d[11]),"=f"(d[12]),"=f"(d[13]),"=f"(d[14]),"=f"(d[15]),"=f"(d[16]),"=f"(d[17]),"=f"(d[18]),"=f"(d[19])
  : "r"(a0), "r"(a1), "r"(a2), "r"(a3), "l"(db), "n"(TB));
}
template <int TB> __device__ __forceinline__ void wgmma_rs_n128(float (&d)[64], uint32_t a0, uint32_t a1, uint32_t a2, uint32_t a3, uint64_t db) {
  asm volatile("wgmma.mma_async.sync.aligned.m64n128k16.f32.bf16.bf16 "
  "{%0,%1,%2,%3,%4,%5,%6,%7,%8,%9,%10,%11,%12,%13,%14,%15,%16,%17,%18,%19,%20,%21,%22,%23,%24,%25,%26,%27,%28,%29,%30,%31,%32,%33,%34,%35,%36,%37,%38,%39,%40,%41,%42,%43,%44,%45,%46,%47,%48,%49,%50,%51,%52,%53,%54,%55,%56,%57,%58,%59,%60,%61,%62,%63}, "
  "{%64,%65,%66,%67}, %68, 1, 1, 1, %69;"
  : "+f"(d[0]),"+f"(d[1]),"+f"(d[2]),"+f"(d[3]),"+f"(d[4]),"+f"(d[5]),"+f"(d[6]),"+f"(d[7]),"+f"(d[8]),"+f"(d[9]),"+f"(d[10]),"+f"(d[11]),"+f"(d[12]),"+f"(d[13]),"+f"(d[14]),"+f"(d[15]),"+f"(d[16]),"+f"(d[17]),"+f"(d[18]),"+f"(d[19]),"+f"(d[20]),"+f"(d[21]),"+f"(d[22]),"+f"(d[23]),"+f"(d[24]),"+f"(d[25]),"+f"(d[26]),"+f"(d[27]),"+f"(d[28]),"+f"(d[29]),"+f"(d[30]),"+f"(d[31]),"+f"(d[32]),"+f"(d[33]),"+f"(d[34]),"+f"(d[35]),"+f"(d[36]),"+f"(d[37]),"+f"(d[38]),"+f"(d[39]),"+f"(d[40]),"+f"(d[41]),"+f"(d[42]),"+f"(d[43]),"+f"(d[44]),"+f"(d[45]),"+f"(d[46]),"+f"(d[47]),"+f"(d[48]),"+f"(d[49]),"+f"(d[50]),"+f"(d[51]),"+f"(d[52]),"+f"(d[53]),"+f"(d[54]),"+f"(d[55]),"+f"(d[56]),"+f"(d[57]),"+f"(d[58]),"+f"(d[59]),"+f"(d[60]),"+f"(d[61]),"+f"(d[62]),"+f"(d[63])
  : "r"(a0), "r"(a1), "r"(a2), "r"(a3), "l"(db), "n"(TB));
}
template <int TA, int TB> __device__ __forceinline__ void wgmma_ss_n8(float (&d)[4], uint64_t da, uint64_t db) {
  asm volatile("wgmma.mma_async.sync.aligned.m64n8k16.f32.bf16.bf16 "
  "{%0,%1,%2,%3}, "
  "%4, %5, 1, 1, 1, %6, %7;"
  : "+f"(d[0]),"+f"(d[1]),"+f"(d[2]),"+f"(d[3])
  : "l"(da), "l"(db), "n"(TA), "n"(TB));
}
template <int TA, int TB> __device__ __forceinline__ void wgmma_ss_n16(float (&d)[8], uint64_t da, uint64_t db) {
  asm volatile("wgmma.mma_async.sync.aligned.m64n16k16.f32.bf16.bf16 "
  "{%0,%1,%2,%3,%4,%5,%6,%7}, "
  "%8, %9, 1, 1, 1, %10, %11;"
  : "+f"(d[0]),"+f"(d[1]),"+f"(d[2]),"+f"(d[3]),"+f"(d[4]),"+f"(d[5]),"+f"(d[6]),"+f"(d[7])
  : "l"(da), "l"(db), "n"(TA), "n"(TB));
}

constexpr int SEQ = 2048, DM = 1024, FF = 3584;
constexpr int NCTA = 128, NSVC = 4;
constexpr int NUNIT = 112;
constexpr uint32_t SLOT = 16384;
constexpr uint32_t MISC = 14 * SLOT;
constexpr uint32_t SMEM_BYTES = MISC + 3072;
constexpr uint32_t M_MOE = 0;
constexpr uint32_t M_BAR = 2048;
constexpr uint32_t M_DUM = 2048 + 1020;
constexpr uint32_t M_IDX = 2048 + 768;
constexpr uint32_t M_KEY = 2048 + 960;
#define R5 1
#define NQ (R5 ? 6 : 5)
constexpr int NF = 16 - NQ, NR = (NQ == 5 || R5) ? 4 : 3;
constexpr int B_FXQ = 0, B_FKV = 3, B_AST = 6, B_MOE = 7, B_MF = 8  , B_CQ = 12, B_XS = 13, B_DF = 14, B_ZOK = 15, B_FWO = 21  , B_FQ = B_FWO - NQ,
              B_UP = 37, B_FIN = 38, B_KVB = 39, B_ME = 40  , B_HF = 44, B_AF = 45  , B_AR = 50  , B_GO = 52,
              B_FAUX = 53, B_EAUX = 54, B_T0 = 55, B_DE = 56, B_EA = 57  , B_VAL = 62  ,
              B_E = 67  , B_STG = 70, B_EQ = 71  , B_EO = 76  , NBAR = 83, B_KV4 = 83, B_MS = 84,
              B_FV = 85  , B_EK = 88  , B_GQ = 91;
constexpr uint32_t MT = 9216, A_ONES = 12 * SLOT + 3 * MT, A_CS = A_ONES + 2048, A_ST = A_CS + 1536;
constexpr uint32_t A_TL = MISC + 2048 + 808;
constexpr int S_V0 = R5 ? 7 : 11, S_V1 = R5 ? 9 : 7;
constexpr uint32_t K_SLOTS = 0x8697A8u, V_SLOTS = 0x97A869u;
constexpr int C_B = 0, C_DONE = 32, NCNT = 2;
constexpr uint32_t QX_SLOTS = NQ == 5 ? 0x43102u : 0x354021u;
constexpr uint32_t QW_SLOTS = R5 ? 0xA9786Au : 0xB76A98u;
constexpr uint32_t qx(int k) { return (QX_SLOTS >> (4 * k)) & 15u; }
constexpr uint32_t qw(int k) { return (QW_SLOTS >> (4 * k)) & 15u; }
constexpr uint32_t S_KVB = R5 ? 1 : 8, S_D0 = R5 ? 11 : (NQ == 5 ? 5 : 1), S_D1 = R5 ? 2 : (NQ == 5 ? 11 : 2);
constexpr uint32_t S_M3 = R5 ? 11 : 5;
constexpr int WQ0 = NQ == 5 ? 1 : 3;
constexpr uint32_t wo_slot_c(int i) { return i >= 9 ? wo_slot_c(i - 9) : (i == 7 ? S_D0 : (i == 8 ? S_D1 : (((i & 1) || i + WQ0 == 1) ? qx((i + WQ0) >> 1) : qw((i + WQ0) >> 1)))); }
constexpr uint64_t wo_slots() { uint64_t t = 0; for (int i = 0; i < 16; i++) t |= (uint64_t)wo_slot_c(i) << (4 * i); return t; }
constexpr uint64_t WO_SLOTS = wo_slots();
constexpr uint32_t A_SLOTS = 0xDC000u | (S_KVB << 8) | (qw(NQ - 1) << 4) | qx(NQ - 1);
constexpr uint32_t SX14 = qx(NQ - 2), SX15 = qx(NQ - 1), SXQ0 = qx(0);
#define WOD 2
#define PLC 3
#define PFG1 10
#define PFNS1 150
#define PFG0 3
#define RS0 0
#define WPF 1
#define POLLNS 150
#define SVNS 100
#define MPROMO CU_TENSOR_MAP_L2_PROMOTION_L2_128B
#define MW0 0
#define PFILL 0
#define H2W (NQ - 3)
#define TOPW 1000
#define PFT 0
#define SV0 2
#define SV0A 14
#define SV0B 22
#define ASTE 2
#define PFS 1
#define PFTAB 0x0012222220000ull
#define HW 0
#define DPF 1
#define PROBE 0x8
#define OS1 0
#define YW 0
#define OS2 3
#define NOVAL 0
#define NDIR 1
#define I0 (2 + NDIR)
#define DW 0
#define OSP 1
#define NA 5
#define STAG 4
#define GOE 0
#define SVP 99
#define KEY1 0
#define HYB 0
#define DV 0
#define DVJ 4
#define DVK 10
#define FW 0
#define E1E 0
#define GATE 0
#define SVD 0
#define XPROMO CU_TENSOR_MAP_L2_PROMOTION_L2_128B
#define MC0 3
#define MX 0
#define OUTV 1
#define BW0 2
#define QL 1
#define NP 0
#define FINCP 0
#define DNS 0
#define WOK 99
#define WOD1 2
#define SVT 64
#define MRED 1
#define MRW -1
#define SQ 2
#define H2D 400
#define MRD 300
#define STP 0
#define TPNS 50
#define DLP 0
#define MFIN 0
#define MFD 300
#define SF 1
#define PH MFIN
#define RSL 0
#define PFW 3000
#define KVE 1
#define P2NS 0
#define OS3 4
#define PLP 2
#define FINJ 9
#define PFD 0
#define PFG 3
#define PFNS2 150
#define PFNS 250
#define MAP 2
#define RSNS 60
#define SVS 6
#define PRODLATE 0
#define MC 7
#define QE 0
#define TMP 1
#define TMPW 4
#define DS 14
#define RL 0
#define EV 0
#define LQ 0
#define SPL 0
#define HALFST 0
#define PHI2 1
#define E7 1
#define RF 1
#define RK 0
#define LE 0
#define SL7 0
#define XP 3
#define VR 4
#define KEEP 1
#define KP 4
#define KC 1
#define MS 0
constexpr int CON_REGS = 224, MOE_REGS = 40, PROD_REGS = 24;
constexpr uint32_t SPIN_MAX = 2000000;
constexpr uint32_t SENT = 0xFFFFFFFFu;

struct __align__(128) Scratch {
  uint4 o[NCTA * 2048];
  uint4 part[NCTA * 544];
  uint4 fin[8 * 640];
  float2 stats[SEQ];
  uint32_t key[SEQ];
  uint32_t cs[3 * DM];
  uint4 y[NCTA * 128];
  uint32_t h[56 * 256];
  uint32_t top[128];
  uint32_t cnt[NCNT * 32];
};
__device__ Scratch G;
#define TLS(th, i)
#define TLP_(i)
#define TLG(i)
#define TLDUMP()

__device__ __forceinline__ bool elect_one() {
  uint32_t p;
  asm volatile("{\n.reg .pred P;\nelect.sync _|P, 0xffffffff;\nselp.b32 %0, 1, 0, P;\n}" : "=r"(p));
  return p;
}
__device__ __forceinline__ void mbar_init(uint32_t b, uint32_t c) { asm volatile("mbarrier.init.shared::cta.b64 [%0], %1;" ::"r"(b), "r"(c) : "memory"); }
__device__ __forceinline__ void mbar_expect_tx(uint32_t b, uint32_t bytes) { asm volatile("mbarrier.arrive.expect_tx.shared::cta.b64 _, [%0], %1;" ::"r"(b), "r"(bytes) : "memory"); }
__device__ __forceinline__ void mbar_arrive(uint32_t b) { asm volatile("mbarrier.arrive.shared::cta.b64 _, [%0];" ::"r"(b) : "memory"); }
__device__ __forceinline__ void mbar_wait_b(uint32_t b, uint32_t parity) {
  asm volatile(
      "{\n.reg .pred p;\n.reg .u32 cnt;\nmov.u32 cnt, 0;\n"
      "LW:\nmbarrier.try_wait.parity.shared::cta.b64 p, [%0], %1;\n@p bra LD;\n"
      "add.u32 cnt, cnt, 1;\nsetp.lt.u32 p, cnt, 4000000;\n@p bra LW;\ntrap;\nLD:\n}" ::"r"(b), "r"(parity) : "memory");
}
__device__ __forceinline__ void mbar_wait(uint32_t b, uint32_t parity) {
  asm volatile("{\n.reg .pred p;\nLW:\nmbarrier.try_wait.parity.shared::cta.b64 p, [%0], %1;\n@!p bra LW;\n}" ::"r"(b), "r"(parity) : "memory");
}
__device__ __forceinline__ bool mbar_test(uint32_t b, uint32_t parity) {
  uint32_t r;
  asm volatile("{\n.reg .pred p;\nmbarrier.test_wait.parity.shared::cta.b64 p, [%1], %2;\nselp.b32 %0, 1, 0, p;\n}" : "=r"(r) : "r"(b), "r"(parity) : "memory");
  return r;
}
__device__ __forceinline__ uint32_t ev_arrive(uint32_t a) { uint32_t r; asm volatile("atom.shared.add.u32 %0, [%1], 1;" : "=r"(r) : "r"(a) : "memory"); return r; }
__device__ __forceinline__ void tma2d(uint32_t dst, const CUtensorMap* m, int c0, int c1, uint32_t bar) {
  asm volatile("cp.async.bulk.tensor.2d.shared::cluster.global.mbarrier::complete_tx::bytes [%0], [%1, {%3, %4}], [%2];" ::"r"(dst), "l"(m), "r"(bar), "r"(c0), "r"(c1) : "memory");
}
__device__ __forceinline__ void tma3d(uint32_t dst, const CUtensorMap* m, int c1, int c2, uint32_t bar) {
  asm volatile("cp.async.bulk.tensor.3d.shared::cluster.global.mbarrier::complete_tx::bytes [%0], [%1, {%3, %4, %5}], [%2];" ::"r"(dst), "l"(m), "r"(bar), "r"(0), "r"(c1), "r"(c2) : "memory");
}
__device__ __forceinline__ void tma3d_mc(uint32_t dst, const CUtensorMap* m, int c1, int c2, uint32_t bar) {
  asm volatile("cp.async.bulk.tensor.3d.shared::cluster.global.mbarrier::complete_tx::bytes.multicast::cluster [%0], [%1, {%3, %4, %5}], [%2], %6;" ::"r"(dst), "l"(m), "r"(bar), "r"(0), "r"(c1), "r"(c2), "h"((uint16_t)3) : "memory");
}
__device__ __forceinline__ void tma5d(uint32_t dst, const CUtensorMap* m, int c2, int c4, uint32_t bar, bool mc) {
  if (mc) asm volatile("cp.async.bulk.tensor.5d.shared::cluster.global.mbarrier::complete_tx::bytes.multicast::cluster [%0], [%1, {%3, %3, %4, %3, %5}], [%2], %6;" ::"r"(dst), "l"(m), "r"(bar), "r"(0), "r"(c2), "r"(c4), "h"((uint16_t)3) : "memory");
  else asm volatile("cp.async.bulk.tensor.5d.shared::cluster.global.mbarrier::complete_tx::bytes [%0], [%1, {%3, %3, %4, %3, %5}], [%2];" ::"r"(dst), "l"(m), "r"(bar), "r"(0), "r"(c2), "r"(c4) : "memory");
}
__device__ __forceinline__ void mbar_arrive_cta(uint32_t b, uint32_t cta) {
  asm volatile("{\n.reg .b32 ra;\nmapa.shared::cluster.u32 ra, %0, %1;\nmbarrier.arrive.shared::cluster.b64 _, [ra];\n}" ::"r"(b), "r"(cta) : "memory");
}
constexpr uint64_t POL_FIRST = 0x12F0000000000000ull;
__device__ __forceinline__ void tma2d_ef(uint32_t dst, const CUtensorMap* m, int c0, int c1, uint32_t bar) {
  asm volatile("cp.async.bulk.tensor.2d.shared::cluster.global.mbarrier::complete_tx::bytes.L2::cache_hint [%0], [%1, {%3, %4}], [%2], %5;" ::"r"(dst), "l"(m), "r"(bar), "r"(c0), "r"(c1), "l"(POL_FIRST) : "memory");
}
__device__ __forceinline__ void bulk_ld(uint32_t dst, const void* src, uint32_t bytes, uint32_t bar) {
  asm volatile("cp.async.bulk.shared::cluster.global.mbarrier::complete_tx::bytes [%0], [%1], %2, [%3];" ::"r"(dst), "l"(src), "r"(bytes), "r"(bar) : "memory");
}
__device__ __forceinline__ void bulk_pf(const void* src, uint32_t bytes) { asm volatile("cp.async.bulk.prefetch.L2.global [%0], %1;" ::"l"(src), "r"(bytes) : "memory"); }
__device__ __forceinline__ void tma2d_pf(const CUtensorMap* m, int c0, int c1) {
  asm volatile("cp.async.bulk.prefetch.tensor.2d.L2.global [%0, {%1, %2}];" ::"l"(m), "r"(c0), "r"(c1) : "memory");
}
__device__ __forceinline__ void map_pf(const CUtensorMap* m) { asm volatile("prefetch.tensormap [%0];" ::"l"(m) : "memory"); }
__device__ __forceinline__ void line_pf(const void* p) { asm volatile("prefetch.global.L2 [%0];" ::"l"(p)); }
__device__ __forceinline__ void pf128(uint32_t dummy, const void* src) { asm volatile("cp.async.ca.shared.global.L2::128B [%0], [%1], 4;" ::"r"(dummy), "l"(src) : "memory"); }
__device__ __forceinline__ void pf256(uint32_t dummy, const void* src) { asm volatile("cp.async.ca.shared.global.L2::256B [%0], [%1], 4;" ::"r"(dummy), "l"(src) : "memory"); }
__device__ __forceinline__ void cp16x2(uint32_t dst, const void* src) {
  asm volatile("cp.async.cg.shared.global [%0], [%1], 16;\ncp.async.cg.shared.global [%0+4096], [%1+512], 16;" ::"r"(dst), "l"(src) : "memory");
}
constexpr uint32_t HI_SW128 = 0x40000000u | (1024 >> 4), HI_SW64 = 0x80000000u | (512 >> 4), HI_NOSW = 512 >> 4;
__device__ __forceinline__ uint64_t mkdesc(uint32_t lo, uint32_t hi) { uint64_t d; asm("mov.b64 %0, {%1, %2};" : "=l"(d) : "r"(lo), "r"(hi)); return d; }
__device__ __forceinline__ void wg_fence() { asm volatile("wgmma.fence.sync.aligned;" ::: "memory"); }
__device__ __forceinline__ void wg_commit() { asm volatile("wgmma.commit_group.sync.aligned;" ::: "memory"); }
template <int N> __device__ __forceinline__ void wg_wait() { asm volatile("wgmma.wait_group.sync.aligned %0;" ::"n"(N) : "memory"); }
template <int N> __device__ __forceinline__ void reg_fence(float (&a)[N]) {
#pragma unroll
  for (int i = 0; i < N; i++) asm volatile("" : "+f"(a[i])::"memory");
}
template <int ID, int N> __device__ __forceinline__ void bar_sync() { asm volatile("bar.sync %0, %1;" ::"n"(ID), "n"(N) : "memory"); }
__device__ __forceinline__ void fence_async_smem() { asm volatile("fence.proxy.async.shared::cta;" ::: "memory"); }
__device__ __forceinline__ void fence_async_gmem() { asm volatile("fence.proxy.async.global;" ::: "memory"); }
__device__ __forceinline__ uint32_t pack_bf16(float lo, float hi) { uint32_t r; asm("cvt.rn.bf16x2.f32 %0, %1, %2;" : "=r"(r) : "f"(hi), "f"(lo)); return r; }
__device__ __forceinline__ float bf_lo(uint32_t v) { return __uint_as_float(v << 16); }
__device__ __forceinline__ float bf_hi(uint32_t v) { return __uint_as_float(v & 0xFFFF0000u); }
__device__ __forceinline__ float bf_round(float v) { return bf_lo(pack_bf16(v, v)); }
__device__ __forceinline__ uint32_t bf_sub2(uint32_t a, uint32_t b) { uint32_t r; asm("sub.rn.bf16x2 %0, %1, %2;" : "=r"(r) : "r"(a), "r"(b)); return r; }
__device__ __forceinline__ float rcp(float v) { float r; asm("rcp.approx.ftz.f32 %0, %1;" : "=f"(r) : "f"(v)); return r; }
__device__ __forceinline__ float ex2(float v) { float r; asm("ex2.approx.ftz.f32 %0, %1;" : "=f"(r) : "f"(v)); return r; }
__device__ __forceinline__ float sigmoid(float v) { return rcp(1.f + ex2(v * -1.4426950408889634f)); }
__device__ __forceinline__ void stsm4(uint32_t a, uint32_t r0, uint32_t r1, uint32_t r2, uint32_t r3) {
  asm volatile("stmatrix.sync.aligned.m8n8.x4.shared.b16 [%0], {%1,%2,%3,%4};" ::"r"(a), "r"(r0), "r"(r1), "r"(r2), "r"(r3) : "memory");
}
__device__ __forceinline__ void stsm4t(uint32_t a, uint32_t r0, uint32_t r1, uint32_t r2, uint32_t r3) {
  asm volatile("stmatrix.sync.aligned.m8n8.x4.trans.shared.b16 [%0], {%1,%2,%3,%4};" ::"r"(a), "r"(r0), "r"(r1), "r"(r2), "r"(r3) : "memory");
}
__device__ __forceinline__ void ldsm4(uint32_t a, uint32_t& r0, uint32_t& r1, uint32_t& r2, uint32_t& r3) {
  asm volatile("ldmatrix.sync.aligned.m8n8.x4.shared.b16 {%0,%1,%2,%3}, [%4];" : "=r"(r0), "=r"(r1), "=r"(r2), "=r"(r3) : "r"(a) : "memory");
}
__device__ __forceinline__ uint32_t movmat(uint32_t a) { uint32_t d; asm volatile("movmatrix.sync.aligned.m8n8.trans.b16 %0, %1;" : "=r"(d) : "r"(a)); return d; }
__device__ __forceinline__ void sts_h(uint32_t a, float v) { asm volatile("st.shared.u16 [%0], %1;" ::"r"(a), "h"((uint16_t)pack_bf16(v, v)) : "memory"); }
__device__ __forceinline__ float2 lds_f2(uint32_t a) { float2 v; asm volatile("ld.shared.v2.f32 {%0,%1}, [%2];" : "=f"(v.x), "=f"(v.y) : "r"(a)); return v; }
__device__ __forceinline__ float lds_f(uint32_t a) { float v; asm volatile("ld.shared.f32 %0, [%1];" : "=f"(v) : "r"(a)); return v; }
__device__ __forceinline__ float4 lds_f4(uint32_t a) { float4 v; asm volatile("ld.shared.v4.f32 {%0,%1,%2,%3}, [%4];" : "=f"(v.x), "=f"(v.y), "=f"(v.z), "=f"(v.w) : "r"(a)); return v; }
__device__ __forceinline__ uint32_t lds_u(uint32_t a) { uint32_t v; asm volatile("ld.shared.u32 %0, [%1];" : "=r"(v) : "r"(a) : "memory"); return v; }
__device__ __forceinline__ uint4 lds_u4(uint32_t a) { uint4 v; asm volatile("ld.shared.v4.u32 {%0,%1,%2,%3}, [%4];" : "=r"(v.x), "=r"(v.y), "=r"(v.z), "=r"(v.w) : "r"(a) : "memory"); return v; }
__device__ __forceinline__ void sts_u(uint32_t a, uint32_t v) { asm volatile("st.shared.u32 [%0], %1;" ::"r"(a), "r"(v) : "memory"); }
__device__ __forceinline__ void sts_u4(uint32_t a, uint4 v) { asm volatile("st.shared.v4.u32 [%0], {%1,%2,%3,%4};" ::"r"(a), "r"(v.x), "r"(v.y), "r"(v.z), "r"(v.w) : "memory"); }
__device__ __forceinline__ uint4 ldx4(const void* p) { uint4 v; asm volatile("ld.relaxed.gpu.global.v4.u32 {%0,%1,%2,%3}, [%4];" : "=r"(v.x), "=r"(v.y), "=r"(v.z), "=r"(v.w) : "l"(p) : "memory"); return v; }
__device__ __forceinline__ uint2 ldx2(const void* p) { uint2 v; asm volatile("ld.relaxed.gpu.global.v2.u32 {%0,%1}, [%2];" : "=r"(v.x), "=r"(v.y) : "l"(p) : "memory"); return v; }
__device__ __forceinline__ uint32_t ldx1(const void* p) { uint32_t v; asm volatile("ld.relaxed.gpu.global.u32 %0, [%1];" : "=r"(v) : "l"(p) : "memory"); return v; }
__device__ __forceinline__ void stx4(void* p, uint32_t a, uint32_t b, uint32_t c, uint32_t d) { asm volatile("st.relaxed.gpu.global.v4.u32 [%0], {%1,%2,%3,%4};" ::"l"(p), "r"(a), "r"(b), "r"(c), "r"(d) : "memory"); }
__device__ __forceinline__ void stx2(void* p, uint32_t a, uint32_t b) { asm volatile("st.relaxed.gpu.global.v2.u32 [%0], {%1,%2};" ::"l"(p), "r"(a), "r"(b) : "memory"); }
__device__ __forceinline__ void stx1(void* p, uint32_t a) { asm volatile("st.relaxed.gpu.global.u32 [%0], %1;" ::"l"(p), "r"(a) : "memory"); }
__device__ __forceinline__ uint32_t umax4(uint4 v) { return max(max(v.x, v.y), max(v.z, v.w)); }
__device__ __forceinline__ uint32_t f2x(float f) { return min(__float_as_uint(f), 0xFFFFFFFEu); }
__device__ __forceinline__ void red4(float* p, float a, float b, float c, float d) { asm volatile("red.relaxed.gpu.global.add.v4.f32 [%0], {%1,%2,%3,%4};" ::"l"(p), "f"(a), "f"(b), "f"(c), "f"(d) : "memory"); }
__device__ __forceinline__ void cnt_arrive(int c) { asm volatile("red.release.gpu.global.add.u32 [%0], 1;" ::"l"(&G.cnt[c]) : "memory"); }
__device__ __forceinline__ void cnt_wait(int c, uint32_t target) {
#pragma unroll 1
  for (uint32_t it = 0; it < SPIN_MAX; it++) {
    uint32_t v;
    asm volatile("ld.acquire.gpu.global.u32 %0, [%1];" : "=r"(v) : "l"(&G.cnt[c]) : "memory");
    if (v >= target) break;
    __nanosleep(POLLNS);
  }
}
__device__ __forceinline__ void cnt_done() {
  uint32_t t;
  asm volatile("atom.acq_rel.gpu.global.add.u32 %0, [%1], 1;" : "=r"(t) : "l"(&G.cnt[C_DONE]) : "memory");
  if (t == NCTA + NSVC - 1) {
#pragma unroll 1
    for (int i = 0; i < NCNT; i++) G.cnt[i * 32] = 0;
  }
}
__device__ __forceinline__ float phi(float u, float rs, float rl) {
  float a = fmaf(u, rs, 1.000001f), e = ex2(u * rl), r;
  asm("add.sat.f32 %0, %1, 0f358637BD;" : "=f"(e) : "f"(e));
  asm("max.NaN.f32 %0, %1, %2;" : "=f"(r) : "f"(a), "f"(e));
  return r;
}

__device__ __forceinline__ uint32_t phi2(float u0, float rs0, float rl0, float u1, float rs1, float rl1) {
  float e0, e1;
  asm("{\n.reg .f32 t;\nabs.f32 t, %1;\nneg.f32 t, t;\nex2.approx.ftz.f32 %0, t;\n}" : "=f"(e0) : "f"(u0 * rl0));
  asm("{\n.reg .f32 t;\nabs.f32 t, %1;\nneg.f32 t, t;\nex2.approx.ftz.f32 %0, t;\n}" : "=f"(e1) : "f"(u1 * rl1));
  uint32_t e = pack_bf16(e0, e1), r;
  const uint32_t a = pack_bf16(fmaf(u0, rs0, 1.000001f), fmaf(u1, rs1, 1.000001f));
  asm("add.rn.bf16x2 %0, %0, %1;" : "+r"(e) : "r"(0x35863586u));
  asm("max.NaN.bf16x2 %0, %1, %2;" : "=r"(r) : "r"(a), "r"(e));
  return r;
}

__device__ __forceinline__ int kstep1(int e, int hg) { return e < 14 ? (e < 2 * hg ? e : e + 2) : 2 * hg + e - 14; }
__device__ __forceinline__ int slab(int n, int hg) {
  return n + (((n + 7 - hg) * 37) >> 8);
}
__host__ __device__ constexpr uint32_t d_off(int i) { return i < 3 ? 12 * SLOT + (NR == 4 ? i : (i == 2 ? 0 : i + 1)) * MT : (i < 5 ? S_D0 * SLOT + (i - 3) * 8192 : S_D1 * SLOT + (i - 5) * 8192); }
__host__ __device__ constexpr uint32_t h_off(int i) { return i < 3 ? 12 * SLOT + i * MT + 8192 : (i < 5 ? A_ONES + (i - 3) * 1024 : MISC + M_MOE + (i - 5) * 1024); }
__device__ __forceinline__ uint32_t m_off(int r) { return r < 3 ? 12 * SLOT + r * MT : S_M3 * SLOT; }
__device__ __forceinline__ int x_slot(int e, int s) { return NQ == 5 ? (e < 14 ? s : e - 11) : (e < 13 ? s : 3 + s); }
__device__ __forceinline__ uint32_t wo_slot(int i) { return (uint32_t)(WO_SLOTS >> (4 * i)) & 15u; }

__global__ void __launch_bounds__(512, 1)
fused_kernel(const __nv_bfloat16* __restrict__ x, const __nv_bfloat16* __restrict__ wqkv, const __nv_bfloat16* __restrict__ wo,
             const __nv_bfloat16* __restrict__ wr, const __nv_bfloat16* __restrict__ wd, const int by_sm,
             const __grid_constant__ CUtensorMap tmX, const __grid_constant__ CUtensorMap tmW,
             const __grid_constant__ CUtensorMap tmWo, const __grid_constant__ CUtensorMap tmOut,
             const __grid_constant__ CUtensorMap tmG, const __grid_constant__ CUtensorMap tmU,
             const __grid_constant__ CUtensorMap tmD, const __grid_constant__ CUtensorMap tmR,
             const __grid_constant__ CUtensorMap tmWp) {
  if (TMP && threadIdx.x == 32 * TMPW) { map_pf(&tmX); map_pf(&tmW); }
  extern __shared__ __align__(1024) uint8_t smem_raw[];
  const uint32_t sb = (uint32_t)__cvta_generic_to_shared(smem_raw);
  const uint32_t bars = sb + MISC + M_BAR;
  uint32_t smid;
  asm("mov.u32 %0, %%smid;" : "=r"(smid));
  const int tpc = smid >> 1;
  int cl = tpc + max(((tpc - 25) * 37) >> 8, 0);
  cl = tpc < 60 ? cl : cl - 1;
  cl = tpc < 62 ? cl : (tpc - 58) * 8;
  const int u = by_sm ? 2 * cl + (blockIdx.x & 1) : blockIdx.x;
  const int hg = (u >> 4) & 7, tb = u & 15;
  const int b = tb * 8 + hg;
  const int lane = threadIdx.x & 31;
  const int warp = __shfl_sync(~0u, threadIdx.x >> 5, 0);
  const int ltid = threadIdx.x;
  const int g = lane >> 2, t = lane & 3;
  const uint32_t d0 = (sb & 0x3FFFF) >> 4;
#define BAR(i) (bars + 8 * (i))
  TLS(0, 0);

  const int rank = u & 1;
  auto load_entry = [&](int e, int s) {
    const int k0 = kstep1(e, hg) * 64;
    mbar_expect_tx(BAR(B_FXQ + s), e < NF ? 2 * SLOT : SLOT);
    mbar_expect_tx(BAR(B_FKV + s), R5 ? SLOT : 2 * SLOT);
    if (R5 && e < 11) mbar_expect_tx(BAR(B_FV + s), SLOT);
    const uint32_t vb = R5 ? BAR(B_FV + s) : BAR(B_FKV + s);
    tma2d(sb + x_slot(e, s) * SLOT, &tmX, k0, tb * 128, BAR(B_FXQ + s));
    if (e < MC0 || !(MC & 1)) {
      if (e < NF) tma3d(sb + (3 + s) * SLOT, &tmW, k0, 2 * hg, BAR(B_FXQ + s));
      tma3d(sb + (6 + 2 * s) * SLOT, &tmW, k0, 16 + 2 * hg, BAR(B_FKV + s));
      tma3d(sb + (7 + 2 * s) * SLOT, &tmW, k0, 32 + 2 * hg, vb);
    } else {
      if (e < NF && (e & 1) == rank) tma3d_mc(sb + (3 + s) * SLOT, &tmW, k0, 2 * hg, BAR(B_FXQ + s));
      if (R5 && e >= 11) { if (rank == 0) tma3d_mc(sb + ((K_SLOTS >> (4 * (e - 10))) & 15u) * SLOT, &tmW, k0, 16 + 2 * hg, BAR(B_FKV + s)); }
      else tma3d_mc(sb + (6 + 2 * s + rank) * SLOT, &tmW, k0, 16 + 16 * rank + 2 * hg, rank ? vb : BAR(B_FKV + s));
    }
  };
  if (warp == FW && u < NCTA) {
    if (elect_one()) {
      mbar_init(BAR(B_FXQ), 1); mbar_init(BAR(B_FKV), 1);
      if (R5) mbar_init(BAR(B_FV), 1);
      load_entry(0, 0);
      asm volatile("fence.mbarrier_init.release.cluster;" ::: "memory");
      TLS(FW * 32, 61);
    }
    __syncwarp();
  }
  if (u >= NCTA) {
    const int j = u - NCTA;
    if (warp == 8 && elect_one()) {
#pragma unroll
      for (int i = 0; i < 13; i++) mbar_init(BAR(i), 1);
    }
    if (ltid < 64) sts_u4(sb + MISC + ltid * 16, make_uint4(0x3F803F80u, 0x3F803F80u, 0x3F803F80u, 0x3F803F80u));
    fence_async_smem();
    __syncthreads();
    if (warp < 4) {
      int s = 0, p = 0;
#pragma unroll 1
      for (int pass = 0; pass < 3; pass++) {
        float acc[4][4];
#pragma unroll
        for (int c = 0; c < 4; c++) acc[c][0] = acc[c][1] = acc[c][2] = acc[c][3] = 0.f;
#pragma unroll 1
        for (int k = 0; k < 16; k++) {
          mbar_wait(BAR(s), p);
          wg_fence();
#pragma unroll
          for (int c = 0; c < 4; c++)
#pragma unroll
            for (int kk = 0; kk < 4; kk++)
              wgmma_ss_n8<1, 0>(acc[c], mkdesc((d0 + s * 2048 + c * 512 + kk * 128) | (512u << 16), HI_SW128), mkdesc((d0 + (MISC >> 4)) | (1u << 16), HI_SW128));
          wg_commit();
          wg_wait<0>();
          if (ltid == 0) mbar_arrive(BAR(6 + s));
          if (++s == SVS) { s = 0; p ^= 1; }
        }
        uint32_t* pc = G.cs + (pass < 2 ? DM + pass * DM : 0) + j * 256 + warp * 16 + g;
#pragma unroll
        for (int c = 0; c < 4; c++) {
          reg_fence(acc[c]);
          const uint32_t v = __float_as_uint((t & 1) ? acc[c][2] : acc[c][0]);
          if (t < 2) stx1(pc + c * 64 + t * 8, v ? v : 0x80000000u);
        }
        TLS(0, 1 + pass);
      }
    } else if (warp >= 8 && j == 0) {
      const int wq = warp - 8;
      const uint32_t top = sb + MISC + 1024;
#pragma unroll 1
      for (uint32_t it = 0; it < SPIN_MAX; it++) {
        const uint4 v0 = ldx4(G.key + wq * 256 + lane * 4), v1 = ldx4(G.key + wq * 256 + 128 + lane * 4);
        uint32_t ok;
        asm volatile("{\n.reg .pred p, q;\nsetp.ne.u32 p, %1, 0;\nbar.red.and.pred q, 2, 256, p;\nselp.b32 %0, 1, 0, q;\n}" : "=r"(ok) : "r"((v0.x & v0.y & v0.z & v0.w & v1.x & v1.y & v1.z & v1.w) >> 27) : "memory");
        ok = __any_sync(~0u, ok);
        if (!ok && it) continue;
        TLS(256, 4);
        uint32_t np = 0u - (1u << 28), mine = 0;
#pragma unroll 1
        for (int r = 0; r < 8; r++) {
          const uint32_t m0 = __viaddmax_u32(v0.x, np, v0.y + np), m1 = __viaddmax_u32(v0.z, np, v0.w + np), m2 = __viaddmax_u32(v1.x, np, v1.y + np), m3 = __viaddmax_u32(v1.z, np, v1.w + np);
          np -= __reduce_max_sync(~0u, max(max(m0, m1), max(m2, m3)));
          if (g == r) mine = 0u - np;
        }
        if (t == 0) sts_u(top + (wq * 8 + g) * 4, mine);
        bar_sync<2, 256>();
        TLS(256, 5);
        int rk = 0;
#pragma unroll
        for (int i = 0; i < 4; i++) {
          const uint4 o = lds_u4(top + t * 64 + i * 16);
          rk += (o.x > mine) + (o.y > mine) + (o.z > mine) + (o.w > mine);
        }
        rk += __shfl_xor_sync(~0u, rk, 1);
        rk += __shfl_xor_sync(~0u, rk, 2);
        if (ok) { if (rk < 8) stx1(G.top + t * 32 + rk, mine); break; }
        __nanosleep(2500);
      }
      TLS(256, 7);
    } else if (warp == 4) {
      int s = 0, p = 1;
      if (SVD) __nanosleep(SVD);
#pragma unroll 1
      for (int i = 0; i < 48; i++) {
        mbar_wait(BAR(6 + s), p);
        if (j == 0 && i >= SV0A && i < SV0B) mbar_wait(BAR(s >= SV0 ? s - SV0 : s - SV0 + SVS), s >= SV0 ? p ^ 1 : p);
        if (elect_one()) {
          mbar_expect_tx(BAR(s), 2 * SLOT);
          const int ch = (i < 32 ? 16 + (i & 16) : 0) + j * 4, k0 = (i & 15) * 64;
          tma3d(sb + s * 2 * SLOT, &tmW, k0, ch, BAR(s));
          tma3d(sb + s * 2 * SLOT + SLOT, &tmW, k0, ch + 2, BAR(s));
        }
        if (++s == SVS) { s = 0; p ^= 1; }
      }
    }
    if (ltid == 0) cnt_wait(C_DONE, NCTA);
    __syncthreads();
    const uint4 zero = make_uint4(0, 0, 0, 0);
    if (ltid < 128) reinterpret_cast<uint4*>(G.key)[j * 128 + ltid] = zero;
    else if (ltid < 320) reinterpret_cast<uint4*>(G.cs)[j * 192 + ltid - 128] = zero;
    else if (ltid < 322) reinterpret_cast<uint4*>(G.top)[j * 8 + ltid - 320] = zero;
    if (ltid == 0) { cnt_done(); TLDUMP(); }
    return;
  }

  if (warp == 12) {
    if (elect_one()) {
#pragma unroll
      for (int i = 1; i < 7; i++) if (i != B_FKV) mbar_init(BAR(i), 1);
      if (R5) { mbar_init(BAR(B_FV + 1), 1); mbar_init(BAR(B_FV + 2), 1); }
      if (E1E) load_entry(1, 1);
      asm volatile("fence.mbarrier_init.release.cluster;" ::: "memory");
    }
  } else if (warp >= 13) {
    if (elect_one()) {
      if (warp == 15) {
#pragma unroll
        for (int i = B_FAUX; i < NBAR; i++) mbar_init(BAR(i), i < B_E || !MC ? 2 : 4);
        mbar_init(BAR(B_KV4), 4); mbar_init(BAR(B_MS), 2); mbar_init(BAR(B_GQ), 1);
        if (R5) { mbar_init(BAR(B_EK), 4); mbar_init(BAR(B_EK + 1), 4); mbar_init(BAR(B_EK + 2), 4); }
      } else {
#pragma unroll
        for (int i = 0; i < 23; i++) mbar_init(BAR((warp == 13 ? 7 : 30) + i), 1);
      }
      asm volatile("fence.mbarrier_init.release.cluster;" ::: "memory");
    }
  }
  __syncthreads();
  if (MC) asm volatile("barrier.cluster.arrive.relaxed.aligned;" ::: "memory");

  const bool unit = u < NUNIT;
  const int dcol = (u & 15) * 64, drow = (u >> 4) * 448;
  if (warp >= 12) {
    asm volatile("setmaxnreg.dec.sync.aligned.u32 %0;" ::"n"(PROD_REGS));
    if (MC && warp != 12) asm volatile("barrier.cluster.wait.aligned;" ::: "memory");
    if (warp == 12) {
      int s = 1 + E1E, p = 1, pn = 3;
#pragma unroll 1
      for (int e = 1 + E1E; e < 16; e++) {
        if (MC && e == MC0) asm volatile("barrier.cluster.wait.aligned;" ::: "memory");
        if (e == GATE) mbar_wait(BAR(B_FXQ), 0);
        mbar_wait(BAR(B_E + s), p);
        if (elect_one()) {
          load_entry(e, s);
          if (NR == 4 && e == 11) mbar_arrive(BAR(B_ME + 3));
          if (e == ASTE) {
            mbar_expect_tx(BAR(B_AST), 2 * SLOT + 2048);
            bulk_ld(sb + 12 * SLOT, x + (size_t)b * 16 * DM, 2 * SLOT, BAR(B_AST));
            bulk_ld(sb + MISC + M_MOE, wr, 2048, BAR(B_AST));
          } else if (e >= 3) {
            if (e < 6) bulk_pf(wqkv + (size_t)((e - 2) * 256 + 2 * b) * 3 * DM, 2 * 3 * DM * 2);
            if (e < 7) bulk_pf(wo + (size_t)((e - 3) * 256 + 2 * b) * DM, 2 * DM * 2);
            if (NUNIT) {
#pragma unroll 1
              for (int i = (PFTAB >> (4 * (e - 3))) & 15; i > 0; i--, pn++) {
                if (pn >= 16) { if (!(MX & 8)) tma2d_pf(&tmD, dcol, drow + (pn - 16) * 64); }
                else if (unit && !(MX & 2)) tma2d_pf(rank ? &tmU : &tmG, (u >> 1) * 64, pn * 64);
              }
            }
          }
        }
        if (R5 && e >= 11) {
          mbar_wait(BAR(B_EK + (s == 2 ? 0 : s + 1)), e >= 14);
          if (elect_one()) {
            mbar_expect_tx(BAR(B_FV + s), SLOT);
            if (rank) tma3d_mc(sb + ((V_SLOTS >> (4 * (e - 10))) & 15u) * SLOT, &tmW, kstep1(e, hg) * 64, 32 + 2 * hg, BAR(B_FV + s));
          }
        }
        if (++s == 3) { s = 0; p ^= 1; }
      }
#pragma unroll 1
      for (int k = 0; k < NQ; k++) {
        if (k == 0) mbar_wait(BAR(B_E + 1), 0);
        if (k == 1) mbar_wait(BAR(B_EK + 2), 1);
        if (k == 2) mbar_wait(BAR(B_EK + 0), 0);
        if (k == 3) mbar_wait(BAR(B_STG), 0);
        if (k == 5) mbar_wait(BAR(B_EQ), 0);
        if (elect_one()) {
          const int k0 = kstep1(NF + k, hg) * 64;
          mbar_expect_tx(BAR(B_FQ + k), SLOT);
          if (!(MC & 2)) tma3d(sb + ((QW_SLOTS >> (4 * k)) & 15u) * SLOT, &tmW, k0, 2 * hg, BAR(B_FQ + k));
          else if ((k & 1) == rank) tma3d_mc(sb + ((QW_SLOTS >> (4 * k)) & 15u) * SLOT, &tmW, k0, 2 * hg, BAR(B_FQ + k));
        }
      }
#pragma unroll 1
      for (int i = 0; i < 16; i++) {
        mbar_wait(i < 7 ? BAR(B_EQ + ((i + WQ0) >> 1)) : (i < 9 ? BAR(B_DE) : BAR(B_EO + i - 9)), 0);
        if (i == WOK) mbar_wait(BAR(B_KVB), 0);
        mbar_wait(BAR(B_FWO + i - (i < WOK ? WOD1 : WOD)), 0);
        if (elect_one()) {
          mbar_expect_tx(BAR(B_FWO + i), SLOT);
#pragma unroll
          for (int hf = 0; hf < ((MC & 4) ? 1 : 2); hf++) {
            const int n = 2 * i + ((MC & 4) ? rank : hf), m = slab(n - 4, hg), hd = n < 4 ? 4 * hg + n : 4 * (m & 7) + (m >> 3);
            if (i < 2 + NDIR) tma5d(sb + wo_slot(i) * SLOT + (n & 1) * 8192, &tmWp, hd * 4, 2 * hg, BAR(B_FWO + i), MC & 4);
            else if (MC & 4) tma3d_mc(sb + wo_slot(i) * SLOT + rank * 8192, &tmWo, hd * 32, 2 * hg, BAR(B_FWO + i));
            else tma3d(sb + wo_slot(i) * SLOT + hf * 8192, &tmWo, hd * 32, 2 * hg, BAR(B_FWO + i));
          }
        }
      }
    } else if (warp == 13) {
      if (elect_one()) {
        map_pf(rank ? &tmU : &tmG); map_pf(&tmR); map_pf(&tmD); map_pf(&tmWo); map_pf(&tmWp); map_pf(&tmOut);
      }
      bar_sync<6, 64>();
      if (elect_one()) {
        cnt_wait(C_B, NCTA);
        fence_async_gmem();
        mbar_expect_tx(BAR(B_FAUX), 1024);
        bulk_ld(sb + A_ST, G.stats + tb * 128, 1024, BAR(B_FAUX));
      }
      __syncwarp();
      TLS(416, 68);
#pragma unroll 1
      for (int m = 1; m < 4; m++) {
        const int part = m == 3 ? 0 : m;
        uint4 c;
#pragma unroll 1
        for (uint32_t it = 0; it < SPIN_MAX; it++) {
          c = ldx4(G.cs + part * DM + hg * 128 + lane * 4);
          if (__all_sync(~0u, min(min(c.x, c.y), min(c.z, c.w)))) break;
          __nanosleep(POLLNS);
        }
        sts_u4(sb + A_CS + part * 512 + lane * 16, c);
        __syncwarp();
        if (m > 1 && lane == 0) mbar_arrive(BAR(m == 2 ? B_FAUX : B_CQ));
        TLS(416, 71 + m);
      }
      mbar_wait(BAR(B_XS), 1);
      if (elect_one()) asm volatile("red.relaxed.gpu.global.add.u32 [%0], 1;" ::"l"(&G.cnt[C_DONE]) : "memory");
    } else if (warp == 14) {
      const uint4 sent = make_uint4(SENT, SENT, SENT, SENT);
      uint4* ro = G.o + (tb * 32 + hg) * 512 + lane;
      uint4* rp = G.part + b * 544 + lane;
      if (RSL) bar_sync<5, 160>(); else mbar_wait(BAR(B_AST), 0);
#pragma unroll 1
      for (int i = RS0; i < 40; i++) {
        uint4* q = i < 32 ? ro + (i >> 3) * 4096 + (i & 7) * 64 : rp + (i - 32) * 64;
        q[0] = sent; q[32] = sent;
        __nanosleep(RSNS);
      }
      rp[512] = sent;
#pragma unroll
      for (int i = 0; i < 4; i++) G.y[u * 128 + i * 32 + lane] = sent;
      if (unit) reinterpret_cast<uint4*>(G.h)[u * 32 + lane] = sent;
      G.fin[hg * 640 + tb * 40 + lane] = sent;
      if (lane < 8) G.fin[hg * 640 + tb * 40 + 32 + lane] = sent;
      if (!RSL) bar_sync<5, 160>();
      __syncwarp();
      TLS(448, 67);
      if (lane == 0) cnt_arrive(C_B);
      __syncwarp();
      TLS(448, 32);
      asm volatile("bar.arrive 6, 64;" ::: "memory");
    } else {
      const uint32_t stg = sb + 12 * SLOT;
      auto load_a = [&](int n, int r) {
        mbar_expect_tx(BAR(B_MF + r), (MX & 2) ? 1024 : MT);
        if (!(MX & 2)) tma2d_ef(sb + m_off(r), rank ? &tmU : &tmG, (u >> 1) * 64, n * 64, BAR(B_MF + r));
      };
      mbar_wait(BAR(B_XS), 0);
      if (unit) {
#pragma unroll 1
        for (int i = 0; i < 3; i++) {
          if (elect_one()) load_a(i, i);
          __nanosleep(PFILL);
        }
      }
      uint32_t key;
#pragma unroll 1
      for (uint32_t it = 0; it < SPIN_MAX; it++) {
        key = ldx1(G.top + ((u >> 1) & 3) * 32 + (lane & 7));
        if (__all_sync(~0u, key)) break;
        __nanosleep(TPNS);
      }
      TLS(480, 66);
      if (lane < 8) sts_u(sb + MISC + M_IDX + lane * 4, key);
      __syncwarp();
      if (lane == 0) mbar_arrive(BAR(B_XS));
      if (unit) {
        int tok[8];
#pragma unroll
        for (int i = 0; i < 8; i++) tok[i] = ~__shfl_sync(~0u, key, i) & 2047;
        int r = 0, p = 0;
#pragma unroll 1
        for (int n = 0; n < 16; n++) {
          if (n >= 3) mbar_wait(BAR(B_ME + r), r == 3 ? p : p ^ 1);
          if (elect_one()) {
            if (n >= 3) load_a(n, r);
#pragma unroll
            for (int i = 0; i < 8; i++) tma2d(sb + m_off(r) + 8192 + i * 128, &tmR, n * 64, tok[i], BAR(B_MF + r));
          }
          if (++r == NR) { r = 0; p ^= 1; }
        }
      }
      if (NUNIT) {
        if (lane == 0) mbar_expect_tx(BAR(B_DF), (MX & 8) ? 0 : 7 * 8192);
#pragma unroll 1
        for (int i = 0; i < 7; i++) {
          if (NR == 4) {
            if (i >= 3) mbar_wait(i < 5 ? BAR(B_ME + 3) : (R5 ? BAR(B_EQ + 1) : BAR(B_STG)), 0);
            else if (unit) mbar_wait(BAR(B_ME + i), 1);
          } else {
            if (i >= 3) mbar_wait(BAR(B_EQ + ((i - 3) >> 1)), 0);
            else if (unit) mbar_wait(BAR(B_ME + (i == 2 ? 0 : i + 1)), i == 2);
          }
          if (!(MX & 8) && elect_one()) tma2d_ef(sb + d_off(i), &tmD, dcol, drow + i * 64, BAR(B_DF));
          if (DNS) __nanosleep(DNS);
        }
      }
    }
    if (warp == 14) {
      if (DPF && NUNIT && !(MX & 8)) {
        mbar_wait(DS ? BAR(B_MS) : (DPF == 1 ? BAR(B_FQ) : BAR(B_T0)), 0);
#pragma unroll 1
        for (int pf = 0; pf < 7; pf++) { pf256(sb + MISC + M_DUM, wd + (size_t)(drow + pf * 64 + rank * 32 + lane) * DM + (dcol & ~127)); __nanosleep(PFNS2); }
      }
      const uint32_t* src = reinterpret_cast<const uint32_t*>(G.part + ((lane >> 3) * 32 + hg) * 544 + 512) + tb * 8 + (lane & 7);
      mbar_wait(BAR(B_EQ + MRW), 0);
      if (MRD) __nanosleep(MRD);
      uint32_t z0, z1, z2, z3;
#pragma unroll 1
      for (uint32_t it = 0; it < SPIN_MAX; it++) {
        z0 = ldx1(src); z1 = ldx1(src + 8 * 2176); z2 = ldx1(src + 16 * 2176); z3 = ldx1(src + 24 * 2176);
        if (!__any_sync(~0u, max(max(z0, z1), max(z2, z3)) == SENT)) break;
      }
      if (MRED == 2 && elect_one()) mbar_arrive(BAR(B_ZOK));
      float zz = (__uint_as_float(z0) + __uint_as_float(z1)) + (__uint_as_float(z2) + __uint_as_float(z3));
      zz += __shfl_xor_sync(~0u, zz, 8);
      zz += __shfl_xor_sync(~0u, zz, 16);
      stx1(reinterpret_cast<uint32_t*>(G.fin + hg * 640) + (tb >> 2) * 640 + 512 + ((tb >> 1) & 1) * 64 + (lane & 1) * 32 + (tb & 1) * 16 + ((lane & 7) >> 1) * 4 + (lane >> 3),
           pack_bf16(zz, zz));
      TLS(448, 12);
    }
    if (!MFIN && (warp == 13 || warp == 14)) {
      mbar_wait(BAR(B_EQ + H2W), 0);
      if (H2D) __nanosleep(H2D);
#pragma unroll 1
      for (uint32_t it = 0; it < SPIN_MAX; it++) {
        if (warp == 14 && elect_one()) { mbar_expect_tx(BAR(B_FIN), 10240); bulk_ld(sb + S_KVB * SLOT, G.fin + hg * 640, 10240, BAR(B_FIN)); }
        mbar_wait(BAR(B_FIN), it & 1);
        uint32_t m = 0;
#pragma unroll
        for (int i = 0; i < 10; i++) m = max(m, lds_u(sb + S_KVB * SLOT + (i * 64 + ltid - 416) * 16 + (g >> 1) * 4));
        uint32_t bad;
        asm volatile("{\n.reg .pred p, q;\nsetp.eq.u32 p, %1, 0xFFFFFFFF;\nbar.red.or.pred q, 7, 64, p;\nselp.b32 %0, 1, 0, q;\n}" : "=r"(bad) : "r"(m) : "memory");
        if (!__any_sync(~0u, bad)) break;
      }
      if (warp == 14 && elect_one()) mbar_arrive(BAR(B_KVB));
      TLS(448, 14);
    }
    if (PH && (warp == 13 || warp == 14)) {
      bar_sync<3, 192>();
      mbar_wait(BAR(B_STG), 0);
#pragma unroll 1
      for (uint32_t it = 0; NUNIT && it < SPIN_MAX; it++) {
        if (elect_one()) {
          const uint32_t* ph = G.h + (u >> 4) * 7 * 256;
          if (warp == 13) { mbar_expect_tx(BAR(B_HF), 7168); bulk_ld(sb + h_off(3), ph + 768, 2048, BAR(B_HF)); bulk_ld(sb + h_off(5), ph + 1280, 2048, BAR(B_HF)); }
          else { bulk_ld(sb + h_off(0), ph, 1024, BAR(B_HF)); bulk_ld(sb + h_off(1), ph + 256, 1024, BAR(B_HF)); bulk_ld(sb + h_off(2), ph + 512, 1024, BAR(B_HF)); }
        }
        mbar_wait(BAR(B_HF), it & 1);
        uint32_t m = 0;
#pragma unroll
        for (int i = 0; i < 7; i++) m = max(m, lds_u(sb + h_off(i) + (ltid - 416) * 16 + (g >> 1) * 4));
        uint32_t bad;
        asm volatile("{\n.reg .pred p, q;\nsetp.eq.u32 p, %1, 0xFFFFFFFF;\nbar.red.or.pred q, 7, 64, p;\nselp.b32 %0, 1, 0, q;\n}" : "=r"(bad) : "r"(m) : "memory");
        if (!__any_sync(~0u, bad)) break;
        __nanosleep(POLLNS);
      }
      if (warp == 14 && elect_one()) mbar_arrive(BAR(B_KVB));
    }
    __syncwarp();
    if (warp >= 13) {
      const char* og = reinterpret_cast<const char*>(G.o + tb * 16384);
      auto probe = [&](uint32_t m) {
        const char* p = og + m * 8192u + (lane & 15) * 512 + 496;
#pragma unroll 1
        for (uint32_t it = 0; it < SPIN_MAX; it++)
          if (!__any_sync(~0u, ldx1(p) == SENT)) break;
      };
      if (warp == 15) {
        int r = 0, p = 1;
        mbar_wait(BAR(B_EAUX), 0);
#pragma unroll 1
        for (int i = I0; i < 16; i++) {
          const uint32_t dst = sb + ((A_SLOTS >> (4 * r)) & 15u) * SLOT, m0 = slab(2 * i - 4, hg), m1 = slab(2 * i - 3, hg);
          if (i == I0 + 3) mbar_wait(BAR(B_DE), 0);
          mbar_wait(BAR(B_EA + r), p);
          if ((PROBE >> i) & 1) probe(lane < 16 ? m0 : m1);
          if (elect_one()) {
            mbar_expect_tx(BAR(B_AF + r), SLOT);
            bulk_ld(dst, og + m0 * 8192u, 8192, BAR(B_AF + r)); bulk_ld(dst + 8192, og + m1 * 8192u, 8192, BAR(B_AF + r));
          }
          if (++r == NA) { r = 0; p ^= 1; }
        }
      } else {
        const uint32_t lo = lane * 32 + g * 4, hb = sb + (warp - 13) * 8192;
        uint32_t ph = 0;
        int r = 0, p = 0;
#pragma unroll 1
        for (int i = I0; i < 16; i++) {
          const uint32_t mine = hb + ((A_SLOTS >> (4 * r)) & 15u) * SLOT;
          auto bad = [&]() {
            uint32_t v[8];
#pragma unroll
            for (int j = 0; j < 8; j++) v[j] = lds_u(mine + lo + j * 1024);
            return __any_sync(~0u, max(max(max(v[0], v[1]), max(v[2], v[3])), max(max(v[4], v[5]), max(v[6], v[7]))) == SENT);
          };
          mbar_wait(BAR(B_AF + r), p);
          if (!NOVAL && bad()) {
            const uint32_t m = slab(2 * i - 17 + warp, hg);
#pragma unroll 1
            for (uint32_t it = 0; it < 64; it++) {
              probe(m);
              if (elect_one()) { mbar_expect_tx(BAR(B_AR + warp - 13), 8192); bulk_ld(mine, og + m * 8192u, 8192, BAR(B_AR + warp - 13)); }
              mbar_wait(BAR(B_AR + warp - 13), ph);
              ph ^= 1;
              if (!bad()) break;
            }
          }
          if (elect_one()) mbar_arrive(BAR(B_VAL + r));
          if (++r == NA) { r = 0; p ^= 1; }
        }
      }
    }
  } else if (warp >= 8) {
    asm volatile("setmaxnreg.dec.sync.aligned.u32 %0;" ::"n"(MOE_REGS));
    if (MC) asm volatile("barrier.cluster.wait.aligned;" ::: "memory");
    const int aw = warp - 8;
    const uint32_t mbuf = sb + MISC + M_MOE, stg = sb + 12 * SLOT;
    mbar_wait(BAR(B_AST), 0);
    TLS(288, 64);
    {
      float v[16];
#pragma unroll
      for (int r = 0; r < 16; r++) v[r] = 0.f;
      const uint32_t base = stg + aw * 4 * 2048 + lane * 8;
#pragma unroll 1
      for (int c = 0; c < 8; c++) {
        const float2 w2 = lds_f2(mbuf + c * 256 + lane * 8);
        const float w[4] = {bf_lo(__float_as_uint(w2.x)), bf_hi(__float_as_uint(w2.x)), bf_lo(__float_as_uint(w2.y)), bf_hi(__float_as_uint(w2.y))};
        v[12] += (w[0] + w[1]) + (w[2] + w[3]);
#pragma unroll
        for (int r = 0; r < 4; r++) {
          const float2 x2 = lds_f2(base + r * 2048 + c * 256);
#pragma unroll
          for (int e = 0; e < 2; e++) {
            const uint32_t xx = __float_as_uint(e ? x2.y : x2.x);
            const float lo = bf_lo(xx), hi = bf_hi(xx);
            v[r] += lo; v[4 + r] = fmaf(lo, lo, v[4 + r]); v[8 + r] = fmaf(lo, w[2 * e], v[8 + r]);
            v[r] += hi; v[4 + r] = fmaf(hi, hi, v[4 + r]); v[8 + r] = fmaf(hi, w[2 * e + 1], v[8 + r]);
          }
        }
      }
#pragma unroll
      for (int l = 0; l < 4; l++) {
        const int n = 8 >> l;
        const bool up = lane & (2 * n);
#pragma unroll
        for (int r = 0; r < 8; r++) {
          if (r < n) { const float a = v[r], c = v[n + r]; v[r] = (up ? c : a) + __shfl_xor_sync(~0u, up ? a : c, 2 * n); }
        }
      }
      v[0] += __shfl_xor_sync(~0u, v[0], 1);
      const float sx = __shfl_sync(~0u, v[0], 2 * t), sq = __shfl_sync(~0u, v[0], 8 + 2 * t), sw = __shfl_sync(~0u, v[0], 16 + 2 * t), ws = __shfl_sync(~0u, v[0], 24);
      if (lane < 4) {
        const int row = b * 16 + aw * 4 + lane;
        const float mean = sx * (1.f / DM);
        const float var = fmaxf(fmaf(-mean, mean, sq * (1.f / DM)), 0.f);
        float sd;
        asm("sqrt.approx.ftz.f32 %0, %1;" : "=f"(sd) : "f"(bf_round(bf_round(var) + 1e-5f)));
        const float rstd = rcp(bf_round(sd));
        const float mb = bf_round(mean);
        uint32_t rb = pack_bf16(fmaf(-mb, ws, sw) * rstd, 0.f) & 0xFFFFu;
        rb = (rb & 0x8000u) ? (~rb & 0xFFFFu) : (rb | 0x8000u);
        const uint32_t key = (1u << 27) | (rb << 11) | (uint32_t)(2047 - row);
        if (KEY1) sts_u(sb + MISC + M_KEY + (aw * 4 + lane) * 4, key); else stx1(G.key + row, key);
        G.stats[row] = make_float2(mb, rstd);
      }
    }
    bar_sync<2, 128>();
    if (KEY1 && ltid < 272) stx1(G.key + b * 16 + lane, lds_u(sb + MISC + M_KEY + lane * 4));
    TLS(288, 65);
    sts_u4(sb + A_ONES + (ltid - 256) * 16, make_uint4(0x3F803F80u, 0x3F803F80u, 0x3F803F80u, 0x3F803F80u));
    fence_async_smem();
    asm volatile("bar.arrive 5, 160;" ::: "memory");
    if (ltid == 256) { if (unit && rank == 0) mbar_expect_tx(BAR(B_UP), 2048); mbar_arrive(BAR(B_XS)); }
    bar_sync<2, 128>();
    mbar_wait(BAR(B_XS), 1);
    TLS(288, 70);
    if (NUNIT) {
      if (unit) {
        int r = 0, p = 0;
        uint32_t rel = 0;
        float acc[8];
        uint2 s0, s1;
#pragma unroll
        for (int i = 0; i < 8; i++) acc[i] = 0.f;
        if (MS == 16) mbar_wait(BAR(B_T0), 0); else if (MS) mbar_wait(BAR(B_MS), 0);
#pragma unroll 1
        for (int n = 0; n < 16; n++) {
          if (n == 15) {
            mbar_wait(BAR(B_FAUX), 0);
            s0 = ldx2(G.stats + (~lds_u(sb + MISC + M_IDX + t * 8) & 2047)); s1 = ldx2(G.stats + (~lds_u(sb + MISC + M_IDX + t * 8 + 4) & 2047));
          }
          mbar_wait(BAR(B_MF + r), p);
          if (!(n & 3)) TLS(288, 56 + (n >> 2));
          const uint32_t mo = m_off(r) >> 4, da = (d0 + mo) | (512u << 16), db = (d0 + mo + 512) | (1u << 16);
          const uint32_t hb = 0x40000000u | ((A_ONES >> 4) - 512 - mo);
          wg_fence();
#pragma unroll
          for (int kk = 0; kk < ((MX & 1) ? 1 : 4); kk++) wgmma_ss_n16<1, 0>(acc, mkdesc(da + kk * 128, HI_SW128), mkdesc(db + kk * 2, hb));
          wg_commit();
          wg_wait<1>();
          if (n > 0 && !rel && ltid == 256) mbar_arrive(BAR(B_ME + (r == 0 ? NR - 1 : r - 1)));
          rel = 0;
          const int r0 = r;
          if (++r == NR) { r = 0; p ^= 1; }
        }
        wg_wait<0>();
        reg_fence(acc);
        {
          if (!MW0 && !rel && ltid == 256) mbar_arrive(BAR(B_ME + 15 % NR));
          TLS(288, 71);
          const float v0 = bf_round(fmaf(-__uint_as_float(s0.x), acc[4], acc[0]) * __uint_as_float(s0.y));
          const float v1 = bf_round(fmaf(-__uint_as_float(s1.x), acc[4], acc[1]) * __uint_as_float(s1.y));
          const float v2 = bf_round(fmaf(-__uint_as_float(s0.x), acc[6], acc[2]) * __uint_as_float(s0.y));
          const float v3 = bf_round(fmaf(-__uint_as_float(s1.x), acc[6], acc[3]) * __uint_as_float(s1.y));
          if (rank) {
            asm volatile("{\n.reg .b32 ra, rb;\nmapa.shared::cluster.u32 ra, %0, 0;\nmapa.shared::cluster.u32 rb, %1, 0;\n"
                         "st.async.weak.shared::cluster.mbarrier::complete_tx::bytes.v4.f32 [ra], {%2, %3, %4, %5}, [rb];\n}"
                         ::"r"(mbuf + (ltid - 256) * 16), "r"(BAR(B_UP)), "f"(v0), "f"(v1), "f"(v2), "f"(v3) : "memory");
          } else {
            const float g0 = bf_round(v0 * sigmoid(v0)), g1 = bf_round(v1 * sigmoid(v1)), g2 = bf_round(v2 * sigmoid(v2)), g3 = bf_round(v3 * sigmoid(v3));
            mbar_wait(BAR(B_UP), 0);
            const uint4 uu = lds_u4(mbuf + (ltid - 256) * 16);
            const uint32_t h0 = movmat(pack_bf16(g0 * __uint_as_float(uu.x), g1 * __uint_as_float(uu.y)));
            const uint32_t h1 = movmat(pack_bf16(g2 * __uint_as_float(uu.z), g3 * __uint_as_float(uu.w)));
            uint32_t* ph = G.h + (u >> 1) * 256 + g * 32 + t;
            stx1(ph + ((2 * aw) ^ g) * 4, h0); stx1(ph + ((2 * aw + 1) ^ g) * 4, h1);
          }
          TLS(288, 60);
        }
      }
    }
    if (PH) asm volatile("bar.arrive 3, 192;" ::: "memory");
    {
      const int wd_ = ltid & 63;
      const uint32_t* src = reinterpret_cast<const uint32_t*>(G.part + hg * 544 + (aw >> 1) * 256 + tb * 16) + wd_;
      mbar_wait(MRED == 2 ? BAR(B_ZOK) : BAR(B_EQ + MRW), 0);
      if (MRD) __nanosleep(MRD);
      TLS(256, 48);
      uint32_t v[16];
#pragma unroll 1
      for (uint32_t it = 0; it < SPIN_MAX; it++) {
        uint32_t m = 0;
#pragma unroll
        for (int i = 0; i < 16; i++) v[i] = ldx1(src + i * 8 * 2176);
#pragma unroll
        for (int i = 0; i < 16; i++) m = max(m, v[i]);
        if (!__any_sync(~0u, m == SENT)) break;
      }
      TLS(256, 55);
      float lo[4], hi[4];
#pragma unroll
      for (int i = 0; i < 4; i++) {
        lo[i] = (bf_lo(v[4 * i]) + bf_lo(v[4 * i + 1])) + (bf_lo(v[4 * i + 2]) + bf_lo(v[4 * i + 3]));
        hi[i] = (bf_hi(v[4 * i]) + bf_hi(v[4 * i + 1])) + (bf_hi(v[4 * i + 2]) + bf_hi(v[4 * i + 3]));
      }
      stx1(reinterpret_cast<uint32_t*>(G.fin + hg * 640) + (tb >> 2) * 640 + ((tb >> 1) & 1) * 64 + (tb & 1) * 16 + (aw >> 1) * 32 + ((wd_ >> 2) & 3) * 128 + (wd_ >> 4) * 4 + (wd_ & 3),
           pack_bf16((lo[0] + lo[1]) + (lo[2] + lo[3]), (hi[0] + hi[1]) + (hi[2] + hi[3])));
      TLS(256, 5);
    }
    if (NUNIT) {
      mbar_wait(BAR(B_STG), 0);
      bar_sync<2, 128>();
      if (HW) __nanosleep(HW);
#pragma unroll 1
      for (uint32_t it = 0; it < SPIN_MAX; it++) {
        if (elect_one()) {
          const uint32_t* ph = G.h + (u >> 4) * 7 * 256;
          if (aw == 3) { mbar_expect_tx(BAR(B_HF), 7168); bulk_ld(sb + h_off(3), ph + 768, 2048, BAR(B_HF)); bulk_ld(sb + h_off(5), ph + 1280, 2048, BAR(B_HF)); }
          else bulk_ld(stg + aw * MT + 8192, ph + aw * 256, 1024, BAR(B_HF));
        }
        mbar_wait(BAR(B_HF), it & 1);
        const uint32_t o = (ltid & 63) * 16 + (g >> 1) * 4, o2 = o + (aw >> 1) * 1024;
        const uint32_t m = max(max(lds_u(sb + h_off(0) + (aw >> 1) * MT + o), lds_u(sb + h_off(2) + o)), max(lds_u(sb + h_off(3) + o2), lds_u(sb + h_off(5) + o2)));
        uint32_t bad;
        asm volatile("{\n.reg .pred p, q;\nsetp.eq.u32 p, %1, 0xFFFFFFFF;\nbar.red.or.pred q, 2, 128, p;\nselp.b32 %0, 1, 0, q;\n}" : "=r"(bad) : "r"(m) : "memory");
        if (!__any_sync(~0u, bad)) break;
        __nanosleep(POLLNS);
      }
      TLS(288, 62);
      float acc[4] = {0.f, 0.f, 0.f, 0.f};
      mbar_wait(BAR(B_DF), 0);
      TLS(288, 63);
#pragma unroll 1
      for (int i = 0; i < 7; i++) {
        const uint32_t da = (d0 + (d_off(i) >> 4)) | (512u << 16), db = (d0 + (h_off(i) >> 4)) | (1u << 16);
        wg_fence();
#pragma unroll
        for (int kk = 0; kk < ((MX & 4) ? 1 : 4); kk++) wgmma_ss_n8<1, 0>(acc, mkdesc(da + kk * 128, HI_SW128), mkdesc(db + kk * 2, HI_SW128));
        wg_commit();
      }
      wg_wait<0>();
      reg_fence(acc);
      if (ltid < 258) { if (MC) mbar_arrive_cta(BAR(B_DE), ltid & 1); else mbar_arrive(BAR(B_DE)); }
      {
        uint32_t* py = reinterpret_cast<uint32_t*>(G.y) + u * 512 + t * 128 + aw * 16 + g;
        stx1(py, f2x(acc[0])); stx1(py + 64, f2x(acc[1])); stx1(py + 8, f2x(acc[2])); stx1(py + 72, f2x(acc[3]));
      }
      TLS(288, 69);
      const uint32_t key = lds_u(sb + MISC + M_IDX + (lane & 7) * 4);
      uint32_t rb = (key >> 11) & 0xFFFFu;
      rb = (rb & 0x8000u) ? (rb & 0x7FFFu) : (~rb & 0xFFFFu);
      const float sg = bf_round(sigmoid(__uint_as_float(rb << 16)));
      uint32_t hits = __ballot_sync(~0u, ((~key >> 7) & 15) == tb) & 255u;
      const uint32_t* py = reinterpret_cast<const uint32_t*>(G.y) + (2 * hg + (aw >> 1)) * 512 + (ltid & 63);
      if (hits) {
        sts_u4(mbuf + (ltid - 256) * 16, make_uint4(0, 0, 0, 0));
        bar_sync<2, 128>();
        if (YW >= 0) mbar_wait(BAR(B_EO + YW), 0); else if (YW == -2) mbar_wait(BAR(B_EAUX), 0);
      }
#pragma unroll 1
      while (hits) {
        const int n0 = __ffs(hits) - 1;
        hits &= hits - 1;
        const int n1 = hits ? __ffs(hits) - 1 : n0;
        hits &= hits - 1;
        uint32_t v[16];
#pragma unroll 1
        for (uint32_t it = 0; it < SPIN_MAX; it++) {
          uint32_t m = 0;
#pragma unroll
          for (int i = 0; i < 8; i++) { v[i] = ldx1(py + n0 * 64 + i * 8192); v[8 + i] = ldx1(py + n1 * 64 + i * 8192); }
#pragma unroll
          for (int i = 0; i < 16; i++) m = max(m, v[i]);
          if (!__any_sync(~0u, m == SENT)) break;
          __nanosleep(POLLNS);
        }
#pragma unroll
        for (int e = 0; e < 2; e++) {
          const uint32_t* w8 = v + 8 * e;
          const float y = ((__uint_as_float(w8[0]) + __uint_as_float(w8[1])) + (__uint_as_float(w8[2]) + __uint_as_float(w8[3]))) +
                          ((__uint_as_float(w8[4]) + __uint_as_float(w8[5])) + (__uint_as_float(w8[6]) + __uint_as_float(w8[7])));
          const int n = e ? n1 : n0;
          sts_h(mbuf + (aw >> 1) * 1024 + n * 128 + ((((ltid >> 3) & 7) ^ n) << 4) + (lane & 7) * 2, bf_round(y) * __shfl_sync(~0u, sg, n));
        }
      }
    }
    if (!NUNIT && ltid < 258) mbar_arrive(BAR(B_DE));
    fence_async_smem();
    bar_sync<2, 128>();
    TLS(288, 33);
    if (ltid == 288) mbar_arrive(BAR(B_MOE));
  } else {
    asm volatile("setmaxnreg.inc.sync.aligned.u32 %0;" ::"n"(CON_REGS));
    if (MC) asm volatile("barrier.cluster.wait.aligned;" ::: "memory");
    const int w = warp >> 2, wq = warp & 3, tid = ltid;
    const bool lead = (tid & 127) == 0;
    const uint32_t dA = (d0 + w * 512) | (1u << 16);
    const uint32_t dB = d0 | (512u << 16);
    auto release = [&](int bar) { if (lead) mbar_arrive(BAR(bar)); };
    auto release2 = [&](int bar) {
      if (MC) { if ((tid & 127) < 2) mbar_arrive_cta(BAR(bar), tid & 1); } else release(bar);
    };
    float aq[64], ak[64], av[64];
#pragma unroll
    for (int i = 0; i < 64; i++) aq[i] = ak[i] = av[i] = 0.f;
    auto q_step = [&](uint32_t bar, int p, uint32_t xs, uint32_t qs) {
      mbar_wait_b(bar, p);
      wg_fence();
#pragma unroll
      for (int kk = 0; kk < 4; kk++)
        wgmma_ss_n128<0, 1>(aq, mkdesc(dA + xs * 1024 + kk * 2, HI_SW128), mkdesc(dB + qs * 1024 + kk * 128, HI_SW128));
      wg_commit();
    };
    const uint32_t dT = dB + w * 512, dX = d0 | (1u << 16);
    auto t_step = [&](float (&a)[64], uint32_t ws, uint32_t xs) {
      wg_fence();
#pragma unroll
      for (int kk = 0; kk < 4; kk++)
        wgmma_ss_n128<1, 0>(a, mkdesc(dT + ws * 1024 + kk * 128, HI_SW128), mkdesc(dX + xs * 1024 + kk * 2, HI_SW128));
      wg_commit();
    };
    {
      int s = 0, p = 0, sp = 2;
#pragma unroll 1
      for (int e = 0; e < NF; e++) {
        TLS(0, 16 + e);
        if (((MS && MS < NF) || (DS && DS < NF)) && e == (MS ? MS : DS)) release(B_MS);
        q_step(BAR(B_FXQ + s), p, s, 3 + s);
        wg_wait<1>();
        if (e > 0) release2(B_E + sp);
        mbar_wait(BAR(B_FKV + s), p);
        t_step(ak, 6 + 2 * s, s);
        if (R5) mbar_wait(BAR(B_FV + s), p);
        t_step(av, 7 + 2 * s, s);
        if (R5 && e == NF - 1) { wg_wait<1>(); release2(B_EK + s); }
        sp = s;
        if (++s == 3) { s = 0; p ^= 1; }
      }
#pragma unroll 1
      for (int e = NF; e < 16; e++) {
        TLS(0, 16 + e);
        if (((MS >= NF && MS < 16) || DS >= NF) && e == (MS ? MS : DS)) release(B_MS);
        mbar_wait(BAR(B_FXQ + s), p);
        mbar_wait(BAR(B_FKV + s), p);
        t_step(ak, R5 ? (K_SLOTS >> (4 * (e - 10))) & 15u : 6 + 2 * s, x_slot(e, s));
        wg_wait<1>();
        release2(B_E + sp);
        if (R5) mbar_wait(BAR(B_FV + s), p);
        t_step(av, R5 ? (V_SLOTS >> (4 * (e - 10))) & 15u : 7 + 2 * s, x_slot(e, s));
        if (R5) { wg_wait<1>(); release2(B_EK + s); }
        sp = s;
        if (++s == 3) { s = 0; p ^= 1; }
      }
    }
    const uint32_t aux = sb;
    mbar_wait(BAR(B_FAUX), 0);
    const int row0 = w * 64 + wq * 16 + g;
    const float ck0 = lds_f(aux + A_CS + 512 + row0 * 4), ck1 = lds_f(aux + A_CS + 512 + (row0 + 8) * 4);
    const float cv0 = lds_f(aux + A_CS + 1024 + row0 * 4), cv1 = lds_f(aux + A_CS + 1024 + (row0 + 8) * 4);
    const uint32_t moff = (uint32_t)(w * 64 + wq * 16 + (lane & 15)) * 128 + (((lane >> 4) ^ (lane & 7)) << 4);
    const uint32_t sta = aux + A_ST + t * 16;
    float kvp[36], ao[64];
    uint32_t xr[32];
    float nm0, nm1, rs0, rs1;
    auto row_stats = [&]() {
      const float2 st0 = lds_f2(aux + A_ST + row0 * 8), st1 = lds_f2(aux + A_ST + (row0 + 8) * 8);
      nm0 = -st0.x; nm1 = -st1.x; rs0 = st0.y; rs1 = st1.y;
    };
    auto ld_x = [&]() {
#pragma unroll
      for (int j = 0; j < 16; j += 2) ldsm4(sb + (j < 8 ? SX14 : SX15) * SLOT + (moff ^ ((j & 7) << 4)), xr[2 * j], xr[2 * j + 1], xr[2 * j + 2], xr[2 * j + 3]);
    };
    auto resid = [&]() {
      const float c0 = 1.f + rs0, c1 = 1.f + rs1, e0 = nm0 * rs0, e1 = nm1 * rs1;
#pragma unroll
      for (int j = 0; j < 16; j++) {
        ao[4 * j + 0] = fmaf(bf_lo(xr[2 * j]), c0, e0); ao[4 * j + 1] = fmaf(bf_hi(xr[2 * j]), c0, e0);
        ao[4 * j + 2] = fmaf(bf_lo(xr[2 * j + 1]), c1, e1); ao[4 * j + 3] = fmaf(bf_hi(xr[2 * j + 1]), c1, e1);
      }
    };
    {
      uint32_t pa[32];
      float4 st[16];
      auto ld = [&](int j) { st[j] = lds_f4(sta + j * 64); };
      auto k_blk = [&](int c) {
#pragma unroll
        for (int i = 0; i < 2; i++) {
          const float4 u = st[2 * c + i];
          const float l0 = u.y * 1.4426950408889634f, l1 = u.w * 1.4426950408889634f;
          const float* a = ak + 8 * c + 4 * i;
          pa[4 * c + 2 * i] = phi2(fmaf(-u.x, ck0, a[0]), u.y, l0, fmaf(-u.z, ck0, a[1]), u.w, l1);
          pa[4 * c + 2 * i + 1] = phi2(fmaf(-u.x, ck1, a[2]), u.y, l0, fmaf(-u.z, ck1, a[3]), u.w, l1);
        }
      };
      const uint32_t voff = sb + w * 8192 + (uint32_t)(8 * (lane >> 4) + (lane & 7)) * 128 + (((2 * wq + ((lane >> 3) & 1)) ^ (lane & 7)) << 4);
      auto v_blk = [&](int c) {
        uint32_t r[4];
#pragma unroll
        for (int i = 0; i < 2; i++) {
          const float4 u = st[2 * c + i];
          const float* a = av + 8 * c + 4 * i;
          r[2 * i] = pack_bf16(fmaf(-u.x, cv0, a[0]) * u.y, fmaf(-u.z, cv0, a[1]) * u.w);
          r[2 * i + 1] = pack_bf16(fmaf(-u.x, cv1, a[2]) * u.y, fmaf(-u.z, cv1, a[3]) * u.w);
        }
        stsm4t(voff + (c < 4 ? S_V0 : S_V1) * SLOT + (c & 3) * 2048, r[0], r[1], r[2], r[3]);
      };
      auto kv_mma = [&](int c) {
        const uint32_t bo = (c < 4 ? S_V0 : S_V1) * 1024 + w * 512 + (c & 3) * 128;
        const uint64_t bb = mkdesc((d0 + bo) | (((A_ONES >> 4) - bo) << 16), HI_SW128);
        if (c == 0) wgmma_rz_n72<1>(kvp, pa[4 * c], pa[4 * c + 1], pa[4 * c + 2], pa[4 * c + 3], bb);
        else wgmma_rs_n72<1>(kvp, pa[4 * c], pa[4 * c + 1], pa[4 * c + 2], pa[4 * c + 3], bb);
      };
      ld(0); ld(1);
      wg_wait<0>();
      reg_fence(ak); reg_fence(av);
      TLS(0, 2);
      if (!R5) release2(B_E);
      release(B_T0);
      if (LQ) { v_blk(0); ld(2); ld(3); } else { ld(2); ld(3); v_blk(0); }
      ld(4); ld(5); v_blk(1); k_blk(0);
      ld(6); ld(7); v_blk(2); ld(8); ld(9); v_blk(3); k_blk(1);
      ld(10); ld(11); v_blk(4); ld(12); ld(13); v_blk(5); k_blk(2);
      ld(14); ld(15); v_blk(6); v_blk(7); k_blk(3);
      if (RL) { ld(8); ld(9); }
      TLS(0, 3);
      fence_async_smem();
      asm volatile("bar.sync %0, 128;" ::"r"(3 + w) : "memory");
      if (XP == 0) ld_x();
      wg_fence();
      kv_mma(0); kv_mma(1); kv_mma(2); kv_mma(3);
      wg_commit();
#pragma unroll
      for (int c = 4; c < 8; c++) {
        if (RL && c < 7) { ld(2 * c + 2); ld(2 * c + 3); }
        k_blk(c);
        wg_fence();
        kv_mma(c);
        wg_commit();
      }
      if (XP == 3 && (RK == 0 || RK == 9)) ld_x();
      if (QE) { q_step(BAR(B_FQ), 0, SXQ0, QW_SLOTS & 15u); wg_wait<1>(); } else wg_wait<0>();
      reg_fence(kvp);
      auto hand_back = [&]() { release2(B_STG); __syncwarp(); };
      if (!SF) hand_back();
      TLS(0, 4);
      uint4* pp = G.part + b * 544;
      uint32_t pk[8];
#pragma unroll
      for (int j = 0; j < 8; j++) pk[j] = wq >= 2 ? pack_bf16(kvp[16 + 2 * j], kvp[17 + 2 * j]) : pack_bf16(kvp[2 * j], kvp[2 * j + 1]);
      stx4(pp + tid, pk[0], pk[2], pk[4], pk[6]);
      stx4(pp + 256 + tid, pk[1], pk[3], pk[5], pk[7]);
      if (t == 0) stx2(reinterpret_cast<uint2*>(pp + 512) + (tid >> 2), f2x(kvp[32]), f2x(kvp[34]));
      if (SF == 1) hand_back();
      if (XP == 1) ld_x();
      if (!QE) q_step(BAR(B_FQ), 0, SXQ0, QW_SLOTS & 15u);
      if (XP == 2) ld_x();
      if (SF == 2) hand_back();
      if (RK == 0 || RK == 9) {
        uint32_t chk = 0;
#pragma unroll
        for (int j = 0; j < 8; j++) chk ^= xr[4 * j];
        asm volatile("{\n.reg .pred p;\nsetp.eq.u32 p, %0, 0x7FC17FC3;\n@p st.shared.u32 [%1], %0;\n}" ::"r"(chk), "r"(sb + MISC + M_DUM) : "memory");
      }
      const int wd_ = wq * 16 + (lane & 15);
      const uint32_t* src = reinterpret_cast<const uint32_t*>(G.part + ((lane >> 4) * 64 + hg) * 544 + w * 256 + tb * 16) + wd_;
      uint32_t* fin = reinterpret_cast<uint32_t*>(G.fin + hg * 640) + (tb >> 2) * 640 + ((tb >> 1) & 1) * 64 + (tb & 1) * 16 + w * 32 + ((wd_ >> 2) & 3) * 128 + wq * 4 + (wd_ & 3);
      uint32_t v[8];
      auto part_load = [&]() {
#pragma unroll
        for (int i = 0; i < 8; i++) v[i] = ldx1(src + i * 8 * 2176);
      };
#pragma unroll
      for (int k = 1; k < NQ; k++) {
        if (SQ && k == NQ - SQ && w == 1) mbar_wait(BAR(B_GQ), 0);
        q_step(BAR(B_FQ + k), 0, (QX_SLOTS >> (4 * k)) & 15u, (QW_SLOTS >> (4 * k)) & 15u);
        if (SQ && k == NQ - 1 && tid == 0) mbar_arrive(BAR(B_GQ));
        TLS(0, 48 + k);
        if (!MRED && k == PLP) part_load();
        if (!MRED && k == PLC) {
#pragma unroll 1
          for (uint32_t it = 0; it < SPIN_MAX; it++) {
            if (!__any_sync(~0u, max(max(max(v[0], v[1]), max(v[2], v[3])), max(max(v[4], v[5]), max(v[6], v[7]))) == SENT)) break;
            part_load();
          }
          float lo = ((bf_lo(v[0]) + bf_lo(v[1])) + (bf_lo(v[2]) + bf_lo(v[3]))) + ((bf_lo(v[4]) + bf_lo(v[5])) + (bf_lo(v[6]) + bf_lo(v[7])));
          float hi = ((bf_hi(v[0]) + bf_hi(v[1])) + (bf_hi(v[2]) + bf_hi(v[3]))) + ((bf_hi(v[4]) + bf_hi(v[5])) + (bf_hi(v[6]) + bf_hi(v[7])));
          lo += __shfl_xor_sync(~0u, lo, 16); hi += __shfl_xor_sync(~0u, hi, 16);
          if (lane < 16) stx1(fin, pack_bf16(lo, hi));
          TLS(0, 5);
        }
        wg_wait<1>();
        release2(B_EQ + k - 1);
        if (k == RK) { row_stats(); ld_x(); resid(); reg_fence(ao); }
      }
      TLS(0, 13);
      mbar_wait(BAR(B_CQ), 0);
    }
    wg_wait<0>();
    reg_fence(aq);
    TLS(0, 15);
    if (RK == 0 || RK == 9) row_stats();
    const float rl0 = rs0 * 1.4426950408889634f, rl1 = rs1 * 1.4426950408889634f;
    uint32_t pq[32];
#pragma unroll
    for (int j = 0; j < 16; j++) {
      const float2 c = lds_f2(aux + A_CS + (j * 8 + 2 * t) * 4);
      const float* a = aq + 4 * j;
      pq[2 * j] = phi2(fmaf(nm0, c.x, a[0]), rs0, rl0, fmaf(nm0, c.y, a[1]), rs0, rl0);
      pq[2 * j + 1] = phi2(fmaf(nm1, c.x, a[2]), rs1, rl1, fmaf(nm1, c.y, a[3]), rs1, rl1);
    }
    TLS(0, 6);
    if (RK == 9) { resid(); if (RF) reg_fence(ao); }
    mbar_wait_b(BAR(MFIN ? B_KV4 : B_KVB), 0);
    TLS(0, 7);
    uint32_t of[32];
    uint4* mine = G.o + (tb * 32 + hg) * 512 + warp * 64 + g * 4 + (t ^ (g >> 1));
    const uint32_t dW = d0 | (256u << 16);
    auto o_store = [&](int h) {
#pragma unroll
      for (int c = 0; c < 2; c++) stx4(mine + h * 4096 + c * 32, of[8 * h + c], of[8 * h + 2 + c], of[8 * h + 4 + c], of[8 * h + 6 + c]);
    };
    auto out_step = [&](uint32_t slot, const uint32_t* a) {
      const uint32_t d = dW + slot * 1024;
      wg_fence();
#pragma unroll
      for (int kk = 0; kk < 4; kk++) wgmma_rs_n128<1>(ao, a[4 * kk], a[4 * kk + 1], a[4 * kk + 2], a[4 * kk + 3], mkdesc(d + (kk >> 1) * 512 + (kk & 1) * 128, HI_SW128));
      wg_commit();
    };
    uint4 v[NDIR][4];
    auto ld_o = [&](int k) {
      const uint4* p0 = mine + (slab(2 * k, hg) - hg) * 512;
      const uint4* p1 = mine + (slab(2 * k + 1, hg) - hg) * 512;
      v[k][0] = ldx4(p0); v[k][1] = ldx4(p0 + 32); v[k][2] = ldx4(p1); v[k][3] = ldx4(p1 + 32);
    };
    auto ld_all = [&]() {
#pragma unroll
      for (int k = 0; k < NDIR; k++) ld_o(k);
    };
    {
      float oa[4][20];
      const uint32_t dK = (d0 + S_KVB * 1024) | (8u << 16);
      wg_fence();
#pragma unroll
      for (int h = 0; h < 4; h++) {
        wgmma_rz_n40<1>(oa[h], pq[8 * h], pq[8 * h + 1], pq[8 * h + 2], pq[8 * h + 3], mkdesc(dK + h * 160, HI_NOSW));
        wgmma_rs_n40<1>(oa[h], pq[8 * h + 4], pq[8 * h + 5], pq[8 * h + 6], pq[8 * h + 7], mkdesc(dK + h * 160 + 16, HI_NOSW));
        if (h == 0 || h == 3) wg_commit();
      }
      auto norm = [&](int h) {
        const float r0 = rcp(oa[h][16] + 1e-6f), r1 = rcp(oa[h][18] + 1e-6f);
#pragma unroll
        for (int j = 0; j < 4; j++) {
          of[8 * h + 2 * j] = pack_bf16(oa[h][4 * j] * r0, oa[h][4 * j + 1] * r0);
          of[8 * h + 2 * j + 1] = pack_bf16(oa[h][4 * j + 2] * r1, oa[h][4 * j + 3] * r1);
        }
      };
      wg_wait<1>();
      reg_fence(oa[0]);
      norm(0);
      if (LE == 4) ld_all();
      o_store(0);
      if (LE == 3) ld_all();
      TLS(0, 8);
      wg_wait<0>();
      reg_fence(oa[1]); reg_fence(oa[2]); reg_fence(oa[3]);
      TLP_(0);
      release(B_EAUX);
      norm(1);
      if (OS1 == 3) o_store(1);
      if (E7 && NP == 0 && SL7 && hg == 7) o_store(1);
      if (NP == 0) { norm(2); norm(3); }
      if (E7 && NP == 0 && SL7 && hg == 7) { o_store(2); o_store(3); }
      TLP_(1);
      mbar_wait_b(BAR(B_FWO), 0);
      TLP_(2);
      if (RK == 0) resid();
      if (LE == 2) ld_all();
      TLP_(3);
      out_step(WO_SLOTS & 15u, of);
      TLP_(4);
      if (NP == 1) { norm(2); norm(3); }
      if (LE == 1) ld_all();
    }
    if (OS1 == 0) o_store(1);
    mbar_wait(BAR(B_FWO + 1), 0);
    TLP_(5);
    out_step((WO_SLOTS >> 4) & 15u, of + 16);
    TLP_(6);
    const bool early = SL7 && hg == 7;
    if (OS1 == 1 && !(E7 && early)) o_store(1);
    TLP_(7);
    if (early && !E7) { o_store(2); o_store(3); }
    {
      if (DW) __nanosleep(DW);
      if (LE == 0) ld_all();
      if (OS1 == 2 && !(E7 && early)) o_store(1);
#pragma unroll
      for (int k = 0; k < NDIR; k++) {
#pragma unroll 1
        for (uint32_t it = 0; it < SPIN_MAX; it++) {
          if (!__any_sync(~0u, max(max(v[k][0].x, v[k][1].x), max(v[k][2].x, v[k][3].x)) == SENT)) break;
#pragma unroll
          for (int j = k; j < NDIR; j++) ld_o(j);
        }
        TLP_(8);
        const uint32_t a[16] = {v[k][0].x, v[k][1].x, v[k][0].y, v[k][1].y, v[k][0].z, v[k][1].z, v[k][0].w, v[k][1].w,
                                v[k][2].x, v[k][3].x, v[k][2].y, v[k][3].y, v[k][2].z, v[k][3].z, v[k][2].w, v[k][3].w};
        mbar_wait(BAR(B_FWO + 2 + k), 0);
        TLS(0, 34 + k);
        out_step((WO_SLOTS >> (8 + 4 * k)) & 15u, a);
        TLP_(9);
        if (k) { wg_wait<1>(); release2(B_EO); }
      }
      if (!early) o_store(2);
    }
    auto routed = [&]() {
      mbar_wait(BAR(B_MOE), 0);
      const float2 kk = lds_f2(sb + MISC + M_IDX + t * 8);
      const int k0 = (int)(~__float_as_uint(kk.x) & 2047u) - tb * 128, k1 = (int)(~__float_as_uint(kk.y) & 2047u) - tb * 128;
      if (NUNIT && __any_sync(~0u, (k0 >> 6) == w || (k1 >> 6) == w)) {
        const uint32_t a0 = (k0 == row0 ? 0x3F80u : 0u) | (k1 == row0 ? 0x3F800000u : 0u);
        const uint32_t a1 = (k0 == row0 + 8 ? 0x3F80u : 0u) | (k1 == row0 + 8 ? 0x3F800000u : 0u);
        wg_fence();
        wgmma_rs_n128<1>(ao, a0, a1, 0u, 0u, mkdesc((d0 + ((MISC + M_MOE) >> 4)) | (64u << 16), 0x40000000u));
        wg_commit();
      }
    };
    auto out_half = [&](int h, const float* v) {
      const uint32_t ost = sb + (w ? S_D1 : S_D0) * SLOT + wq * 4096 + h * 2048;
#pragma unroll
      for (int j = 0; j < 8; j += 2)
        stsm4(ost + ((moff & 2047) ^ (j << 4)), pack_bf16(v[4 * j], v[4 * j + 1]), pack_bf16(v[4 * j + 2], v[4 * j + 3]),
              pack_bf16(v[4 * j + 4], v[4 * j + 5]), pack_bf16(v[4 * j + 6], v[4 * j + 7]));
      fence_async_smem();
      __syncwarp();
      if (elect_one()) {
        asm volatile("cp.async.bulk.tensor.2d.global.shared::cta.bulk_group [%0, {%2, %3}], [%1];" ::"l"(&tmOut), "r"(ost), "r"(hg * 128 + h * 64), "r"(tb * 128 + warp * 16) : "memory");
        if (h) asm volatile("cp.async.bulk.commit_group;\ncp.async.bulk.wait_group.read 0;" ::: "memory");
      }
      __syncwarp();
    };
    bool done = false;
    {
      const uint32_t dO = (d0 + w * 256) | (1u << 16);
      auto step = [&](int i, int r, int p, uint32_t as, uint32_t ws) {
        mbar_wait(BAR(B_FWO + i), 0);
        mbar_wait(BAR(B_VAL + r), p);
        TLS(0, 32 + i);
        const uint32_t da = dO + as * 1024, db = dW + ws * 1024;
        wg_fence();
#pragma unroll
        for (int kk = 0; kk < 4; kk++)
          wgmma_ss_n128<0, 1>(ao, mkdesc(da + (kk >> 1) * 512 + (kk & 1) * 2, HI_SW64), mkdesc(db + (kk >> 1) * 512 + (kk & 1) * 128, HI_SW128));
        wg_commit();
      };
      uint64_t tbl = WO_SLOTS >> (4 * I0);
      int r = 0, p = 0, rp = 0;
#pragma unroll 1
      for (int i = I0; i < 12; i++) {
        step(i, r, p, (A_SLOTS >> (4 * r)) & 15u, (uint32_t)tbl & 15u);
        tbl >>= 4;
#pragma unroll
        for (int c = 0; c < 2; c++)
          if (i == OS3 + c && !early) stx4(mine + 3 * 4096 + c * 32, of[24 + c], of[26 + c], of[28 + c], of[30 + c]);
        wg_wait<1>();
        if (i > I0) release(B_EA + rp);
        rp = r;
        if (++r == NA) { r = 0; p ^= 1; }
        if (i >= 3 && i <= 9) release2(B_EO + i - 3);
      }
      if (SPL && w == 1) {
        float bl[32], bh[32];
        mbar_wait(BAR(B_GO), 0);
        routed();
#pragma unroll
        for (int h = 0; h < 2; h++) {
#pragma unroll
          for (int i = 12; i < 16; i++) {
            const int r_ = (i - I0) % NA;
            if (h == 0) { mbar_wait(BAR(B_FWO + i), 0); mbar_wait(BAR(B_VAL + r_), ((i - I0) / NA) & 1); }
            const uint32_t da = dO + ((A_SLOTS >> (4 * r_)) & 15u) * 1024, db = dW + ((uint32_t)(WO_SLOTS >> (4 * i)) & 15u) * 1024 + h * 256;
            if (h == 0 || i == 12) wg_fence();
#pragma unroll
            for (int kk = 0; kk < 4; kk++) {
              const uint64_t a = mkdesc(da + (kk >> 1) * 512 + (kk & 1) * 2, HI_SW64), bb = mkdesc(db + (kk >> 1) * 512 + (kk & 1) * 128, HI_SW128);
              if (i == 12 && kk == 0) wgmma_sz_n64<0, 1>(h ? bh : bl, a, bb); else wgmma_ss_n64<0, 1>(h ? bh : bl, a, bb);
            }
          }
          wg_commit();
        }
        wg_wait<1>();
        reg_fence(ao); reg_fence(bl);
#pragma unroll
        for (int j = 0; j < 32; j++) bl[j] += ao[j];
        out_half(0, bl);
        wg_wait<0>();
        reg_fence(bh);
#pragma unroll
        for (int j = 0; j < 32; j++) bh[j] += ao[32 + j];
        out_half(1, bh);
        done = true;
      } else
#pragma unroll
      for (int i = 12; i < 16; i++) {
        if (i == 16 - STAG && w == 1) mbar_wait(BAR(B_GO), 0);
        step(i, (i - I0) % NA, ((i - I0) / NA) & 1, (A_SLOTS >> (4 * ((i - I0) % NA))) & 15u, (uint32_t)(WO_SLOTS >> (4 * i)) & 15u);
        if (STAG && i == 15 - GOE && tid == 0) mbar_arrive(BAR(B_GO));
      }
    }
    if (!done) {
      routed();
      wg_wait<0>();
      reg_fence(ao);
      TLS(0, 10);
      out_half(0, ao);
      out_half(1, ao + 32);
    }
    TLS(0, 11);
    TLS(128, 9);
  }
}

typedef CUresult (*EncFn)(CUtensorMap*, CUtensorMapDataType, cuuint32_t, void*, const cuuint64_t*, const cuuint64_t*, const cuuint32_t*,
                          const cuuint32_t*, CUtensorMapInterleave, CUtensorMapSwizzle, CUtensorMapL2promotion, CUtensorMapFloatOOBfill);

void make_map2(EncFn enc, CUtensorMap* m, void* p, uint64_t rows, uint64_t cols, uint32_t brows, CUtensorMapL2promotion promo) {
  cuuint64_t gd[2] = {cols, rows}, gs[1] = {cols * 2};
  cuuint32_t bd[2] = {64, brows}, es[2] = {1, 1};
  enc(m, CU_TENSOR_MAP_DATA_TYPE_BFLOAT16, 2, p, gd, gs, bd, es, CU_TENSOR_MAP_INTERLEAVE_NONE, CU_TENSOR_MAP_SWIZZLE_128B, promo,
      CU_TENSOR_MAP_FLOAT_OOB_FILL_NONE);
}
void make_map3(EncFn enc, CUtensorMap* m, void* p, uint64_t rows, uint64_t cols, uint32_t brows) {
  cuuint64_t gd[3] = {64, rows, cols / 64}, gs[2] = {cols * 2, 128};
  cuuint32_t bd[3] = {64, brows, 2}, es[3] = {1, 1, 1};
  enc(m, CU_TENSOR_MAP_DATA_TYPE_BFLOAT16, 3, p, gd, gs, bd, es, CU_TENSOR_MAP_INTERLEAVE_NONE, CU_TENSOR_MAP_SWIZZLE_128B,
      CU_TENSOR_MAP_L2_PROMOTION_L2_256B, CU_TENSOR_MAP_FLOAT_OOB_FILL_NONE);
}

}

extern "C" void kernel_launch(void* const* d_in, const int* in_sizes, int n_in, void* d_out, int out_size) {
  static EncFn enc = nullptr;
  static int by_sm = 0;
  if (!enc) {
    void* fn = nullptr;
    cudaDriverEntryPointQueryResult qr;
    cudaGetDriverEntryPoint("cuTensorMapEncodeTiled", &fn, cudaEnableDefault, &qr);
    enc = (EncFn)fn;
    int dev = 0, sms = 0;
    cudaGetDevice(&dev);
    cudaDeviceGetAttribute(&sms, cudaDevAttrMultiProcessorCount, dev);
    by_sm = MAP == 2 && sms == NCTA + NSVC;
    cudaFuncSetAttribute(fused_kernel, cudaFuncAttributeMaxDynamicSharedMemorySize, SMEM_BYTES);
  }
  CUtensorMap tmX, tmW, tmWo, tmOut, tmG, tmU, tmD, tmR, tmWp;
  {
    cuuint64_t gd[5] = {64, 2, 128, 4, 16}, gs[4] = {2048, 16384, 4096, 128};
    cuuint32_t bd[5] = {64, 2, 4, 4, 2}, es[5] = {1, 1, 1, 1, 1};
    enc(&tmWp, CU_TENSOR_MAP_DATA_TYPE_BFLOAT16, 5, d_in[2], gd, gs, bd, es, CU_TENSOR_MAP_INTERLEAVE_NONE, CU_TENSOR_MAP_SWIZZLE_128B,
        CU_TENSOR_MAP_L2_PROMOTION_L2_256B, CU_TENSOR_MAP_FLOAT_OOB_FILL_NONE);
  }
  make_map2(enc, &tmR, d_in[0], SEQ, DM, 1, CU_TENSOR_MAP_L2_PROMOTION_L2_128B);
  make_map2(enc, &tmX, d_in[0], SEQ, DM, 128, XPROMO);
  make_map3(enc, &tmW, d_in[1], DM, 3 * DM, 64);
  make_map3(enc, &tmWo, d_in[2], DM, DM, 32);
  if (OUTV) make_map2(enc, &tmOut, d_out, SEQ, DM, 16, CU_TENSOR_MAP_L2_PROMOTION_L2_128B); else make_map3(enc, &tmOut, d_out, SEQ, DM, 64);
  make_map2(enc, &tmG, d_in[5], DM, FF, 64, MPROMO);
  make_map2(enc, &tmU, d_in[6], DM, FF, 64, MPROMO);
  make_map2(enc, &tmD, d_in[7], FF, DM, 64, MPROMO);
  typedef const __nv_bfloat16* P;
  cudaLaunchConfig_t cfg = {};
  cfg.gridDim = dim3(NCTA + NSVC); cfg.blockDim = dim3(512); cfg.dynamicSmemBytes = SMEM_BYTES; cfg.stream = cudaStreamPerThread;
  cudaLaunchAttribute at[1];
  at[0].id = cudaLaunchAttributeClusterDimension;
  at[0].val.clusterDim.x = 2; at[0].val.clusterDim.y = 1; at[0].val.clusterDim.z = 1;
  cfg.attrs = at; cfg.numAttrs = 1;
  cudaLaunchKernelEx(&cfg, fused_kernel, (P)d_in[0], (P)d_in[1], (P)d_in[2], (P)d_in[4], (P)d_in[7], by_sm, tmX, tmW, tmWo, tmOut, tmG, tmU, tmD, tmR, tmWp);
}
```

```cpp
#include <cuda_runtime.h>
#include <cuda.h>
#include <cuda_bf16.h>
#include <stdint.h>

namespace {

template <int TA, int TB> __device__ __forceinline__ void wgmma_ss_n128(float (&d)[64], uint64_t da, uint64_t db) {
  asm volatile("wgmma.mma_async.sync.aligned.m64n128k16.f32.bf16.bf16 "
  "{%0,%1,%2,%3,%4,%5,%6,%7,%8,%9,%10,%11,%12,%13,%14,%15,%16,%17,%18,%19,%20,%21,%22,%23,%24,%25,%26,%27,%28,%29,%30,%31,%32,%33,%34,%35,%36,%37,%38,%39,%40,%41,%42,%43,%44,%45,%46,%47,%48,%49,%50,%51,%52,%53,%54,%55,%56,%57,%58,%59,%60,%61,%62,%63}, "
  "%64, %65, 1, 1, 1, %66, %67;"
  : "+f"(d[0]),"+f"(d[1]),"+f"(d[2]),"+f"(d[3]),"+f"(d[4]),"+f"(d[5]),"+f"(d[6]),"+f"(d[7]),"+f"(d[8]),"+f"(d[9]),"+f"(d[10]),"+f"(d[11]),"+f"(d[12]),"+f"(d[13]),"+f"(d[14]),"+f"(d[15]),"+f"(d[16]),"+f"(d[17]),"+f"(d[18]),"+f"(d[19]),"+f"(d[20]),"+f"(d[21]),"+f"(d[22]),"+f"(d[23]),"+f"(d[24]),"+f"(d[25]),"+f"(d[26]),"+f"(d[27]),"+f"(d[28]),"+f"(d[29]),"+f"(d[30]),"+f"(d[31]),"+f"(d[32]),"+f"(d[33]),"+f"(d[34]),"+f"(d[35]),"+f"(d[36]),"+f"(d[37]),"+f"(d[38]),"+f"(d[39]),"+f"(d[40]),"+f"(d[41]),"+f"(d[42]),"+f"(d[43]),"+f"(d[44]),"+f"(d[45]),"+f"(d[46]),"+f"(d[47]),"+f"(d[48]),"+f"(d[49]),"+f"(d[50]),"+f"(d[51]),"+f"(d[52]),"+f"(d[53]),"+f"(d[54]),"+f"(d[55]),"+f"(d[56]),"+f"(d[57]),"+f"(d[58]),"+f"(d[59]),"+f"(d[60]),"+f"(d[61]),"+f"(d[62]),"+f"(d[63])
  : "l"(da), "l"(db), "n"(TA), "n"(TB));
}
template <int TA, int TB> __device__ __forceinline__ void wgmma_ss_n64(float (&d)[32], uint64_t da, uint64_t db) {
  asm volatile("wgmma.mma_async.sync.aligned.m64n64k16.f32.bf16.bf16 "
  "{%0,%1,%2,%3,%4,%5,%6,%7,%8,%9,%10,%11,%12,%13,%14,%15,%16,%17,%18,%19,%20,%21,%22,%23,%24,%25,%26,%27,%28,%29,%30,%31}, "
  "%32, %33, 1, 1, 1, %34, %35;"
  : "+f"(d[0]),"+f"(d[1]),"+f"(d[2]),"+f"(d[3]),"+f"(d[4]),"+f"(d[5]),"+f"(d[6]),"+f"(d[7]),"+f"(d[8]),"+f"(d[9]),"+f"(d[10]),"+f"(d[11]),"+f"(d[12]),"+f"(d[13]),"+f"(d[14]),"+f"(d[15]),"+f"(d[16]),"+f"(d[17]),"+f"(d[18]),"+f"(d[19]),"+f"(d[20]),"+f"(d[21]),"+f"(d[22]),"+f"(d[23]),"+f"(d[24]),"+f"(d[25]),"+f"(d[26]),"+f"(d[27]),"+f"(d[28]),"+f"(d[29]),"+f"(d[30]),"+f"(d[31])
  : "l"(da), "l"(db), "n"(TA), "n"(TB));
}
template <int TA, int TB> __device__ __forceinline__ void wgmma_sz_n64(float (&d)[32], uint64_t da, uint64_t db) {
  asm volatile("wgmma.mma_async.sync.aligned.m64n64k16.f32.bf16.bf16 "
  "{%0,%1,%2,%3,%4,%5,%6,%7,%8,%9,%10,%11,%12,%13,%14,%15,%16,%17,%18,%19,%20,%21,%22,%23,%24,%25,%26,%27,%28,%29,%30,%31}, "
  "%32, %33, 0, 1, 1, %34, %35;"
  : "=f"(d[0]),"=f"(d[1]),"=f"(d[2]),"=f"(d[3]),"=f"(d[4]),"=f"(d[5]),"=f"(d[6]),"=f"(d[7]),"=f"(d[8]),"=f"(d[9]),"=f"(d[10]),"=f"(d[11]),"=f"(d[12]),"=f"(d[13]),"=f"(d[14]),"=f"(d[15]),"=f"(d[16]),"=f"(d[17]),"=f"(d[18]),"=f"(d[19]),"=f"(d[20]),"=f"(d[21]),"=f"(d[22]),"=f"(d[23]),"=f"(d[24]),"=f"(d[25]),"=f"(d[26]),"=f"(d[27]),"=f"(d[28]),"=f"(d[29]),"=f"(d[30]),"=f"(d[31])
  : "l"(da), "l"(db), "n"(TA), "n"(TB));
}
template <int TB> __device__ __forceinline__ void wgmma_rs_n72(float (&d)[36], uint32_t a0, uint32_t a1, uint32_t a2, uint32_t a3, uint64_t db) {
  asm volatile("wgmma.mma_async.sync.aligned.m64n72k16.f32.bf16.bf16 "
  "{%0,%1,%2,%3,%4,%5,%6,%7,%8,%9,%10,%11,%12,%13,%14,%15,%16,%17,%18,%19,%20,%21,%22,%23,%24,%25,%26,%27,%28,%29,%30,%31,%32,%33,%34,%35}, "
  "{%36,%37,%38,%39}, %40, 1, 1, 1, %41;"
  : "+f"(d[0]),"+f"(d[1]),"+f"(d[2]),"+f"(d[3]),"+f"(d[4]),"+f"(d[5]),"+f"(d[6]),"+f"(d[7]),"+f"(d[8]),"+f"(d[9]),"+f"(d[10]),"+f"(d[11]),"+f"(d[12]),"+f"(d[13]),"+f"(d[14]),"+f"(d[15]),"+f"(d[16]),"+f"(d[17]),"+f"(d[18]),"+f"(d[19]),"+f"(d[20]),"+f"(d[21]),"+f"(d[22]),"+f"(d[23]),"+f"(d[24]),"+f"(d[25]),"+f"(d[26]),"+f"(d[27]),"+f"(d[28]),"+f"(d[29]),"+f"(d[30]),"+f"(d[31]),"+f"(d[32]),"+f"(d[33]),"+f"(d[34]),"+f"(d[35])
  : "r"(a0), "r"(a1), "r"(a2), "r"(a3), "l"(db), "n"(TB));
}
template <int TB> __device__ __forceinline__ void wgmma_rz_n72(float (&d)[36], uint32_t a0, uint32_t a1, uint32_t a2, uint32_t a3, uint64_t db) {
  asm volatile("wgmma.mma_async.sync.aligned.m64n72k16.f32.bf16.bf16 "
  "{%0,%1,%2,%3,%4,%5,%6,%7,%8,%9,%10,%11,%12,%13,%14,%15,%16,%17,%18,%19,%20,%21,%22,%23,%24,%25,%26,%27,%28,%29,%30,%31,%32,%33,%34,%35}, "
  "{%36,%37,%38,%39}, %40, 0, 1, 1, %41;"
  : "=f"(d[0]),"=f"(d[1]),"=f"(d[2]),"=f"(d[3]),"=f"(d[4]),"=f"(d[5]),"=f"(d[6]),"=f"(d[7]),"=f"(d[8]),"=f"(d[9]),"=f"(d[10]),"=f"(d[11]),"=f"(d[12]),"=f"(d[13]),"=f"(d[14]),"=f"(d[15]),"=f"(d[16]),"=f"(d[17]),"=f"(d[18]),"=f"(d[19]),"=f"(d[20]),"=f"(d[21]),"=f"(d[22]),"=f"(d[23]),"=f"(d[24]),"=f"(d[25]),"=f"(d[26]),"=f"(d[27]),"=f"(d[28]),"=f"(d[29]),"=f"(d[30]),"=f"(d[31]),"=f"(d[32]),"=f"(d[33]),"=f"(d[34]),"=f"(d[35])
  : "r"(a0), "r"(a1), "r"(a2), "r"(a3), "l"(db), "n"(TB));
}
template <int TB> __device__ __forceinline__ void wgmma_rs_n40(float (&d)[20], uint32_t a0, uint32_t a1, uint32_t a2, uint32_t a3, uint64_t db) {
  asm volatile("wgmma.mma_async.sync.aligned.m64n40k16.f32.bf16.bf16 "
  "{%0,%1,%2,%3,%4,%5,%6,%7,%8,%9,%10,%11,%12,%13,%14,%15,%16,%17,%18,%19}, "
  "{%20,%21,%22,%23}, %24, 1, 1, 1, %25;"
  : "+f"(d[0]),"+f"(d[1]),"+f"(d[2]),"+f"(d[3]),"+f"(d[4]),"+f"(d[5]),"+f"(d[6]),"+f"(d[7]),"+f"(d[8]),"+f"(d[9]),"+f"(d[10]),"+f"(d[11]),"+f"(d[12]),"+f"(d[13]),"+f"(d[14]),"+f"(d[15]),"+f"(d[16]),"+f"(d[17]),"+f"(d[18]),"+f"(d[19])
  : "r"(a0), "r"(a1), "r"(a2), "r"(a3), "l"(db), "n"(TB));
}
template <int TB> __device__ __forceinline__ void wgmma_rz_n40(float (&d)[20], uint32_t a0, uint32_t a1, uint32_t a2, uint32_t a3, uint64_t db) {
  asm volatile("wgmma.mma_async.sync.aligned.m64n40k16.f32.bf16.bf16 "
  "{%0,%1,%2,%3,%4,%5,%6,%7,%8,%9,%10,%11,%12,%13,%14,%15,%16,%17,%18,%19}, "
  "{%20,%21,%22,%23}, %24, 0, 1, 1, %25;"
  : "=f"(d[0]),"=f"(d[1]),"=f"(d[2]),"=f"(d[3]),"=f"(d[4]),"=f"(d[5]),"=f"(d[6]),"=f"(d[7]),"=f"(d[8]),"=f"(d[9]),"=f"(d[10]),"=f"(d[11]),"=f"(d[12]),"=f"(d[13]),"=f"(d[14]),"=f"(d[15]),"=f"(d[16]),"=f"(d[17]),"=f"(d[18]),"=f"(d[19])
  : "r"(a0), "r"(a1), "r"(a2), "r"(a3), "l"(db), "n"(TB));
}
template <int TB> __device__ __forceinline__ void wgmma_rs_n128(float (&d)[64], uint32_t a0, uint32_t a1, uint32_t a2, uint32_t a3, uint64_t db) {
  asm volatile("wgmma.mma_async.sync.aligned.m64n128k16.f32.bf16.bf16 "
  "{%0,%1,%2,%3,%4,%5,%6,%7,%8,%9,%10,%11,%12,%13,%14,%15,%16,%17,%18,%19,%20,%21,%22,%23,%24,%25,%26,%27,%28,%29,%30,%31,%32,%33,%34,%35,%36,%37,%38,%39,%40,%41,%42,%43,%44,%45,%46,%47,%48,%49,%50,%51,%52,%53,%54,%55,%56,%57,%58,%59,%60,%61,%62,%63}, "
  "{%64,%65,%66,%67}, %68, 1, 1, 1, %69;"
  : "+f"(d[0]),"+f"(d[1]),"+f"(d[2]),"+f"(d[3]),"+f"(d[4]),"+f"(d[5]),"+f"(d[6]),"+f"(d[7]),"+f"(d[8]),"+f"(d[9]),"+f"(d[10]),"+f"(d[11]),"+f"(d[12]),"+f"(d[13]),"+f"(d[14]),"+f"(d[15]),"+f"(d[16]),"+f"(d[17]),"+f"(d[18]),"+f"(d[19]),"+f"(d[20]),"+f"(d[21]),"+f"(d[22]),"+f"(d[23]),"+f"(d[24]),"+f"(d[25]),"+f"(d[26]),"+f"(d[27]),"+f"(d[28]),"+f"(d[29]),"+f"(d[30]),"+f"(d[31]),"+f"(d[32]),"+f"(d[33]),"+f"(d[34]),"+f"(d[35]),"+f"(d[36]),"+f"(d[37]),"+f"(d[38]),"+f"(d[39]),"+f"(d[40]),"+f"(d[41]),"+f"(d[42]),"+f"(d[43]),"+f"(d[44]),"+f"(d[45]),"+f"(d[46]),"+f"(d[47]),"+f"(d[48]),"+f"(d[49]),"+f"(d[50]),"+f"(d[51]),"+f"(d[52]),"+f"(d[53]),"+f"(d[54]),"+f"(d[55]),"+f"(d[56]),"+f"(d[57]),"+f"(d[58]),"+f"(d[59]),"+f"(d[60]),"+f"(d[61]),"+f"(d[62]),"+f"(d[63])
  : "r"(a0), "r"(a1), "r"(a2), "r"(a3), "l"(db), "n"(TB));
}
template <int TA, int TB> __device__ __forceinline__ void wgmma_ss_n8(float (&d)[4], uint64_t da, uint64_t db) {
  asm volatile("wgmma.mma_async.sync.aligned.m64n8k16.f32.bf16.bf16 "
  "{%0,%1,%2,%3}, "
  "%4, %5, 1, 1, 1, %6, %7;"
  : "+f"(d[0]),"+f"(d[1]),"+f"(d[2]),"+f"(d[3])
  : "l"(da), "l"(db), "n"(TA), "n"(TB));
}
template <int TA, int TB> __device__ __forceinline__ void wgmma_ss_n16(float (&d)[8], uint64_t da, uint64_t db) {
  asm volatile("wgmma.mma_async.sync.aligned.m64n16k16.f32.bf16.bf16 "
  "{%0,%1,%2,%3,%4,%5,%6,%7}, "
  "%8, %9, 1, 1, 1, %10, %11;"
  : "+f"(d[0]),"+f"(d[1]),"+f"(d[2]),"+f"(d[3]),"+f"(d[4]),"+f"(d[5]),"+f"(d[6]),"+f"(d[7])
  : "l"(da), "l"(db), "n"(TA), "n"(TB));
}

constexpr int SEQ = 2048, DM = 1024, FF = 3584;
constexpr int NCTA = 128, NSVC = 4;
constexpr int NUNIT = 112;
constexpr uint32_t SLOT = 16384;
constexpr uint32_t MISC = 14 * SLOT;
constexpr uint32_t SMEM_BYTES = MISC + 3072;
constexpr uint32_t M_MOE = 0;
constexpr uint32_t M_BAR = 2048;
constexpr uint32_t M_DUM = 2048 + 1020;
constexpr uint32_t M_IDX = 2048 + 768;
constexpr uint32_t M_KEY = 2048 + 960;
#define R5 1
#define NQ (R5 ? 6 : 5)
constexpr int NF = 16 - NQ, NR = (NQ == 5 || R5) ? 4 : 3;
constexpr int B_FXQ = 0, B_FKV = 3, B_AST = 6, B_MOE = 7, B_MF = 8  , B_CQ = 12, B_XS = 13, B_DF = 14, B_ZOK = 15, B_FWO = 21  , B_FQ = B_FWO - NQ,
              B_UP = 37, B_FIN = 38, B_KVB = 39, B_ME = 40  , B_HF = 44, B_AF = 45  , B_AR = 50  , B_GO = 52,
              B_FAUX = 53, B_EAUX = 54, B_T0 = 55, B_DE = 56, B_EA = 57  , B_VAL = 62  ,
              B_E = 67  , B_STG = 70, B_EQ = 71  , B_EO = 76  , NBAR = 83, B_KV4 = 83, B_MS = 84,
              B_FV = 85  , B_EK = 88  , B_GQ = 91, B_GT = 92;
constexpr uint32_t MT = 9216, A_ONES = 12 * SLOT + 3 * MT, A_CS = A_ONES + 2048, A_ST = A_CS + 1536;
constexpr uint32_t A_TL = MISC + 2048 + 808;
constexpr int S_V0 = R5 ? 7 : 11, S_V1 = R5 ? 9 : 7;
constexpr uint32_t K_SLOTS = 0x8697A8u, V_SLOTS = 0x97A869u;
constexpr int C_B = 0, C_DONE = 32, NCNT = 2;
constexpr uint32_t QX_SLOTS = NQ == 5 ? 0x43102u : 0x354021u;
constexpr uint32_t QW_SLOTS = R5 ? 0xA9786Au : 0xB76A98u;
constexpr uint32_t qx(int k) { return (QX_SLOTS >> (4 * k)) & 15u; }
constexpr uint32_t qw(int k) { return (QW_SLOTS >> (4 * k)) & 15u; }
constexpr uint32_t S_KVB = R5 ? 1 : 8, S_D0 = R5 ? 11 : (NQ == 5 ? 5 : 1), S_D1 = R5 ? 2 : (NQ == 5 ? 11 : 2);
constexpr uint32_t S_M3 = R5 ? 11 : 5;
constexpr int WQ0 = NQ == 5 ? 1 : 3;
constexpr uint32_t wo_slot_c(int i) { return i >= 9 ? wo_slot_c(i - 9) : (i == 7 ? S_D0 : (i == 8 ? S_D1 : (((i & 1) || i + WQ0 == 1) ? qx((i + WQ0) >> 1) : qw((i + WQ0) >> 1)))); }
constexpr uint64_t wo_slots() { uint64_t t = 0; for (int i = 0; i < 16; i++) t |= (uint64_t)wo_slot_c(i) << (4 * i); return t; }
constexpr uint64_t WO_SLOTS = wo_slots();
constexpr uint32_t A_SLOTS = 0xDC000u | (S_KVB << 8) | (qw(NQ - 1) << 4) | qx(NQ - 1);
constexpr uint32_t SX14 = qx(NQ - 2), SX15 = qx(NQ - 1), SXQ0 = qx(0);
#define WOD 2
#define PLC 3
#define PFG1 10
#define PFNS1 150
#define PFG0 3
#define RS0 0
#define WPF 1
#define POLLNS 150
#define SVNS 100
#define MPROMO CU_TENSOR_MAP_L2_PROMOTION_L2_128B
#define MW0 0
#define PFILL 0
#define H2W (NQ - 3)
#define TOPW 1000
#define PFT 0
#define SV0 2
#define SV0A 14
#define SV0B 22
#define ASTE 2
#define PFS 1
#define PFTAB 0x0012222220000ull
#define HW 0
#define DPF 1
#define PROBE 0x8
#define OS1 0
#define YW 0
#define OS2 3
#define NOVAL 0
#define NDIR 1
#define I0 (2 + NDIR)
#define DW 0
#define OSP 1
#define NA 5
#define STAG 4
#define GOE 0
#define SVP 99
#define KEY1 0
#define HYB 0
#define DV 0
#define DVJ 4
#define DVK 10
#define FW 0
#define E1E 1
#define GATE 0
#define SVD 0
#define XPROMO CU_TENSOR_MAP_L2_PROMOTION_L2_128B
#define MC0 3
#define MX 0
#define OUTV 1
#define BW0 2
#define QL 1
#define NP 0
#define FINCP 0
#define DNS 0
#define WOK 99
#define WOD1 2
#define SVT 64
#define MRED 1
#define MRW -1
#define ST 0
#define RW 0
#define FMC 0
#define KS 7
#define SQ 2
#define H2D 200
#define MRD 300
#define STP 0
#define TPNS 50
#define DLP 0
#define MFIN 0
#define MFD 300
#define SF 1
#define PH MFIN
#define RSL 0
#define PFW 3000
#define KVE 1
#define P2NS 0
#define OS3 4
#define PLP 2
#define FINJ 9
#define PFD 0
#define PFG 3
#define PFNS2 150
#define PFNS 250
#define MAP 2
#define RSNS 60
#define SVS 6
#define PRODLATE 0
#define MC 7
#define QE 0
#define TMP 1
#define TMPW 4
#define DS 15
#define RL 0
#define EV 0
#define LQ 0
#define SPL 0
#define HALFST 0
#define PHI2 1
#define E7 1
#define RF 1
#define RK 0
#define LE 1
#define SL7 0
#define XP 3
#define VR 4
#define KEEP 1
#define KP 4
#define KC 1
#define MS 0
constexpr int CON_REGS = 224, MOE_REGS = 40, PROD_REGS = 24;
constexpr uint32_t SPIN_MAX = 2000000;
constexpr uint32_t SENT = 0xFFFFFFFFu;

struct __align__(128) Scratch {
  uint4 o[NCTA * 2048];
  uint4 part[NCTA * 544];
  uint4 fin[8 * 640];
  float2 stats[SEQ];
  uint32_t key[SEQ];
  uint32_t cs[3 * DM];
  uint4 y[NCTA * 128];
  uint32_t h[56 * 256];
  uint32_t top[128];
  uint32_t cnt[NCNT * 32];
};
__device__ Scratch G;
#define TLS(th, i)
#define TLP_(i)
#define TLG(i)
#define TLDUMP()

__device__ __forceinline__ bool elect_one() {
  uint32_t p;
  asm volatile("{\n.reg .pred P;\nelect.sync _|P, 0xffffffff;\nselp.b32 %0, 1, 0, P;\n}" : "=r"(p));
  return p;
}
__device__ __forceinline__ void mbar_init(uint32_t b, uint32_t c) { asm volatile("mbarrier.init.shared::cta.b64 [%0], %1;" ::"r"(b), "r"(c) : "memory"); }
__device__ __forceinline__ void mbar_expect_tx(uint32_t b, uint32_t bytes) { asm volatile("mbarrier.arrive.expect_tx.shared::cta.b64 _, [%0], %1;" ::"r"(b), "r"(bytes) : "memory"); }
__device__ __forceinline__ void mbar_arrive(uint32_t b) { asm volatile("mbarrier.arrive.shared::cta.b64 _, [%0];" ::"r"(b) : "memory"); }
__device__ __forceinline__ void mbar_wait_b(uint32_t b, uint32_t parity) {
  asm volatile(
      "{\n.reg .pred p;\n.reg .u32 cnt;\nmov.u32 cnt, 0;\n"
      "LW:\nmbarrier.try_wait.parity.shared::cta.b64 p, [%0], %1;\n@p bra LD;\n"
      "add.u32 cnt, cnt, 1;\nsetp.lt.u32 p, cnt, 4000000;\n@p bra LW;\ntrap;\nLD:\n}" ::"r"(b), "r"(parity) : "memory");
}
__device__ __forceinline__ void mbar_wait(uint32_t b, uint32_t parity) {
  asm volatile("{\n.reg .pred p;\nLW:\nmbarrier.try_wait.parity.shared::cta.b64 p, [%0], %1;\n@!p bra LW;\n}" ::"r"(b), "r"(parity) : "memory");
}
__device__ __forceinline__ bool mbar_test(uint32_t b, uint32_t parity) {
  uint32_t r;
  asm volatile("{\n.reg .pred p;\nmbarrier.test_wait.parity.shared::cta.b64 p, [%1], %2;\nselp.b32 %0, 1, 0, p;\n}" : "=r"(r) : "r"(b), "r"(parity) : "memory");
  return r;
}
__device__ __forceinline__ uint32_t ev_arrive(uint32_t a) { uint32_t r; asm volatile("atom.shared.add.u32 %0, [%1], 1;" : "=r"(r) : "r"(a) : "memory"); return r; }
__device__ __forceinline__ void tma2d(uint32_t dst, const CUtensorMap* m, int c0, int c1, uint32_t bar) {
  asm volatile("cp.async.bulk.tensor.2d.shared::cluster.global.mbarrier::complete_tx::bytes [%0], [%1, {%3, %4}], [%2];" ::"r"(dst), "l"(m), "r"(bar), "r"(c0), "r"(c1) : "memory");
}
__device__ __forceinline__ void tma3d(uint32_t dst, const CUtensorMap* m, int c1, int c2, uint32_t bar) {
  asm volatile("cp.async.bulk.tensor.3d.shared::cluster.global.mbarrier::complete_tx::bytes [%0], [%1, {%3, %4, %5}], [%2];" ::"r"(dst), "l"(m), "r"(bar), "r"(0), "r"(c1), "r"(c2) : "memory");
}
__device__ __forceinline__ void tma3d_mc(uint32_t dst, const CUtensorMap* m, int c1, int c2, uint32_t bar) {
  asm volatile("cp.async.bulk.tensor.3d.shared::cluster.global.mbarrier::complete_tx::bytes.multicast::cluster [%0], [%1, {%3, %4, %5}], [%2], %6;" ::"r"(dst), "l"(m), "r"(bar), "r"(0), "r"(c1), "r"(c2), "h"((uint16_t)3) : "memory");
}
__device__ __forceinline__ void tma5d(uint32_t dst, const CUtensorMap* m, int c2, int c4, uint32_t bar, bool mc) {
  if (mc) asm volatile("cp.async.bulk.tensor.5d.shared::cluster.global.mbarrier::complete_tx::bytes.multicast::cluster [%0], [%1, {%3, %3, %4, %3, %5}], [%2], %6;" ::"r"(dst), "l"(m), "r"(bar), "r"(0), "r"(c2), "r"(c4), "h"((uint16_t)3) : "memory");
  else asm volatile("cp.async.bulk.tensor.5d.shared::cluster.global.mbarrier::complete_tx::bytes [%0], [%1, {%3, %3, %4, %3, %5}], [%2];" ::"r"(dst), "l"(m), "r"(bar), "r"(0), "r"(c2), "r"(c4) : "memory");
}
__device__ __forceinline__ void mbar_arrive_cta(uint32_t b, uint32_t cta) {
  asm volatile("{\n.reg .b32 ra;\nmapa.shared::cluster.u32 ra, %0, %1;\nmbarrier.arrive.shared::cluster.b64 _, [ra];\n}" ::"r"(b), "r"(cta) : "memory");
}
constexpr uint64_t POL_FIRST = 0x12F0000000000000ull;
__device__ __forceinline__ void tma2d_ef(uint32_t dst, const CUtensorMap* m, int c0, int c1, uint32_t bar) {
  asm volatile("cp.async.bulk.tensor.2d.shared::cluster.global.mbarrier::complete_tx::bytes.L2::cache_hint [%0], [%1, {%3, %4}], [%2], %5;" ::"r"(dst), "l"(m), "r"(bar), "r"(c0), "r"(c1), "l"(POL_FIRST) : "memory");
}
__device__ __forceinline__ void bulk_ld(uint32_t dst, const void* src, uint32_t bytes, uint32_t bar) {
  asm volatile("cp.async.bulk.shared::cluster.global.mbarrier::complete_tx::bytes [%0], [%1], %2, [%3];" ::"r"(dst), "l"(src), "r"(bytes), "r"(bar) : "memory");
}
__device__ __forceinline__ void bulk_ld_mc(uint32_t dst, const void* src, uint32_t bytes, uint32_t bar) {
  asm volatile("cp.async.bulk.shared::cluster.global.mbarrier::complete_tx::bytes.multicast::cluster [%0], [%1], %2, [%3], %4;" ::"r"(dst), "l"(src), "r"(bytes), "r"(bar), "h"((uint16_t)3) : "memory");
}
__device__ __forceinline__ void bulk_pf(const void* src, uint32_t bytes) { asm volatile("cp.async.bulk.prefetch.L2.global [%0], %1;" ::"l"(src), "r"(bytes) : "memory"); }
__device__ __forceinline__ void tma2d_pf(const CUtensorMap* m, int c0, int c1) {
  asm volatile("cp.async.bulk.prefetch.tensor.2d.L2.global [%0, {%1, %2}];" ::"l"(m), "r"(c0), "r"(c1) : "memory");
}
__device__ __forceinline__ void map_pf(const CUtensorMap* m) { asm volatile("prefetch.tensormap [%0];" ::"l"(m) : "memory"); }
__device__ __forceinline__ void line_pf(const void* p) { asm volatile("prefetch.global.L2 [%0];" ::"l"(p)); }
__device__ __forceinline__ void pf128(uint32_t dummy, const void* src) { asm volatile("cp.async.ca.shared.global.L2::128B [%0], [%1], 4;" ::"r"(dummy), "l"(src) : "memory"); }
__device__ __forceinline__ void pf256(uint32_t dummy, const void* src) { asm volatile("cp.async.ca.shared.global.L2::256B [%0], [%1], 4;" ::"r"(dummy), "l"(src) : "memory"); }
__device__ __forceinline__ void cp16x2(uint32_t dst, const void* src) {
  asm volatile("cp.async.cg.shared.global [%0], [%1], 16;\ncp.async.cg.shared.global [%0+4096], [%1+512], 16;" ::"r"(dst), "l"(src) : "memory");
}
constexpr uint32_t HI_SW128 = 0x40000000u | (1024 >> 4), HI_SW64 = 0x80000000u | (512 >> 4), HI_NOSW = 512 >> 4;
__device__ __forceinline__ uint64_t mkdesc(uint32_t lo, uint32_t hi) { uint64_t d; asm("mov.b64 %0, {%1, %2};" : "=l"(d) : "r"(lo), "r"(hi)); return d; }
__device__ __forceinline__ void wg_fence() { asm volatile("wgmma.fence.sync.aligned;" ::: "memory"); }
__device__ __forceinline__ void wg_commit() { asm volatile("wgmma.commit_group.sync.aligned;" ::: "memory"); }
template <int N> __device__ __forceinline__ void wg_wait() { asm volatile("wgmma.wait_group.sync.aligned %0;" ::"n"(N) : "memory"); }
template <int N> __device__ __forceinline__ void reg_fence(float (&a)[N]) {
#pragma unroll
  for (int i = 0; i < N; i++) asm volatile("" : "+f"(a[i])::"memory");
}
template <int ID, int N> __device__ __forceinline__ void bar_sync() { asm volatile("bar.sync %0, %1;" ::"n"(ID), "n"(N) : "memory"); }
__device__ __forceinline__ void fence_async_smem() { asm volatile("fence.proxy.async.shared::cta;" ::: "memory"); }
__device__ __forceinline__ void fence_async_gmem() { asm volatile("fence.proxy.async.global;" ::: "memory"); }
__device__ __forceinline__ uint32_t pack_bf16(float lo, float hi) { uint32_t r; asm("cvt.rn.bf16x2.f32 %0, %1, %2;" : "=r"(r) : "f"(hi), "f"(lo)); return r; }
__device__ __forceinline__ float bf_lo(uint32_t v) { return __uint_as_float(v << 16); }
__device__ __forceinline__ float bf_hi(uint32_t v) { return __uint_as_float(v & 0xFFFF0000u); }
__device__ __forceinline__ float bf_round(float v) { return bf_lo(pack_bf16(v, v)); }
__device__ __forceinline__ uint32_t bf_sub2(uint32_t a, uint32_t b) { uint32_t r; asm("sub.rn.bf16x2 %0, %1, %2;" : "=r"(r) : "r"(a), "r"(b)); return r; }
__device__ __forceinline__ float rcp(float v) { float r; asm("rcp.approx.ftz.f32 %0, %1;" : "=f"(r) : "f"(v)); return r; }
__device__ __forceinline__ float ex2(float v) { float r; asm("ex2.approx.ftz.f32 %0, %1;" : "=f"(r) : "f"(v)); return r; }
__device__ __forceinline__ float sigmoid(float v) { return rcp(1.f + ex2(v * -1.4426950408889634f)); }
__device__ __forceinline__ void stsm4(uint32_t a, uint32_t r0, uint32_t r1, uint32_t r2, uint32_t r3) {
  asm volatile("stmatrix.sync.aligned.m8n8.x4.shared.b16 [%0], {%1,%2,%3,%4};" ::"r"(a), "r"(r0), "r"(r1), "r"(r2), "r"(r3) : "memory");
}
__device__ __forceinline__ void stsm4t(uint32_t a, uint32_t r0, uint32_t r1, uint32_t r2, uint32_t r3) {
  asm volatile("stmatrix.sync.aligned.m8n8.x4.trans.shared.b16 [%0], {%1,%2,%3,%4};" ::"r"(a), "r"(r0), "r"(r1), "r"(r2), "r"(r3) : "memory");
}
__device__ __forceinline__ void ldsm4(uint32_t a, uint32_t& r0, uint32_t& r1, uint32_t& r2, uint32_t& r3) {
  asm volatile("ldmatrix.sync.aligned.m8n8.x4.shared.b16 {%0,%1,%2,%3}, [%4];" : "=r"(r0), "=r"(r1), "=r"(r2), "=r"(r3) : "r"(a) : "memory");
}
__device__ __forceinline__ uint32_t movmat(uint32_t a) { uint32_t d; asm volatile("movmatrix.sync.aligned.m8n8.trans.b16 %0, %1;" : "=r"(d) : "r"(a)); return d; }
__device__ __forceinline__ void sts_h(uint32_t a, float v) { asm volatile("st.shared.u16 [%0], %1;" ::"r"(a), "h"((uint16_t)pack_bf16(v, v)) : "memory"); }
__device__ __forceinline__ float2 lds_f2(uint32_t a) { float2 v; asm volatile("ld.shared.v2.f32 {%0,%1}, [%2];" : "=f"(v.x), "=f"(v.y) : "r"(a)); return v; }
__device__ __forceinline__ float lds_f(uint32_t a) { float v; asm volatile("ld.shared.f32 %0, [%1];" : "=f"(v) : "r"(a)); return v; }
__device__ __forceinline__ float4 lds_f4(uint32_t a) { float4 v; asm volatile("ld.shared.v4.f32 {%0,%1,%2,%3}, [%4];" : "=f"(v.x), "=f"(v.y), "=f"(v.z), "=f"(v.w) : "r"(a)); return v; }
__device__ __forceinline__ uint32_t lds_u(uint32_t a) { uint32_t v; asm volatile("ld.shared.u32 %0, [%1];" : "=r"(v) : "r"(a) : "memory"); return v; }
__device__ __forceinline__ uint4 lds_u4(uint32_t a) { uint4 v; asm volatile("ld.shared.v4.u32 {%0,%1,%2,%3}, [%4];" : "=r"(v.x), "=r"(v.y), "=r"(v.z), "=r"(v.w) : "r"(a) : "memory"); return v; }
__device__ __forceinline__ void sts_u(uint32_t a, uint32_t v) { asm volatile("st.shared.u32 [%0], %1;" ::"r"(a), "r"(v) : "memory"); }
__device__ __forceinline__ void sts_u4(uint32_t a, uint4 v) { asm volatile("st.shared.v4.u32 [%0], {%1,%2,%3,%4};" ::"r"(a), "r"(v.x), "r"(v.y), "r"(v.z), "r"(v.w) : "memory"); }
__device__ __forceinline__ uint4 ldx4(const void* p) { uint4 v; asm volatile("ld.relaxed.gpu.global.v4.u32 {%0,%1,%2,%3}, [%4];" : "=r"(v.x), "=r"(v.y), "=r"(v.z), "=r"(v.w) : "l"(p) : "memory"); return v; }
__device__ __forceinline__ uint2 ldx2(const void* p) { uint2 v; asm volatile("ld.relaxed.gpu.global.v2.u32 {%0,%1}, [%2];" : "=r"(v.x), "=r"(v.y) : "l"(p) : "memory"); return v; }
__device__ __forceinline__ uint32_t ldx1(const void* p) { uint32_t v; asm volatile("ld.relaxed.gpu.global.u32 %0, [%1];" : "=r"(v) : "l"(p) : "memory"); return v; }
__device__ __forceinline__ void stx4(void* p, uint32_t a, uint32_t b, uint32_t c, uint32_t d) { asm volatile("st.relaxed.gpu.global.v4.u32 [%0], {%1,%2,%3,%4};" ::"l"(p), "r"(a), "r"(b), "r"(c), "r"(d) : "memory"); }
__device__ __forceinline__ void stx2(void* p, uint32_t a, uint32_t b) { asm volatile("st.relaxed.gpu.global.v2.u32 [%0], {%1,%2};" ::"l"(p), "r"(a), "r"(b) : "memory"); }
__device__ __forceinline__ void stx1(void* p, uint32_t a) { asm volatile("st.relaxed.gpu.global.u32 [%0], %1;" ::"l"(p), "r"(a) : "memory"); }
__device__ __forceinline__ uint32_t umax4(uint4 v) { return max(max(v.x, v.y), max(v.z, v.w)); }
__device__ __forceinline__ uint32_t f2x(float f) { return min(__float_as_uint(f), 0xFFFFFFFEu); }
__device__ __forceinline__ void red4(float* p, float a, float b, float c, float d) { asm volatile("red.relaxed.gpu.global.add.v4.f32 [%0], {%1,%2,%3,%4};" ::"l"(p), "f"(a), "f"(b), "f"(c), "f"(d) : "memory"); }
__device__ __forceinline__ void cnt_arrive(int c) { asm volatile("red.release.gpu.global.add.u32 [%0], 1;" ::"l"(&G.cnt[c]) : "memory"); }
__device__ __forceinline__ void cnt_wait(int c, uint32_t target) {
#pragma unroll 1
  for (uint32_t it = 0; it < SPIN_MAX; it++) {
    uint32_t v;
    asm volatile("ld.acquire.gpu.global.u32 %0, [%1];" : "=r"(v) : "l"(&G.cnt[c]) : "memory");
    if (v >= target) break;
    __nanosleep(POLLNS);
  }
}
__device__ __forceinline__ void cnt_done() {
  uint32_t t;
  asm volatile("atom.acq_rel.gpu.global.add.u32 %0, [%1], 1;" : "=r"(t) : "l"(&G.cnt[C_DONE]) : "memory");
  if (t == NCTA + NSVC - 1) {
#pragma unroll 1
    for (int i = 0; i < NCNT; i++) G.cnt[i * 32] = 0;
  }
}
__device__ __forceinline__ float phi(float u, float rs, float rl) {
  float a = fmaf(u, rs, 1.000001f), e = ex2(u * rl), r;
  asm("add.sat.f32 %0, %1, 0f358637BD;" : "=f"(e) : "f"(e));
  asm("max.NaN.f32 %0, %1, %2;" : "=f"(r) : "f"(a), "f"(e));
  return r;
}

__device__ __forceinline__ uint32_t phi2(float u0, float rs0, float rl0, float u1, float rs1, float rl1) {
  float e0, e1;
  asm("{\n.reg .f32 t;\nabs.f32 t, %1;\nneg.f32 t, t;\nex2.approx.ftz.f32 %0, t;\n}" : "=f"(e0) : "f"(u0 * rl0));
  asm("{\n.reg .f32 t;\nabs.f32 t, %1;\nneg.f32 t, t;\nex2.approx.ftz.f32 %0, t;\n}" : "=f"(e1) : "f"(u1 * rl1));
  uint32_t e = pack_bf16(e0, e1), r;
  const uint32_t a = pack_bf16(fmaf(u0, rs0, 1.000001f), fmaf(u1, rs1, 1.000001f));
  asm("add.rn.bf16x2 %0, %0, %1;" : "+r"(e) : "r"(0x35863586u));
  asm("max.NaN.bf16x2 %0, %1, %2;" : "=r"(r) : "r"(a), "r"(e));
  return r;
}

__device__ __forceinline__ int kstep1(int e, int hg) { return e < 14 ? (e < 2 * hg ? e : e + 2) : 2 * hg + e - 14; }
__device__ __forceinline__ int slab(int n, int hg) {
  return n + (((n + 7 - hg) * 37) >> 8);
}
__host__ __device__ constexpr uint32_t d_off(int i) { return i < 3 ? 12 * SLOT + (NR == 4 ? i : (i == 2 ? 0 : i + 1)) * MT : (i < 5 ? S_D0 * SLOT + (i - 3) * 8192 : S_D1 * SLOT + (i - 5) * 8192); }
__host__ __device__ constexpr uint32_t h_off(int i) { return i < 3 ? 12 * SLOT + i * MT + 8192 : (i < 5 ? A_ONES + (i - 3) * 1024 : MISC + M_MOE + (i - 5) * 1024); }
__device__ __forceinline__ uint32_t m_off(int r) { return r < 3 ? 12 * SLOT + r * MT : S_M3 * SLOT; }
__device__ __forceinline__ int x_slot(int e, int s) { return NQ == 5 ? (e < 14 ? s : e - 11) : (e < 13 ? s : 3 + s); }
__device__ __forceinline__ uint32_t wo_slot(int i) { return (uint32_t)(WO_SLOTS >> (4 * i)) & 15u; }

__global__ void __launch_bounds__(512, 1)
fused_kernel(const __nv_bfloat16* __restrict__ x, const __nv_bfloat16* __restrict__ wqkv, const __nv_bfloat16* __restrict__ wo,
             const __nv_bfloat16* __restrict__ wr, const __nv_bfloat16* __restrict__ wd, __nv_bfloat16* __restrict__ outp, const int by_sm,
             const __grid_constant__ CUtensorMap tmX, const __grid_constant__ CUtensorMap tmW,
             const __grid_constant__ CUtensorMap tmWo, const __grid_constant__ CUtensorMap tmOut,
             const __grid_constant__ CUtensorMap tmG, const __grid_constant__ CUtensorMap tmU,
             const __grid_constant__ CUtensorMap tmD, const __grid_constant__ CUtensorMap tmR,
             const __grid_constant__ CUtensorMap tmWp) {
  if (TMP && threadIdx.x == 32 * TMPW) { map_pf(&tmX); map_pf(&tmW); }
  extern __shared__ __align__(1024) uint8_t smem_raw[];
  const uint32_t sb = (uint32_t)__cvta_generic_to_shared(smem_raw);
  const uint32_t bars = sb + MISC + M_BAR;
  uint32_t smid;
  asm("mov.u32 %0, %%smid;" : "=r"(smid));
  const int tpc = smid >> 1;
  int cl = tpc + max(((tpc - 25) * 37) >> 8, 0);
  cl = tpc < 60 ? cl : cl - 1;
  cl = tpc < 62 ? cl : (tpc - 58) * 8;
  const int u = by_sm ? 2 * cl + (blockIdx.x & 1) : blockIdx.x;
  const int hg = (u >> 4) & 7, tb = u & 15;
  const int b = tb * 8 + hg;
  const int lane = threadIdx.x & 31;
  const int warp = __shfl_sync(~0u, threadIdx.x >> 5, 0);
  const int ltid = threadIdx.x;
  const int g = lane >> 2, t = lane & 3;
  const uint32_t d0 = (sb & 0x3FFFF) >> 4;
#define BAR(i) (bars + 8 * (i))
  TLS(0, 0);

  const int rank = u & 1;
  auto load_entry = [&](int e, int s) {
    const int k0 = kstep1(e, hg) * 64;
    mbar_expect_tx(BAR(B_FXQ + s), e < NF ? 2 * SLOT : SLOT);
    mbar_expect_tx(BAR(B_FKV + s), R5 ? SLOT : 2 * SLOT);
    if (R5 && e < 11) mbar_expect_tx(BAR(B_FV + s), SLOT);
    const uint32_t vb = R5 ? BAR(B_FV + s) : BAR(B_FKV + s);
    tma2d(sb + x_slot(e, s) * SLOT, &tmX, k0, tb * 128, BAR(B_FXQ + s));
    if (e < MC0 || !(MC & 1)) {
      if (e < NF) tma3d(sb + (3 + s) * SLOT, &tmW, k0, 2 * hg, BAR(B_FXQ + s));
      tma3d(sb + (6 + 2 * s) * SLOT, &tmW, k0, 16 + 2 * hg, BAR(B_FKV + s));
      tma3d(sb + (7 + 2 * s) * SLOT, &tmW, k0, 32 + 2 * hg, vb);
    } else {
      if (e < NF && (e & 1) == rank) tma3d_mc(sb + (3 + s) * SLOT, &tmW, k0, 2 * hg, BAR(B_FXQ + s));
      if (R5 && e >= 11) { if (rank == 0) tma3d_mc(sb + ((K_SLOTS >> (4 * (e - 10))) & 15u) * SLOT, &tmW, k0, 16 + 2 * hg, BAR(B_FKV + s)); }
      else tma3d_mc(sb + (6 + 2 * s + rank) * SLOT, &tmW, k0, 16 + 16 * rank + 2 * hg, rank ? vb : BAR(B_FKV + s));
    }
  };
  if (warp == FW && u < NCTA) {
    if (elect_one()) {
      mbar_init(BAR(B_FXQ), 1); mbar_init(BAR(B_FKV), 1);
      if (R5) mbar_init(BAR(B_FV), 1);
      load_entry(0, 0);
      asm volatile("fence.mbarrier_init.release.cluster;" ::: "memory");
      TLS(FW * 32, 61);
    }
    __syncwarp();
  }
  if (u >= NCTA) {
    const int j = u - NCTA;
    if (warp == 8 && elect_one()) {
#pragma unroll
      for (int i = 0; i < 13; i++) mbar_init(BAR(i), 1);
    }
    if (ltid < 64) sts_u4(sb + MISC + ltid * 16, make_uint4(0x3F803F80u, 0x3F803F80u, 0x3F803F80u, 0x3F803F80u));
    fence_async_smem();
    __syncthreads();
    if (warp < 4) {
      int s = 0, p = 0;
#pragma unroll 1
      for (int pass = 0; pass < 3; pass++) {
        float acc[4][4];
#pragma unroll
        for (int c = 0; c < 4; c++) acc[c][0] = acc[c][1] = acc[c][2] = acc[c][3] = 0.f;
#pragma unroll 1
        for (int k = 0; k < 16; k++) {
          mbar_wait(BAR(s), p);
          wg_fence();
#pragma unroll
          for (int c = 0; c < 4; c++)
#pragma unroll
            for (int kk = 0; kk < 4; kk++)
              wgmma_ss_n8<1, 0>(acc[c], mkdesc((d0 + s * 2048 + c * 512 + kk * 128) | (512u << 16), HI_SW128), mkdesc((d0 + (MISC >> 4)) | (1u << 16), HI_SW128));
          wg_commit();
          wg_wait<0>();
          if (ltid == 0) mbar_arrive(BAR(6 + s));
          if (++s == SVS) { s = 0; p ^= 1; }
        }
        uint32_t* pc = G.cs + (pass < 2 ? DM + pass * DM : 0) + j * 256 + warp * 16 + g;
#pragma unroll
        for (int c = 0; c < 4; c++) {
          reg_fence(acc[c]);
          const uint32_t v = __float_as_uint((t & 1) ? acc[c][2] : acc[c][0]);
          if (t < 2) stx1(pc + c * 64 + t * 8, v ? v : 0x80000000u);
        }
        TLS(0, 1 + pass);
      }
    } else if (warp >= 8 && j == 0) {
      const int wq = warp - 8;
      const uint32_t top = sb + MISC + 1024;
#pragma unroll 1
      for (uint32_t it = 0; it < SPIN_MAX; it++) {
        const uint4 v0 = ldx4(G.key + wq * 256 + lane * 4), v1 = ldx4(G.key + wq * 256 + 128 + lane * 4);
        uint32_t ok;
        asm volatile("{\n.reg .pred p, q;\nsetp.ne.u32 p, %1, 0;\nbar.red.and.pred q, 2, 256, p;\nselp.b32 %0, 1, 0, q;\n}" : "=r"(ok) : "r"((v0.x & v0.y & v0.z & v0.w & v1.x & v1.y & v1.z & v1.w) >> 27) : "memory");
        ok = __any_sync(~0u, ok);
        if (!ok && it) continue;
        TLS(256, 4);
        uint32_t np = 0u - (1u << 28), mine = 0;
#pragma unroll 1
        for (int r = 0; r < 8; r++) {
          const uint32_t m0 = __viaddmax_u32(v0.x, np, v0.y + np), m1 = __viaddmax_u32(v0.z, np, v0.w + np), m2 = __viaddmax_u32(v1.x, np, v1.y + np), m3 = __viaddmax_u32(v1.z, np, v1.w + np);
          np -= __reduce_max_sync(~0u, max(max(m0, m1), max(m2, m3)));
          if (g == r) mine = 0u - np;
        }
        if (t == 0) sts_u(top + (wq * 8 + g) * 4, mine);
        bar_sync<2, 256>();
        TLS(256, 5);
        int rk = 0;
#pragma unroll
        for (int i = 0; i < 4; i++) {
          const uint4 o = lds_u4(top + t * 64 + i * 16);
          rk += (o.x > mine) + (o.y > mine) + (o.z > mine) + (o.w > mine);
        }
        rk += __shfl_xor_sync(~0u, rk, 1);
        rk += __shfl_xor_sync(~0u, rk, 2);
        if (ok) { if (rk < 8) stx1(G.top + t * 32 + rk, mine); break; }
        __nanosleep(2500);
      }
      TLS(256, 7);
    } else if (warp == 4) {
      int s = 0, p = 1;
      if (SVD) __nanosleep(SVD);
#pragma unroll 1
      for (int i = 0; i < 48; i++) {
        mbar_wait(BAR(6 + s), p);
        if (j == 0 && i >= SV0A && i < SV0B) mbar_wait(BAR(s >= SV0 ? s - SV0 : s - SV0 + SVS), s >= SV0 ? p ^ 1 : p);
        if (elect_one()) {
          mbar_expect_tx(BAR(s), 2 * SLOT);
          const int ch = (i < 32 ? 16 + (i & 16) : 0) + j * 4, k0 = (i & 15) * 64;
          tma3d(sb + s * 2 * SLOT, &tmW, k0, ch, BAR(s));
          tma3d(sb + s * 2 * SLOT + SLOT, &tmW, k0, ch + 2, BAR(s));
        }
        if (++s == SVS) { s = 0; p ^= 1; }
      }
    }
    if (ltid == 0) cnt_wait(C_DONE, NCTA);
    __syncthreads();
    const uint4 zero = make_uint4(0, 0, 0, 0);
    if (ltid < 128) reinterpret_cast<uint4*>(G.key)[j * 128 + ltid] = zero;
    else if (ltid < 320) reinterpret_cast<uint4*>(G.cs)[j * 192 + ltid - 128] = zero;
    else if (ltid < 322) reinterpret_cast<uint4*>(G.top)[j * 8 + ltid - 320] = zero;
    if (ltid == 0) { cnt_done(); TLDUMP(); }
    return;
  }

  if (warp == 12) {
    if (elect_one()) {
#pragma unroll
      for (int i = 1; i < 7; i++) if (i != B_FKV) mbar_init(BAR(i), 1);
      if (R5) { mbar_init(BAR(B_FV + 1), 1); mbar_init(BAR(B_FV + 2), 1); }
      if (E1E) load_entry(1, 1);
      asm volatile("fence.mbarrier_init.release.cluster;" ::: "memory");
    }
  } else if (warp >= 13) {
    if (elect_one()) {
      if (warp == 15) {
#pragma unroll
        for (int i = B_FAUX; i < NBAR; i++) mbar_init(BAR(i), i < B_E || !MC ? 2 : 4);
        mbar_init(BAR(B_KV4), 4); mbar_init(BAR(B_MS), 2); mbar_init(BAR(B_GQ), 1); mbar_init(BAR(B_GT), 1);
        if (R5) { mbar_init(BAR(B_EK), 4); mbar_init(BAR(B_EK + 1), 4); mbar_init(BAR(B_EK + 2), 4); }
      } else {
#pragma unroll
        for (int i = 0; i < 23; i++) mbar_init(BAR((warp == 13 ? 7 : 30) + i), 1);
      }
      asm volatile("fence.mbarrier_init.release.cluster;" ::: "memory");
    }
  }
  __syncthreads();
  if (MC) asm volatile("barrier.cluster.arrive.relaxed.aligned;" ::: "memory");

  const bool unit = u < NUNIT;
  const int dcol = (u & 15) * 64, drow = (u >> 4) * 448;
  if (warp >= 12) {
    asm volatile("setmaxnreg.dec.sync.aligned.u32 %0;" ::"n"(PROD_REGS));
    if (MC && warp != 12) asm volatile("barrier.cluster.wait.aligned;" ::: "memory");
    if (warp == 12) {
      int s = 1 + E1E, p = 1, pn = 3;
#pragma unroll 1
      for (int e = 1 + E1E; e < 16; e++) {
        if (MC && e == MC0) asm volatile("barrier.cluster.wait.aligned;" ::: "memory");
        if (e == GATE) mbar_wait(BAR(B_FXQ), 0);
        mbar_wait(BAR(B_E + s), p);
        if (elect_one()) {
          load_entry(e, s);
          if (NR == 4 && e == 11) mbar_arrive(BAR(B_ME + 3));
          if (e == ASTE) {
            mbar_expect_tx(BAR(B_AST), 2 * SLOT + 2048);
            bulk_ld(sb + 12 * SLOT, x + (size_t)b * 16 * DM, 2 * SLOT, BAR(B_AST));
            bulk_ld(sb + MISC + M_MOE, wr, 2048, BAR(B_AST));
          } else if (e >= 3) {
            if (e < 6) bulk_pf(wqkv + (size_t)((e - 2) * 256 + 2 * b) * 3 * DM, 2 * 3 * DM * 2);
            if (e < 7) bulk_pf(wo + (size_t)((e - 3) * 256 + 2 * b) * DM, 2 * DM * 2);
            if (NUNIT) {
#pragma unroll 1
              for (int i = (PFTAB >> (4 * (e - 3))) & 15; i > 0; i--, pn++) {
                if (pn >= 16) { if (!(MX & 8)) tma2d_pf(&tmD, dcol, drow + (pn - 16) * 64); }
                else if (unit && !(MX & 2)) tma2d_pf(rank ? &tmU : &tmG, (u >> 1) * 64, pn * 64);
              }
            }
          }
        }
        if (R5 && e >= 11) {
          mbar_wait(BAR(B_EK + (s == 2 ? 0 : s + 1)), e >= 14);
          if (elect_one()) {
            mbar_expect_tx(BAR(B_FV + s), SLOT);
            if (rank) tma3d_mc(sb + ((V_SLOTS >> (4 * (e - 10))) & 15u) * SLOT, &tmW, kstep1(e, hg) * 64, 32 + 2 * hg, BAR(B_FV + s));
          }
        }
        if (++s == 3) { s = 0; p ^= 1; }
      }
#pragma unroll 1
      for (int k = 0; k < NQ; k++) {
        if (k == 0) mbar_wait(BAR(B_E + 1), 0);
        if (k == 1) mbar_wait(BAR(B_EK + 2), 1);
        if (k == 2) mbar_wait(BAR(B_EK + 0), 0);
        if (k == 3) mbar_wait(BAR(B_STG), 0);
        if (k == 5) mbar_wait(BAR(B_EQ), 0);
        if (elect_one()) {
          const int k0 = kstep1(NF + k, hg) * 64;
          mbar_expect_tx(BAR(B_FQ + k), SLOT);
          if (!(MC & 2)) tma3d(sb + ((QW_SLOTS >> (4 * k)) & 15u) * SLOT, &tmW, k0, 2 * hg, BAR(B_FQ + k));
          else if ((k & 1) == rank) tma3d_mc(sb + ((QW_SLOTS >> (4 * k)) & 15u) * SLOT, &tmW, k0, 2 * hg, BAR(B_FQ + k));
        }
      }
#pragma unroll 1
      for (int i = 0; i < 16; i++) {
        mbar_wait(i < 7 ? BAR(B_EQ + ((i + WQ0) >> 1)) : (i < 9 ? BAR(B_DE) : BAR(B_EO + i - 9)), 0);
        if (i == WOK) mbar_wait(BAR(B_KVB), 0);
        mbar_wait(BAR(B_FWO + i - (i < WOK ? WOD1 : WOD)), 0);
        if (elect_one()) {
          mbar_expect_tx(BAR(B_FWO + i), SLOT);
#pragma unroll
          for (int hf = 0; hf < ((MC & 4) ? 1 : 2); hf++) {
            const int n = 2 * i + ((MC & 4) ? rank : hf), m = slab(n - 4, hg), hd = n < 4 ? 4 * hg + n : 4 * (m & 7) + (m >> 3);
            if (i < 2 + NDIR) tma5d(sb + wo_slot(i) * SLOT + (n & 1) * 8192, &tmWp, hd * 4, 2 * hg, BAR(B_FWO + i), MC & 4);
            else if (MC & 4) tma3d_mc(sb + wo_slot(i) * SLOT + rank * 8192, &tmWo, hd * 32, 2 * hg, BAR(B_FWO + i));
            else tma3d(sb + wo_slot(i) * SLOT + hf * 8192, &tmWo, hd * 32, 2 * hg, BAR(B_FWO + i));
          }
        }
      }
    } else if (warp == 13) {
      if (elect_one()) {
        map_pf(rank ? &tmU : &tmG); map_pf(&tmR); map_pf(&tmD); map_pf(&tmWo); map_pf(&tmWp); map_pf(&tmOut);
      }
      bar_sync<6, 64>();
      if (elect_one()) {
        cnt_wait(C_B, NCTA);
        fence_async_gmem();
        mbar_expect_tx(BAR(B_FAUX), 1024);
        bulk_ld(sb + A_ST, G.stats + tb * 128, 1024, BAR(B_FAUX));
      }
      __syncwarp();
      TLS(416, 68);
#pragma unroll 1
      for (int m = 1; m < 4; m++) {
        const int part = m == 3 ? 0 : m;
        uint4 c;
#pragma unroll 1
        for (uint32_t it = 0; it < SPIN_MAX; it++) {
          c = ldx4(G.cs + part * DM + hg * 128 + lane * 4);
          if (__all_sync(~0u, min(min(c.x, c.y), min(c.z, c.w)))) break;
          __nanosleep(POLLNS);
        }
        sts_u4(sb + A_CS + part * 512 + lane * 16, c);
        __syncwarp();
        if (m > 1 && lane == 0) mbar_arrive(BAR(m == 2 ? B_FAUX : B_CQ));
        TLS(416, 71 + m);
      }
      mbar_wait(BAR(B_XS), 1);
      if (elect_one()) asm volatile("red.relaxed.gpu.global.add.u32 [%0], 1;" ::"l"(&G.cnt[C_DONE]) : "memory");
    } else if (warp == 14) {
      const uint4 sent = make_uint4(SENT, SENT, SENT, SENT);
      uint4* ro = G.o + (tb * 32 + hg) * 512 + lane;
      uint4* rp = G.part + b * 544 + lane;
      if (RSL) bar_sync<5, 160>(); else mbar_wait(BAR(B_AST), 0);
#pragma unroll 1
      for (int i = RS0; i < 40; i++) {
        uint4* q = i < 32 ? ro + (i >> 3) * 4096 + (i & 7) * 64 : rp + (i - 32) * 64;
        q[0] = sent; q[32] = sent;
        __nanosleep(RSNS);
      }
      rp[512] = sent;
#pragma unroll
      for (int i = 0; i < 4; i++) G.y[u * 128 + i * 32 + lane] = sent;
      if (unit) reinterpret_cast<uint4*>(G.h)[u * 32 + lane] = sent;
      G.fin[hg * 640 + tb * 40 + lane] = sent;
      if (lane < 8) G.fin[hg * 640 + tb * 40 + 32 + lane] = sent;
      if (!RSL) bar_sync<5, 160>();
      __syncwarp();
      TLS(448, 67);
      if (lane == 0) cnt_arrive(C_B);
      __syncwarp();
      TLS(448, 32);
      asm volatile("bar.arrive 6, 64;" ::: "memory");
    } else {
      const uint32_t stg = sb + 12 * SLOT;
      auto load_a = [&](int n, int r) {
        mbar_expect_tx(BAR(B_MF + r), (MX & 2) ? 1024 : MT);
        if (!(MX & 2)) tma2d_ef(sb + m_off(r), rank ? &tmU : &tmG, (u >> 1) * 64, n * 64, BAR(B_MF + r));
      };
      mbar_wait(BAR(B_XS), 0);
      if (unit) {
#pragma unroll 1
        for (int i = 0; i < 3; i++) {
          if (elect_one()) load_a(i, i);
          __nanosleep(PFILL);
        }
      }
      uint32_t key;
#pragma unroll 1
      for (uint32_t it = 0; it < SPIN_MAX; it++) {
        key = ldx1(G.top + ((u >> 1) & 3) * 32 + (lane & 7));
        if (__all_sync(~0u, key)) break;
        __nanosleep(TPNS);
      }
      TLS(480, 66);
      if (lane < 8) sts_u(sb + MISC + M_IDX + lane * 4, key);
      __syncwarp();
      if (lane == 0) mbar_arrive(BAR(B_XS));
      if (unit) {
        int tok[8];
#pragma unroll
        for (int i = 0; i < 8; i++) tok[i] = ~__shfl_sync(~0u, key, i) & 2047;
        int r = 0, p = 0;
#pragma unroll 1
        for (int n = 0; n < 16; n++) {
          if (n >= 3) mbar_wait(BAR(B_ME + r), r == 3 ? p : p ^ 1);
          if (elect_one()) {
            if (n >= 3) load_a(n, r);
#pragma unroll
            for (int i = 0; i < 8; i++) tma2d(sb + m_off(r) + 8192 + i * 128, &tmR, n * 64, tok[i], BAR(B_MF + r));
          }
          if (++r == NR) { r = 0; p ^= 1; }
        }
      }
      if (NUNIT) {
        if (lane == 0) mbar_expect_tx(BAR(B_DF), (MX & 8) ? 0 : 7 * 8192);
#pragma unroll 1
        for (int i = 0; i < 7; i++) {
          if (NR == 4) {
            if (i >= 3) mbar_wait(i < 5 ? BAR(B_ME + 3) : (R5 ? BAR(B_EQ + 1) : BAR(B_STG)), 0);
            else if (unit) mbar_wait(BAR(B_ME + i), 1);
          } else {
            if (i >= 3) mbar_wait(BAR(B_EQ + ((i - 3) >> 1)), 0);
            else if (unit) mbar_wait(BAR(B_ME + (i == 2 ? 0 : i + 1)), i == 2);
          }
          if (!(MX & 8) && elect_one()) tma2d_ef(sb + d_off(i), &tmD, dcol, drow + i * 64, BAR(B_DF));
          if (DNS) __nanosleep(DNS);
        }
      }
    }
    if (warp == 14) {
      if (DPF && NUNIT && !(MX & 8)) {
        mbar_wait(DS ? BAR(B_MS) : (DPF == 1 ? BAR(B_FQ) : BAR(B_T0)), 0);
#pragma unroll 1
        for (int pf = 0; pf < 7; pf++) { pf256(sb + MISC + M_DUM, wd + (size_t)(drow + pf * 64 + rank * 32 + lane) * DM + (dcol & ~127)); __nanosleep(PFNS2); }
      }
      const uint32_t* src = reinterpret_cast<const uint32_t*>(G.part + ((lane >> 3) * 32 + hg) * 544 + 512) + tb * 8 + (lane & 7);
      mbar_wait(BAR(B_EQ + MRW), 0);
      if (MRD) __nanosleep(MRD);
      uint32_t z0, z1, z2, z3;
#pragma unroll 1
      for (uint32_t it = 0; it < SPIN_MAX; it++) {
        z0 = ldx1(src); z1 = ldx1(src + 8 * 2176); z2 = ldx1(src + 16 * 2176); z3 = ldx1(src + 24 * 2176);
        if (!__any_sync(~0u, max(max(z0, z1), max(z2, z3)) == SENT)) break;
      }
      if (MRED == 2 && elect_one()) mbar_arrive(BAR(B_ZOK));
      float zz = (__uint_as_float(z0) + __uint_as_float(z1)) + (__uint_as_float(z2) + __uint_as_float(z3));
      zz += __shfl_xor_sync(~0u, zz, 8);
      zz += __shfl_xor_sync(~0u, zz, 16);
      stx1(reinterpret_cast<uint32_t*>(G.fin + hg * 640) + (tb >> 2) * 640 + 512 + ((tb >> 1) & 1) * 64 + (lane & 1) * 32 + (tb & 1) * 16 + ((lane & 7) >> 1) * 4 + (lane >> 3),
           pack_bf16(zz, zz));
      TLS(448, 12);
    }
    if (!MFIN && (warp == 13 || warp == 14)) {
      mbar_wait(BAR(B_EQ + H2W), 0);
      if (H2D) __nanosleep(H2D);
#pragma unroll 1
      for (uint32_t it = 0; it < SPIN_MAX; it++) {
        if (warp == 14 && elect_one()) {
          mbar_expect_tx(BAR(B_FIN), 10240);
          if (FMC && MC && it == 0) bulk_ld_mc(sb + S_KVB * SLOT + rank * 5120, G.fin + hg * 640 + rank * 320, 5120, BAR(B_FIN));
          else bulk_ld(sb + S_KVB * SLOT, G.fin + hg * 640, 10240, BAR(B_FIN));
        }
        mbar_wait(BAR(B_FIN), it & 1);
        uint32_t m = 0;
#pragma unroll
        for (int i = 0; i < 10; i++) m = max(m, lds_u(sb + S_KVB * SLOT + (i * 64 + ltid - 416) * 16 + (g >> 1) * 4));
        uint32_t bad;
        asm volatile("{\n.reg .pred p, q;\nsetp.eq.u32 p, %1, 0xFFFFFFFF;\nbar.red.or.pred q, 7, 64, p;\nselp.b32 %0, 1, 0, q;\n}" : "=r"(bad) : "r"(m) : "memory");
        if (!__any_sync(~0u, bad)) break;
      }
      if (warp == 14 && elect_one()) mbar_arrive(BAR(B_KVB));
      TLS(448, 14);
    }
    if (PH && (warp == 13 || warp == 14)) {
      bar_sync<3, 192>();
      mbar_wait(BAR(B_STG), 0);
#pragma unroll 1
      for (uint32_t it = 0; NUNIT && it < SPIN_MAX; it++) {
        if (elect_one()) {
          const uint32_t* ph = G.h + (u >> 4) * 7 * 256;
          if (warp == 13) { mbar_expect_tx(BAR(B_HF), 7168); bulk_ld(sb + h_off(3), ph + 768, 2048, BAR(B_HF)); bulk_ld(sb + h_off(5), ph + 1280, 2048, BAR(B_HF)); }
          else { bulk_ld(sb + h_off(0), ph, 1024, BAR(B_HF)); bulk_ld(sb + h_off(1), ph + 256, 1024, BAR(B_HF)); bulk_ld(sb + h_off(2), ph + 512, 1024, BAR(B_HF)); }
        }
        mbar_wait(BAR(B_HF), it & 1);
        uint32_t m = 0;
#pragma unroll
        for (int i = 0; i < 7; i++) m = max(m, lds_u(sb + h_off(i) + (ltid - 416) * 16 + (g >> 1) * 4));
        uint32_t bad;
        asm volatile("{\n.reg .pred p, q;\nsetp.eq.u32 p, %1, 0xFFFFFFFF;\nbar.red.or.pred q, 7, 64, p;\nselp.b32 %0, 1, 0, q;\n}" : "=r"(bad) : "r"(m) : "memory");
        if (!__any_sync(~0u, bad)) break;
        __nanosleep(POLLNS);
      }
      if (warp == 14 && elect_one()) mbar_arrive(BAR(B_KVB));
    }
    __syncwarp();
    if (warp >= 13) {
      const char* og = reinterpret_cast<const char*>(G.o + tb * 16384);
      auto probe = [&](uint32_t m) {
        const char* p = og + m * 8192u + (lane & 15) * 512 + 496;
#pragma unroll 1
        for (uint32_t it = 0; it < SPIN_MAX; it++)
          if (!__any_sync(~0u, ldx1(p) == SENT)) break;
      };
      if (warp == 15) {
        int r = 0, p = 1;
        mbar_wait(BAR(B_EAUX), 0);
#pragma unroll 1
        for (int i = I0; i < 16; i++) {
          const uint32_t dst = sb + ((A_SLOTS >> (4 * r)) & 15u) * SLOT, m0 = slab(2 * i - 4, hg), m1 = slab(2 * i - 3, hg);
          if (i == I0 + 3) mbar_wait(BAR(B_DE), 0);
          mbar_wait(BAR(B_EA + r), p);
          if ((PROBE >> i) & 1) probe(lane < 16 ? m0 : m1);
          if (elect_one()) {
            mbar_expect_tx(BAR(B_AF + r), SLOT);
            bulk_ld(dst, og + m0 * 8192u, 8192, BAR(B_AF + r)); bulk_ld(dst + 8192, og + m1 * 8192u, 8192, BAR(B_AF + r));
          }
          if (++r == NA) { r = 0; p ^= 1; }
        }
      } else {
        const uint32_t lo = lane * 32 + g * 4, hb = sb + (warp - 13) * 8192;
        uint32_t ph = 0;
        int r = 0, p = 0;
#pragma unroll 1
        for (int i = I0; i < 16; i++) {
          const uint32_t mine = hb + ((A_SLOTS >> (4 * r)) & 15u) * SLOT;
          auto bad = [&]() {
            uint32_t v[8];
#pragma unroll
            for (int j = 0; j < 8; j++) v[j] = lds_u(mine + lo + j * 1024);
            return __any_sync(~0u, max(max(max(v[0], v[1]), max(v[2], v[3])), max(max(v[4], v[5]), max(v[6], v[7]))) == SENT);
          };
          mbar_wait(BAR(B_AF + r), p);
          if (!NOVAL && bad()) {
            const uint32_t m = slab(2 * i - 17 + warp, hg);
#pragma unroll 1
            for (uint32_t it = 0; it < 64; it++) {
              probe(m);
              if (elect_one()) { mbar_expect_tx(BAR(B_AR + warp - 13), 8192); bulk_ld(mine, og + m * 8192u, 8192, BAR(B_AR + warp - 13)); }
              mbar_wait(BAR(B_AR + warp - 13), ph);
              ph ^= 1;
              if (!bad()) break;
            }
          }
          if (elect_one()) mbar_arrive(BAR(B_VAL + r));
          if (++r == NA) { r = 0; p ^= 1; }
        }
      }
    }
  } else if (warp >= 8) {
    asm volatile("setmaxnreg.dec.sync.aligned.u32 %0;" ::"n"(MOE_REGS));
    if (MC) asm volatile("barrier.cluster.wait.aligned;" ::: "memory");
    const int aw = warp - 8;
    const uint32_t mbuf = sb + MISC + M_MOE, stg = sb + 12 * SLOT;
    mbar_wait(BAR(B_AST), 0);
    TLS(288, 64);
    {
      float v[16];
#pragma unroll
      for (int r = 0; r < 16; r++) v[r] = 0.f;
      const uint32_t base = stg + aw * 4 * 2048 + lane * 8;
#pragma unroll 1
      for (int c = 0; c < 8; c++) {
        const float2 w2 = lds_f2(mbuf + c * 256 + lane * 8);
        const float w[4] = {bf_lo(__float_as_uint(w2.x)), bf_hi(__float_as_uint(w2.x)), bf_lo(__float_as_uint(w2.y)), bf_hi(__float_as_uint(w2.y))};
        v[12] += (w[0] + w[1]) + (w[2] + w[3]);
#pragma unroll
        for (int r = 0; r < 4; r++) {
          const float2 x2 = lds_f2(base + r * 2048 + c * 256);
#pragma unroll
          for (int e = 0; e < 2; e++) {
            const uint32_t xx = __float_as_uint(e ? x2.y : x2.x);
            const float lo = bf_lo(xx), hi = bf_hi(xx);
            v[r] += lo; v[4 + r] = fmaf(lo, lo, v[4 + r]); v[8 + r] = fmaf(lo, w[2 * e], v[8 + r]);
            v[r] += hi; v[4 + r] = fmaf(hi, hi, v[4 + r]); v[8 + r] = fmaf(hi, w[2 * e + 1], v[8 + r]);
          }
        }
      }
#pragma unroll
      for (int l = 0; l < 4; l++) {
        const int n = 8 >> l;
        const bool up = lane & (2 * n);
#pragma unroll
        for (int r = 0; r < 8; r++) {
          if (r < n) { const float a = v[r], c = v[n + r]; v[r] = (up ? c : a) + __shfl_xor_sync(~0u, up ? a : c, 2 * n); }
        }
      }
      v[0] += __shfl_xor_sync(~0u, v[0], 1);
      const float sx = __shfl_sync(~0u, v[0], 2 * t), sq = __shfl_sync(~0u, v[0], 8 + 2 * t), sw = __shfl_sync(~0u, v[0], 16 + 2 * t), ws = __shfl_sync(~0u, v[0], 24);
      if (lane < 4) {
        const int row = b * 16 + aw * 4 + lane;
        const float mean = sx * (1.f / DM);
        const float var = fmaxf(fmaf(-mean, mean, sq * (1.f / DM)), 0.f);
        float sd;
        asm("sqrt.approx.ftz.f32 %0, %1;" : "=f"(sd) : "f"(bf_round(bf_round(var) + 1e-5f)));
        const float rstd = rcp(bf_round(sd));
        const float mb = bf_round(mean);
        uint32_t rb = pack_bf16(fmaf(-mb, ws, sw) * rstd, 0.f) & 0xFFFFu;
        rb = (rb & 0x8000u) ? (~rb & 0xFFFFu) : (rb | 0x8000u);
        const uint32_t key = (1u << 27) | (rb << 11) | (uint32_t)(2047 - row);
        if (KEY1) sts_u(sb + MISC + M_KEY + (aw * 4 + lane) * 4, key); else stx1(G.key + row, key);
        G.stats[row] = make_float2(mb, rstd);
      }
    }
    bar_sync<2, 128>();
    if (KEY1 && ltid < 272) stx1(G.key + b * 16 + lane, lds_u(sb + MISC + M_KEY + lane * 4));
    TLS(288, 65);
    sts_u4(sb + A_ONES + (ltid - 256) * 16, make_uint4(0x3F803F80u, 0x3F803F80u, 0x3F803F80u, 0x3F803F80u));
    fence_async_smem();
    asm volatile("bar.arrive 5, 160;" ::: "memory");
    if (ltid == 256) { if (unit && rank == 0) mbar_expect_tx(BAR(B_UP), 2048); mbar_arrive(BAR(B_XS)); }
    bar_sync<2, 128>();
    mbar_wait(BAR(B_XS), 1);
    TLS(288, 70);
    if (NUNIT) {
      if (unit) {
        int r = 0, p = 0;
        uint32_t rel = 0;
        float acc[8];
        uint2 s0, s1;
#pragma unroll
        for (int i = 0; i < 8; i++) acc[i] = 0.f;
        if (MS == 16) mbar_wait(BAR(B_T0), 0); else if (MS) mbar_wait(BAR(B_MS), 0);
#pragma unroll 1
        for (int n = 0; n < 16; n++) {
          if (n == 15) {
            mbar_wait(BAR(B_FAUX), 0);
            s0 = ldx2(G.stats + (~lds_u(sb + MISC + M_IDX + t * 8) & 2047)); s1 = ldx2(G.stats + (~lds_u(sb + MISC + M_IDX + t * 8 + 4) & 2047));
          }
          mbar_wait(BAR(B_MF + r), p);
          if (!(n & 3)) TLS(288, 56 + (n >> 2));
          const uint32_t mo = m_off(r) >> 4, da = (d0 + mo) | (512u << 16), db = (d0 + mo + 512) | (1u << 16);
          const uint32_t hb = 0x40000000u | ((A_ONES >> 4) - 512 - mo);
          wg_fence();
#pragma unroll
          for (int kk = 0; kk < ((MX & 1) ? 1 : 4); kk++) wgmma_ss_n16<1, 0>(acc, mkdesc(da + kk * 128, HI_SW128), mkdesc(db + kk * 2, hb));
          wg_commit();
          wg_wait<1>();
          if (n > 0 && !rel && ltid == 256) mbar_arrive(BAR(B_ME + (r == 0 ? NR - 1 : r - 1)));
          rel = 0;
          const int r0 = r;
          if (++r == NR) { r = 0; p ^= 1; }
        }
        wg_wait<0>();
        reg_fence(acc);
        {
          if (!MW0 && !rel && ltid == 256) mbar_arrive(BAR(B_ME + 15 % NR));
          TLS(288, 71);
          const float v0 = bf_round(fmaf(-__uint_as_float(s0.x), acc[4], acc[0]) * __uint_as_float(s0.y));
          const float v1 = bf_round(fmaf(-__uint_as_float(s1.x), acc[4], acc[1]) * __uint_as_float(s1.y));
          const float v2 = bf_round(fmaf(-__uint_as_float(s0.x), acc[6], acc[2]) * __uint_as_float(s0.y));
          const float v3 = bf_round(fmaf(-__uint_as_float(s1.x), acc[6], acc[3]) * __uint_as_float(s1.y));
          if (rank) {
            asm volatile("{\n.reg .b32 ra, rb;\nmapa.shared::cluster.u32 ra, %0, 0;\nmapa.shared::cluster.u32 rb, %1, 0;\n"
                         "st.async.weak.shared::cluster.mbarrier::complete_tx::bytes.v4.f32 [ra], {%2, %3, %4, %5}, [rb];\n}"
                         ::"r"(mbuf + (ltid - 256) * 16), "r"(BAR(B_UP)), "f"(v0), "f"(v1), "f"(v2), "f"(v3) : "memory");
          } else {
            const float g0 = bf_round(v0 * sigmoid(v0)), g1 = bf_round(v1 * sigmoid(v1)), g2 = bf_round(v2 * sigmoid(v2)), g3 = bf_round(v3 * sigmoid(v3));
            mbar_wait(BAR(B_UP), 0);
            const uint4 uu = lds_u4(mbuf + (ltid - 256) * 16);
            const uint32_t h0 = movmat(pack_bf16(g0 * __uint_as_float(uu.x), g1 * __uint_as_float(uu.y)));
            const uint32_t h1 = movmat(pack_bf16(g2 * __uint_as_float(uu.z), g3 * __uint_as_float(uu.w)));
            uint32_t* ph = G.h + (u >> 1) * 256 + g * 32 + t;
            stx1(ph + ((2 * aw) ^ g) * 4, h0); stx1(ph + ((2 * aw + 1) ^ g) * 4, h1);
          }
          TLS(288, 60);
        }
      }
    }
    if (PH) asm volatile("bar.arrive 3, 192;" ::: "memory");
    {
      const int wd_ = ltid & 63;
      const uint32_t* src = reinterpret_cast<const uint32_t*>(G.part + hg * 544 + (aw >> 1) * 256 + tb * 16) + wd_;
      mbar_wait(MRED == 2 ? BAR(B_ZOK) : BAR(B_EQ + MRW), 0);
      if (MRD) __nanosleep(MRD);
      TLS(256, 48);
      uint32_t v[16];
#pragma unroll 1
      for (uint32_t it = 0; it < SPIN_MAX; it++) {
        uint32_t m = 0;
#pragma unroll
        for (int i = 0; i < 16; i++) v[i] = ldx1(src + i * 8 * 2176);
#pragma unroll
        for (int i = 0; i < 16; i++) m = max(m, v[i]);
        if (!__any_sync(~0u, m == SENT)) break;
      }
      TLS(256, 55);
      float lo[4], hi[4];
#pragma unroll
      for (int i = 0; i < 4; i++) {
        lo[i] = (bf_lo(v[4 * i]) + bf_lo(v[4 * i + 1])) + (bf_lo(v[4 * i + 2]) + bf_lo(v[4 * i + 3]));
        hi[i] = (bf_hi(v[4 * i]) + bf_hi(v[4 * i + 1])) + (bf_hi(v[4 * i + 2]) + bf_hi(v[4 * i + 3]));
      }
      stx1(reinterpret_cast<uint32_t*>(G.fin + hg * 640) + (tb >> 2) * 640 + ((tb >> 1) & 1) * 64 + (tb & 1) * 16 + (aw >> 1) * 32 + ((wd_ >> 2) & 3) * 128 + (wd_ >> 4) * 4 + (wd_ & 3),
           pack_bf16((lo[0] + lo[1]) + (lo[2] + lo[3]), (hi[0] + hi[1]) + (hi[2] + hi[3])));
      TLS(256, 5);
    }
    if (NUNIT) {
      mbar_wait(BAR(B_STG), 0);
      bar_sync<2, 128>();
      if (HW) __nanosleep(HW);
#pragma unroll 1
      for (uint32_t it = 0; it < SPIN_MAX; it++) {
        if (elect_one()) {
          const uint32_t* ph = G.h + (u >> 4) * 7 * 256;
          if (aw == 3) { mbar_expect_tx(BAR(B_HF), 7168); bulk_ld(sb + h_off(3), ph + 768, 2048, BAR(B_HF)); bulk_ld(sb + h_off(5), ph + 1280, 2048, BAR(B_HF)); }
          else bulk_ld(stg + aw * MT + 8192, ph + aw * 256, 1024, BAR(B_HF));
        }
        mbar_wait(BAR(B_HF), it & 1);
        const uint32_t o = (ltid & 63) * 16 + (g >> 1) * 4, o2 = o + (aw >> 1) * 1024;
        const uint32_t m = max(max(lds_u(sb + h_off(0) + (aw >> 1) * MT + o), lds_u(sb + h_off(2) + o)), max(lds_u(sb + h_off(3) + o2), lds_u(sb + h_off(5) + o2)));
        uint32_t bad;
        asm volatile("{\n.reg .pred p, q;\nsetp.eq.u32 p, %1, 0xFFFFFFFF;\nbar.red.or.pred q, 2, 128, p;\nselp.b32 %0, 1, 0, q;\n}" : "=r"(bad) : "r"(m) : "memory");
        if (!__any_sync(~0u, bad)) break;
        __nanosleep(POLLNS);
      }
      TLS(288, 62);
      float acc[4] = {0.f, 0.f, 0.f, 0.f};
      mbar_wait(BAR(B_DF), 0);
      TLS(288, 63);
#pragma unroll 1
      for (int i = 0; i < 7; i++) {
        const uint32_t da = (d0 + (d_off(i) >> 4)) | (512u << 16), db = (d0 + (h_off(i) >> 4)) | (1u << 16);
        wg_fence();
#pragma unroll
        for (int kk = 0; kk < ((MX & 4) ? 1 : 4); kk++) wgmma_ss_n8<1, 0>(acc, mkdesc(da + kk * 128, HI_SW128), mkdesc(db + kk * 2, HI_SW128));
        wg_commit();
      }
      wg_wait<0>();
      reg_fence(acc);
      if (ltid < 258) { if (MC) mbar_arrive_cta(BAR(B_DE), ltid & 1); else mbar_arrive(BAR(B_DE)); }
      {
        uint32_t* py = reinterpret_cast<uint32_t*>(G.y) + u * 512 + t * 128 + aw * 16 + g;
        stx1(py, f2x(acc[0])); stx1(py + 64, f2x(acc[1])); stx1(py + 8, f2x(acc[2])); stx1(py + 72, f2x(acc[3]));
      }
      TLS(288, 69);
      const uint32_t key = lds_u(sb + MISC + M_IDX + (lane & 7) * 4);
      uint32_t rb = (key >> 11) & 0xFFFFu;
      rb = (rb & 0x8000u) ? (rb & 0x7FFFu) : (~rb & 0xFFFFu);
      const float sg = bf_round(sigmoid(__uint_as_float(rb << 16)));
      uint32_t hits = __ballot_sync(~0u, ((~key >> 7) & 15) == tb) & 255u;
      const uint32_t* py = reinterpret_cast<const uint32_t*>(G.y) + (2 * hg + (aw >> 1)) * 512 + (ltid & 63);
      if (hits) {
        sts_u4(mbuf + (ltid - 256) * 16, make_uint4(0, 0, 0, 0));
        bar_sync<2, 128>();
        if (YW >= 0) mbar_wait(BAR(B_EO + YW), 0); else if (YW == -2) mbar_wait(BAR(B_EAUX), 0);
      }
#pragma unroll 1
      while (hits) {
        const int n0 = __ffs(hits) - 1;
        hits &= hits - 1;
        const int n1 = hits ? __ffs(hits) - 1 : n0;
        hits &= hits - 1;
        uint32_t v[16];
#pragma unroll 1
        for (uint32_t it = 0; it < SPIN_MAX; it++) {
          uint32_t m = 0;
#pragma unroll
          for (int i = 0; i < 8; i++) { v[i] = ldx1(py + n0 * 64 + i * 8192); v[8 + i] = ldx1(py + n1 * 64 + i * 8192); }
#pragma unroll
          for (int i = 0; i < 16; i++) m = max(m, v[i]);
          if (!__any_sync(~0u, m == SENT)) break;
          __nanosleep(POLLNS);
        }
#pragma unroll
        for (int e = 0; e < 2; e++) {
          const uint32_t* w8 = v + 8 * e;
          const float y = ((__uint_as_float(w8[0]) + __uint_as_float(w8[1])) + (__uint_as_float(w8[2]) + __uint_as_float(w8[3]))) +
                          ((__uint_as_float(w8[4]) + __uint_as_float(w8[5])) + (__uint_as_float(w8[6]) + __uint_as_float(w8[7])));
          const int n = e ? n1 : n0;
          sts_h(mbuf + (aw >> 1) * 1024 + n * 128 + ((((ltid >> 3) & 7) ^ n) << 4) + (lane & 7) * 2, bf_round(y) * __shfl_sync(~0u, sg, n));
        }
      }
    }
    if (!NUNIT && ltid < 258) mbar_arrive(BAR(B_DE));
    fence_async_smem();
    bar_sync<2, 128>();
    TLS(288, 33);
    if (ltid == 288) mbar_arrive(BAR(B_MOE));
  } else {
    asm volatile("setmaxnreg.inc.sync.aligned.u32 %0;" ::"n"(CON_REGS));
    if (MC) asm volatile("barrier.cluster.wait.aligned;" ::: "memory");
    const int w = warp >> 2, wq = warp & 3, tid = ltid;
    const bool lead = (tid & 127) == 0;
    const uint32_t dA = (d0 + w * 512) | (1u << 16);
    const uint32_t dB = d0 | (512u << 16);
    auto release = [&](int bar) { if (lead) mbar_arrive(BAR(bar)); };
    auto release2 = [&](int bar) {
      if (MC) { if ((tid & 127) < 2) mbar_arrive_cta(BAR(bar), tid & 1); } else release(bar);
    };
    float aq[64], ak[64], av[64];
#pragma unroll
    for (int i = 0; i < 64; i++) aq[i] = ak[i] = av[i] = 0.f;
    auto q_step = [&](uint32_t bar, int p, uint32_t xs, uint32_t qs) {
      mbar_wait_b(bar, p);
      wg_fence();
#pragma unroll
      for (int kk = 0; kk < 4; kk++)
        wgmma_ss_n128<0, 1>(aq, mkdesc(dA + xs * 1024 + kk * 2, HI_SW128), mkdesc(dB + qs * 1024 + kk * 128, HI_SW128));
      wg_commit();
    };
    const uint32_t dT = dB + w * 512, dX = d0 | (1u << 16);
    auto t_step = [&](float (&a)[64], uint32_t ws, uint32_t xs) {
      wg_fence();
#pragma unroll
      for (int kk = 0; kk < 4; kk++)
        wgmma_ss_n128<1, 0>(a, mkdesc(dT + ws * 1024 + kk * 128, HI_SW128), mkdesc(dX + xs * 1024 + kk * 2, HI_SW128));
      wg_commit();
    };
    {
      int s = 0, p = 0, sp = 2;
#pragma unroll 1
      for (int e = 0; e < NF; e++) {
        TLS(0, 16 + e);
        if (((MS && MS < NF) || (DS && DS < NF)) && e == (MS ? MS : DS)) release(B_MS);
        q_step(BAR(B_FXQ + s), p, s, 3 + s);
        wg_wait<1>();
        if (e > 0) release2(B_E + sp);
        mbar_wait(BAR(B_FKV + s), p);
        t_step(ak, 6 + 2 * s, s);
        if (R5) mbar_wait(BAR(B_FV + s), p);
        t_step(av, 7 + 2 * s, s);
        if (R5 && e == NF - 1) { wg_wait<1>(); release2(B_EK + s); }
        sp = s;
        if (++s == 3) { s = 0; p ^= 1; }
      }
#pragma unroll 1
      for (int e = NF; e < 16; e++) {
        TLS(0, 16 + e);
        if (((MS >= NF && MS < 16) || DS >= NF) && e == (MS ? MS : DS)) release(B_MS);
        if (ST && e == 16 - ST && w == 1) mbar_wait(BAR(B_GT), 0);
        mbar_wait(BAR(B_FXQ + s), p);
        mbar_wait(BAR(B_FKV + s), p);
        t_step(ak, R5 ? (K_SLOTS >> (4 * (e - 10))) & 15u : 6 + 2 * s, x_slot(e, s));
        wg_wait<1>();
        release2(B_E + sp);
        if (R5) mbar_wait(BAR(B_FV + s), p);
        t_step(av, R5 ? (V_SLOTS >> (4 * (e - 10))) & 15u : 7 + 2 * s, x_slot(e, s));
        if (ST && e == 15 && tid == 0) mbar_arrive(BAR(B_GT));
        if (R5) { wg_wait<1>(); release2(B_EK + s); }
        sp = s;
        if (++s == 3) { s = 0; p ^= 1; }
      }
    }
    const uint32_t aux = sb;
    mbar_wait(BAR(B_FAUX), 0);
    const int row0 = w * 64 + wq * 16 + g;
    const float ck0 = lds_f(aux + A_CS + 512 + row0 * 4), ck1 = lds_f(aux + A_CS + 512 + (row0 + 8) * 4);
    const float cv0 = lds_f(aux + A_CS + 1024 + row0 * 4), cv1 = lds_f(aux + A_CS + 1024 + (row0 + 8) * 4);
    const uint32_t moff = (uint32_t)(w * 64 + wq * 16 + (lane & 15)) * 128 + (((lane >> 4) ^ (lane & 7)) << 4);
    const uint32_t sta = aux + A_ST + t * 16;
    float kvp[36], ao[64];
    uint32_t xr[32];
    float nm0, nm1, rs0, rs1;
    auto row_stats = [&]() {
      const float2 st0 = lds_f2(aux + A_ST + row0 * 8), st1 = lds_f2(aux + A_ST + (row0 + 8) * 8);
      nm0 = -st0.x; nm1 = -st1.x; rs0 = st0.y; rs1 = st1.y;
    };
    auto ld_x = [&]() {
#pragma unroll
      for (int j = 0; j < 16; j += 2) ldsm4(sb + (j < 8 ? SX14 : SX15) * SLOT + (moff ^ ((j & 7) << 4)), xr[2 * j], xr[2 * j + 1], xr[2 * j + 2], xr[2 * j + 3]);
    };
    auto resid = [&]() {
      const float c0 = 1.f + rs0, c1 = 1.f + rs1, e0 = nm0 * rs0, e1 = nm1 * rs1;
#pragma unroll
      for (int j = 0; j < 16; j++) {
        ao[4 * j + 0] = fmaf(bf_lo(xr[2 * j]), c0, e0); ao[4 * j + 1] = fmaf(bf_hi(xr[2 * j]), c0, e0);
        ao[4 * j + 2] = fmaf(bf_lo(xr[2 * j + 1]), c1, e1); ao[4 * j + 3] = fmaf(bf_hi(xr[2 * j + 1]), c1, e1);
      }
    };
    {
      uint32_t pa[32];
      float4 st[16];
      auto ld = [&](int j) { st[j] = lds_f4(sta + j * 64); };
      auto k_blk = [&](int c) {
#pragma unroll
        for (int i = 0; i < 2; i++) {
          const float4 u = st[2 * c + i];
          const float l0 = u.y * 1.4426950408889634f, l1 = u.w * 1.4426950408889634f;
          const float* a = ak + 8 * c + 4 * i;
          pa[4 * c + 2 * i] = phi2(fmaf(-u.x, ck0, a[0]), u.y, l0, fmaf(-u.z, ck0, a[1]), u.w, l1);
          pa[4 * c + 2 * i + 1] = phi2(fmaf(-u.x, ck1, a[2]), u.y, l0, fmaf(-u.z, ck1, a[3]), u.w, l1);
        }
      };
      const uint32_t voff = sb + w * 8192 + (uint32_t)(8 * (lane >> 4) + (lane & 7)) * 128 + (((2 * wq + ((lane >> 3) & 1)) ^ (lane & 7)) << 4);
      auto v_blk = [&](int c) {
        uint32_t r[4];
#pragma unroll
        for (int i = 0; i < 2; i++) {
          const float4 u = st[2 * c + i];
          const float* a = av + 8 * c + 4 * i;
          r[2 * i] = pack_bf16(fmaf(-u.x, cv0, a[0]) * u.y, fmaf(-u.z, cv0, a[1]) * u.w);
          r[2 * i + 1] = pack_bf16(fmaf(-u.x, cv1, a[2]) * u.y, fmaf(-u.z, cv1, a[3]) * u.w);
        }
        stsm4t(voff + (c < 4 ? S_V0 : S_V1) * SLOT + (c & 3) * 2048, r[0], r[1], r[2], r[3]);
      };
      auto kv_mma = [&](int c) {
        const uint32_t bo = (c < 4 ? S_V0 : S_V1) * 1024 + w * 512 + (c & 3) * 128;
        const uint64_t bb = mkdesc((d0 + bo) | (((A_ONES >> 4) - bo) << 16), HI_SW128);
        if (c == 0) wgmma_rz_n72<1>(kvp, pa[4 * c], pa[4 * c + 1], pa[4 * c + 2], pa[4 * c + 3], bb);
        else wgmma_rs_n72<1>(kvp, pa[4 * c], pa[4 * c + 1], pa[4 * c + 2], pa[4 * c + 3], bb);
      };
      ld(0); ld(1);
      wg_wait<0>();
      reg_fence(ak); reg_fence(av);
      TLS(0, 2);
      if (!R5) release2(B_E);
      release(B_T0);
      if (LQ) { v_blk(0); ld(2); ld(3); } else { ld(2); ld(3); v_blk(0); }
      ld(4); ld(5); v_blk(1); k_blk(0);
      ld(6); ld(7); v_blk(2); ld(8); ld(9); v_blk(3); k_blk(1);
      ld(10); ld(11); v_blk(4); ld(12); ld(13); v_blk(5); k_blk(2);
      ld(14); ld(15); v_blk(6); v_blk(7); k_blk(3);
      if (RL) { ld(8); ld(9); }
#pragma unroll
      for (int c = 4; c < KS; c++) k_blk(c);
      TLS(0, 3);
      fence_async_smem();
      asm volatile("bar.sync %0, 128;" ::"r"(3 + w) : "memory");
      if (XP == 0) ld_x();
      wg_fence();
#pragma unroll
      for (int c = 0; c < KS; c++) kv_mma(c);
      wg_commit();
#pragma unroll
      for (int c = KS; c < 8; c++) {
        if (RL && c < 7) { ld(2 * c + 2); ld(2 * c + 3); }
        k_blk(c);
        wg_fence();
        kv_mma(c);
        wg_commit();
      }
      if (XP == 3 && (RK == 0 || RK == 9)) ld_x();
      if (QE) { q_step(BAR(B_FQ), 0, SXQ0, QW_SLOTS & 15u); wg_wait<1>(); } else wg_wait<0>();
      reg_fence(kvp);
      auto hand_back = [&]() { release2(B_STG); __syncwarp(); };
      if (!SF) hand_back();
      TLS(0, 4);
      uint4* pp = G.part + b * 544;
      uint32_t pk[8];
#pragma unroll
      for (int j = 0; j < 8; j++) pk[j] = wq >= 2 ? pack_bf16(kvp[16 + 2 * j], kvp[17 + 2 * j]) : pack_bf16(kvp[2 * j], kvp[2 * j + 1]);
      stx4(pp + tid, pk[0], pk[2], pk[4], pk[6]);
      stx4(pp + 256 + tid, pk[1], pk[3], pk[5], pk[7]);
      if (t == 0) stx2(reinterpret_cast<uint2*>(pp + 512) + (tid >> 2), f2x(kvp[32]), f2x(kvp[34]));
      if (SF == 1) hand_back();
      if (XP == 1) ld_x();
      if (!QE) q_step(BAR(B_FQ), 0, SXQ0, QW_SLOTS & 15u);
      if (XP == 2) ld_x();
      if (SF == 2) hand_back();
      if (RK == 0 || RK == 9) {
        uint32_t chk = 0;
#pragma unroll
        for (int j = 0; j < 8; j++) chk ^= xr[4 * j];
        asm volatile("{\n.reg .pred p;\nsetp.eq.u32 p, %0, 0x7FC17FC3;\n@p st.shared.u32 [%1], %0;\n}" ::"r"(chk), "r"(sb + MISC + M_DUM) : "memory");
      }
      const int wd_ = wq * 16 + (lane & 15);
      const uint32_t* src = reinterpret_cast<const uint32_t*>(G.part + ((lane >> 4) * 64 + hg) * 544 + w * 256 + tb * 16) + wd_;
      uint32_t* fin = reinterpret_cast<uint32_t*>(G.fin + hg * 640) + (tb >> 2) * 640 + ((tb >> 1) & 1) * 64 + (tb & 1) * 16 + w * 32 + ((wd_ >> 2) & 3) * 128 + wq * 4 + (wd_ & 3);
      uint32_t v[8];
      auto part_load = [&]() {
#pragma unroll
        for (int i = 0; i < 8; i++) v[i] = ldx1(src + i * 8 * 2176);
      };
#pragma unroll
      for (int k = 1; k < NQ; k++) {
        if (SQ && k == NQ - SQ && w == 1) mbar_wait(BAR(B_GQ), 0);
        q_step(BAR(B_FQ + k), 0, (QX_SLOTS >> (4 * k)) & 15u, (QW_SLOTS >> (4 * k)) & 15u);
        if (SQ && k == NQ - 1 && tid == 0) mbar_arrive(BAR(B_GQ));
        TLS(0, 48 + k);
        if (!MRED && k == PLP) part_load();
        if (!MRED && k == PLC) {
#pragma unroll 1
          for (uint32_t it = 0; it < SPIN_MAX; it++) {
            if (!__any_sync(~0u, max(max(max(v[0], v[1]), max(v[2], v[3])), max(max(v[4], v[5]), max(v[6], v[7]))) == SENT)) break;
            part_load();
          }
          float lo = ((bf_lo(v[0]) + bf_lo(v[1])) + (bf_lo(v[2]) + bf_lo(v[3]))) + ((bf_lo(v[4]) + bf_lo(v[5])) + (bf_lo(v[6]) + bf_lo(v[7])));
          float hi = ((bf_hi(v[0]) + bf_hi(v[1])) + (bf_hi(v[2]) + bf_hi(v[3]))) + ((bf_hi(v[4]) + bf_hi(v[5])) + (bf_hi(v[6]) + bf_hi(v[7])));
          lo += __shfl_xor_sync(~0u, lo, 16); hi += __shfl_xor_sync(~0u, hi, 16);
          if (lane < 16) stx1(fin, pack_bf16(lo, hi));
          TLS(0, 5);
        }
        wg_wait<1>();
        release2(B_EQ + k - 1);
        if (k == RK) { row_stats(); ld_x(); resid(); reg_fence(ao); }
      }
      TLS(0, 13);
      mbar_wait(BAR(B_CQ), 0);
    }
    wg_wait<0>();
    reg_fence(aq);
    TLS(0, 15);
    if (RK == 0 || RK == 9) row_stats();
    const float rl0 = rs0 * 1.4426950408889634f, rl1 = rs1 * 1.4426950408889634f;
    uint32_t pq[32];
#pragma unroll
    for (int j = 0; j < 16; j++) {
      const float2 c = lds_f2(aux + A_CS + (j * 8 + 2 * t) * 4);
      const float* a = aq + 4 * j;
      pq[2 * j] = phi2(fmaf(nm0, c.x, a[0]), rs0, rl0, fmaf(nm0, c.y, a[1]), rs0, rl0);
      pq[2 * j + 1] = phi2(fmaf(nm1, c.x, a[2]), rs1, rl1, fmaf(nm1, c.y, a[3]), rs1, rl1);
    }
    TLS(0, 6);
    if (RK == 9) { resid(); if (RF) reg_fence(ao); }
    mbar_wait_b(BAR(MFIN ? B_KV4 : B_KVB), 0);
    TLS(0, 7);
    uint32_t of[32];
    uint4* mine = G.o + (tb * 32 + hg) * 512 + warp * 64 + g * 4 + (t ^ (g >> 1));
    const uint32_t dW = d0 | (256u << 16);
    auto o_store = [&](int h) {
#pragma unroll
      for (int c = 0; c < 2; c++) stx4(mine + h * 4096 + c * 32, of[8 * h + c], of[8 * h + 2 + c], of[8 * h + 4 + c], of[8 * h + 6 + c]);
    };
    auto out_step = [&](uint32_t slot, const uint32_t* a) {
      const uint32_t d = dW + slot * 1024;
      wg_fence();
#pragma unroll
      for (int kk = 0; kk < 4; kk++) wgmma_rs_n128<1>(ao, a[4 * kk], a[4 * kk + 1], a[4 * kk + 2], a[4 * kk + 3], mkdesc(d + (kk >> 1) * 512 + (kk & 1) * 128, HI_SW128));
      wg_commit();
    };
    uint4 v[NDIR][4];
    auto ld_o = [&](int k) {
      const uint4* p0 = mine + (slab(2 * k, hg) - hg) * 512;
      const uint4* p1 = mine + (slab(2 * k + 1, hg) - hg) * 512;
      v[k][0] = ldx4(p0); v[k][1] = ldx4(p0 + 32); v[k][2] = ldx4(p1); v[k][3] = ldx4(p1 + 32);
    };
    auto ld_all = [&]() {
#pragma unroll
      for (int k = 0; k < NDIR; k++) ld_o(k);
    };
    {
      float oa[4][20];
      const uint32_t dK = (d0 + S_KVB * 1024) | (8u << 16);
      wg_fence();
#pragma unroll
      for (int h = 0; h < 4; h++) {
        wgmma_rz_n40<1>(oa[h], pq[8 * h], pq[8 * h + 1], pq[8 * h + 2], pq[8 * h + 3], mkdesc(dK + h * 160, HI_NOSW));
        wgmma_rs_n40<1>(oa[h], pq[8 * h + 4], pq[8 * h + 5], pq[8 * h + 6], pq[8 * h + 7], mkdesc(dK + h * 160 + 16, HI_NOSW));
        if (h == 0 || h == 3) wg_commit();
      }
      auto norm = [&](int h) {
        const float r0 = rcp(oa[h][16] + 1e-6f), r1 = rcp(oa[h][18] + 1e-6f);
#pragma unroll
        for (int j = 0; j < 4; j++) {
          of[8 * h + 2 * j] = pack_bf16(oa[h][4 * j] * r0, oa[h][4 * j + 1] * r0);
          of[8 * h + 2 * j + 1] = pack_bf16(oa[h][4 * j + 2] * r1, oa[h][4 * j + 3] * r1);
        }
      };
      wg_wait<1>();
      reg_fence(oa[0]);
      norm(0);
      if (LE == 4) ld_all();
      o_store(0);
      if (LE == 3) ld_all();
      TLS(0, 8);
      wg_wait<0>();
      reg_fence(oa[1]); reg_fence(oa[2]); reg_fence(oa[3]);
      TLP_(0);
      release(B_EAUX);
      norm(1);
      if (OS1 == 3) o_store(1);
      if (E7 && NP == 0 && SL7 && hg == 7) o_store(1);
      if (NP == 0) { norm(2); norm(3); }
      if (E7 && NP == 0 && SL7 && hg == 7) { o_store(2); o_store(3); }
      TLP_(1);
      mbar_wait_b(BAR(B_FWO), 0);
      TLP_(2);
      if (RK == 0) resid();
      if (LE == 2) ld_all();
      TLP_(3);
      out_step(WO_SLOTS & 15u, of);
      TLP_(4);
      if (NP == 1) { norm(2); norm(3); }
      if (LE == 1) ld_all();
      if (LE == 5) ld_o(0);
    }
    if (OS1 == 0) o_store(1);
    mbar_wait(BAR(B_FWO + 1), 0);
    TLP_(5);
    out_step((WO_SLOTS >> 4) & 15u, of + 16);
    TLP_(6);
    const bool early = SL7 && hg == 7;
    if (OS1 == 1 && !(E7 && early)) o_store(1);
    TLP_(7);
    if (early && !E7) { o_store(2); o_store(3); }
    {
      if (DW) __nanosleep(DW);
      if (LE == 0) ld_all();
      if (LE == 5 && NDIR > 1) ld_o(NDIR - 1);
      if (OS1 == 2 && !(E7 && early)) o_store(1);
#pragma unroll
      for (int k = 0; k < NDIR; k++) {
#pragma unroll 1
        for (uint32_t it = 0; it < SPIN_MAX; it++) {
          if (!__any_sync(~0u, max(max(v[k][0].x, v[k][1].x), max(v[k][2].x, v[k][3].x)) == SENT)) break;
#pragma unroll
          for (int j = k; j < (LE == 5 ? k + 1 : NDIR); j++) ld_o(j);
        }
        TLP_(8);
        const uint32_t a[16] = {v[k][0].x, v[k][1].x, v[k][0].y, v[k][1].y, v[k][0].z, v[k][1].z, v[k][0].w, v[k][1].w,
                                v[k][2].x, v[k][3].x, v[k][2].y, v[k][3].y, v[k][2].z, v[k][3].z, v[k][2].w, v[k][3].w};
        mbar_wait(BAR(B_FWO + 2 + k), 0);
        TLS(0, 34 + k);
        out_step((WO_SLOTS >> (8 + 4 * k)) & 15u, a);
        TLP_(9);
        if (k) { wg_wait<1>(); release2(B_EO); }
      }
      if (!early) o_store(2);
    }
    auto routed = [&]() {
      mbar_wait(BAR(B_MOE), 0);
      const float2 kk = lds_f2(sb + MISC + M_IDX + t * 8);
      const int k0 = (int)(~__float_as_uint(kk.x) & 2047u) - tb * 128, k1 = (int)(~__float_as_uint(kk.y) & 2047u) - tb * 128;
      if (NUNIT && __any_sync(~0u, (k0 >> 6) == w || (k1 >> 6) == w)) {
        const uint32_t a0 = (k0 == row0 ? 0x3F80u : 0u) | (k1 == row0 ? 0x3F800000u : 0u);
        const uint32_t a1 = (k0 == row0 + 8 ? 0x3F80u : 0u) | (k1 == row0 + 8 ? 0x3F800000u : 0u);
        wg_fence();
        wgmma_rs_n128<1>(ao, a0, a1, 0u, 0u, mkdesc((d0 + ((MISC + M_MOE) >> 4)) | (64u << 16), 0x40000000u));
        wg_commit();
      }
    };
    auto out_half = [&](int h, const float* v) {
      const uint32_t ost = sb + (w ? S_D1 : S_D0) * SLOT + wq * 4096 + h * 2048;
#pragma unroll
      for (int j = 0; j < 8; j += 2)
        stsm4(ost + ((moff & 2047) ^ (j << 4)), pack_bf16(v[4 * j], v[4 * j + 1]), pack_bf16(v[4 * j + 2], v[4 * j + 3]),
              pack_bf16(v[4 * j + 4], v[4 * j + 5]), pack_bf16(v[4 * j + 6], v[4 * j + 7]));
      if (OUTV == 3 || (OUTV == 4 && h == 0)) {
        __syncwarp();
        __nv_bfloat16* dst = outp + (size_t)(tb * 128 + warp * 16 + (lane >> 3)) * DM + hg * 128 + h * 64 + (lane & 7) * 8;
#pragma unroll
        for (int i = 0; i < 4; i++) {
          const int r = 4 * i + (lane >> 3);
          const uint4 u4 = lds_u4(ost + r * 128 + (((lane & 7) ^ (r & 7)) << 4));
          asm volatile("st.global.v4.u32 [%0], {%1,%2,%3,%4};" ::"l"(dst + (size_t)i * 4 * DM), "r"(u4.x), "r"(u4.y), "r"(u4.z), "r"(u4.w) : "memory");
        }
        return;
      }
      fence_async_smem();
      __syncwarp();
      if (elect_one()) {
        asm volatile("cp.async.bulk.tensor.2d.global.shared::cta.bulk_group [%0, {%2, %3}], [%1];" ::"l"(&tmOut), "r"(ost), "r"(hg * 128 + h * 64), "r"(tb * 128 + warp * 16) : "memory");
        if (h) asm volatile("cp.async.bulk.commit_group;\ncp.async.bulk.wait_group.read 0;" ::: "memory");
      }
      __syncwarp();
    };
    bool done = false;
    {
      const uint32_t dO = (d0 + w * 256) | (1u << 16);
      auto step = [&](int i, int r, int p, uint32_t as, uint32_t ws) {
        mbar_wait(BAR(B_FWO + i), 0);
        mbar_wait(BAR(B_VAL + r), p);
        TLS(0, 32 + i);
        const uint32_t da = dO + as * 1024, db = dW + ws * 1024;
        wg_fence();
#pragma unroll
        for (int kk = 0; kk < 4; kk++)
          wgmma_ss_n128<0, 1>(ao, mkdesc(da + (kk >> 1) * 512 + (kk & 1) * 2, HI_SW64), mkdesc(db + (kk >> 1) * 512 + (kk & 1) * 128, HI_SW128));
        wg_commit();
      };
      uint64_t tbl = WO_SLOTS >> (4 * I0);
      int r = 0, p = 0, rp = 0;
#pragma unroll 1
      for (int i = I0; i < 12; i++) {
        step(i, r, p, (A_SLOTS >> (4 * r)) & 15u, (uint32_t)tbl & 15u);
        tbl >>= 4;
#pragma unroll
        for (int c = 0; c < 2; c++)
          if (i == OS3 + c && !early) stx4(mine + 3 * 4096 + c * 32, of[24 + c], of[26 + c], of[28 + c], of[30 + c]);
        wg_wait<1>();
        if (i > I0) release(B_EA + rp);
        rp = r;
        if (++r == NA) { r = 0; p ^= 1; }
        if (i >= 3 && i <= 9) release2(B_EO + i - 3);
      }
      if (SPL && w == 1) {
        float bl[32], bh[32];
        mbar_wait(BAR(B_GO), 0);
        routed();
#pragma unroll
        for (int h = 0; h < 2; h++) {
#pragma unroll
          for (int i = 12; i < 16; i++) {
            const int r_ = (i - I0) % NA;
            if (h == 0) { mbar_wait(BAR(B_FWO + i), 0); mbar_wait(BAR(B_VAL + r_), ((i - I0) / NA) & 1); }
            const uint32_t da = dO + ((A_SLOTS >> (4 * r_)) & 15u) * 1024, db = dW + ((uint32_t)(WO_SLOTS >> (4 * i)) & 15u) * 1024 + h * 256;
            if (h == 0 || i == 12) wg_fence();
#pragma unroll
            for (int kk = 0; kk < 4; kk++) {
              const uint64_t a = mkdesc(da + (kk >> 1) * 512 + (kk & 1) * 2, HI_SW64), bb = mkdesc(db + (kk >> 1) * 512 + (kk & 1) * 128, HI_SW128);
              if (i == 12 && kk == 0) wgmma_sz_n64<0, 1>(h ? bh : bl, a, bb); else wgmma_ss_n64<0, 1>(h ? bh : bl, a, bb);
            }
          }
          wg_commit();
        }
        wg_wait<1>();
        reg_fence(ao); reg_fence(bl);
#pragma unroll
        for (int j = 0; j < 32; j++) bl[j] += ao[j];
        out_half(0, bl);
        wg_wait<0>();
        reg_fence(bh);
#pragma unroll
        for (int j = 0; j < 32; j++) bh[j] += ao[32 + j];
        out_half(1, bh);
        done = true;
      } else
#pragma unroll
      for (int i = 12; i < 16; i++) {
        if (i == 16 - STAG && w == 1) mbar_wait(BAR(B_GO), 0);
        step(i, (i - I0) % NA, ((i - I0) / NA) & 1, (A_SLOTS >> (4 * ((i - I0) % NA))) & 15u, (uint32_t)(WO_SLOTS >> (4 * i)) & 15u);
        if (STAG && i == 15 - GOE && tid == 0) mbar_arrive(BAR(B_GO));
      }
    }
    if (!done) {
      routed();
      wg_wait<0>();
      reg_fence(ao);
      TLS(0, 10);
      out_half(0, ao);
      out_half(1, ao + 32);
    }
    TLS(0, 11);
    TLS(128, 9);
  }
}

typedef CUresult (*EncFn)(CUtensorMap*, CUtensorMapDataType, cuuint32_t, void*, const cuuint64_t*, const cuuint64_t*, const cuuint32_t*,
                          const cuuint32_t*, CUtensorMapInterleave, CUtensorMapSwizzle, CUtensorMapL2promotion, CUtensorMapFloatOOBfill);

void make_map2(EncFn enc, CUtensorMap* m, void* p, uint64_t rows, uint64_t cols, uint32_t brows, CUtensorMapL2promotion promo) {
  cuuint64_t gd[2] = {cols, rows}, gs[1] = {cols * 2};
  cuuint32_t bd[2] = {64, brows}, es[2] = {1, 1};
  enc(m, CU_TENSOR_MAP_DATA_TYPE_BFLOAT16, 2, p, gd, gs, bd, es, CU_TENSOR_MAP_INTERLEAVE_NONE, CU_TENSOR_MAP_SWIZZLE_128B, promo,
      CU_TENSOR_MAP_FLOAT_OOB_FILL_NONE);
}
void make_map3(EncFn enc, CUtensorMap* m, void* p, uint64_t rows, uint64_t cols, uint32_t brows) {
  cuuint64_t gd[3] = {64, rows, cols / 64}, gs[2] = {cols * 2, 128};
  cuuint32_t bd[3] = {64, brows, 2}, es[3] = {1, 1, 1};
  enc(m, CU_TENSOR_MAP_DATA_TYPE_BFLOAT16, 3, p, gd, gs, bd, es, CU_TENSOR_MAP_INTERLEAVE_NONE, CU_TENSOR_MAP_SWIZZLE_128B,
      CU_TENSOR_MAP_L2_PROMOTION_L2_256B, CU_TENSOR_MAP_FLOAT_OOB_FILL_NONE);
}

}

extern "C" void kernel_launch(void* const* d_in, const int* in_sizes, int n_in, void* d_out, int out_size) {
  static EncFn enc = nullptr;
  static int by_sm = 0;
  if (!enc) {
    void* fn = nullptr;
    cudaDriverEntryPointQueryResult qr;
    cudaGetDriverEntryPoint("cuTensorMapEncodeTiled", &fn, cudaEnableDefault, &qr);
    enc = (EncFn)fn;
    int dev = 0, sms = 0;
    cudaGetDevice(&dev);
    cudaDeviceGetAttribute(&sms, cudaDevAttrMultiProcessorCount, dev);
    by_sm = MAP == 2 && sms == NCTA + NSVC;
    cudaFuncSetAttribute(fused_kernel, cudaFuncAttributeMaxDynamicSharedMemorySize, SMEM_BYTES);
  }
  CUtensorMap tmX, tmW, tmWo, tmOut, tmG, tmU, tmD, tmR, tmWp;
  {
    cuuint64_t gd[5] = {64, 2, 128, 4, 16}, gs[4] = {2048, 16384, 4096, 128};
    cuuint32_t bd[5] = {64, 2, 4, 4, 2}, es[5] = {1, 1, 1, 1, 1};
    enc(&tmWp, CU_TENSOR_MAP_DATA_TYPE_BFLOAT16, 5, d_in[2], gd, gs, bd, es, CU_TENSOR_MAP_INTERLEAVE_NONE, CU_TENSOR_MAP_SWIZZLE_128B,
        CU_TENSOR_MAP_L2_PROMOTION_L2_256B, CU_TENSOR_MAP_FLOAT_OOB_FILL_NONE);
  }
  make_map2(enc, &tmR, d_in[0], SEQ, DM, 1, CU_TENSOR_MAP_L2_PROMOTION_L2_128B);
  make_map2(enc, &tmX, d_in[0], SEQ, DM, 128, XPROMO);
  make_map3(enc, &tmW, d_in[1], DM, 3 * DM, 64);
  make_map3(enc, &tmWo, d_in[2], DM, DM, 32);
  if (OUTV) make_map2(enc, &tmOut, d_out, SEQ, DM, 16, CU_TENSOR_MAP_L2_PROMOTION_L2_128B); else make_map3(enc, &tmOut, d_out, SEQ, DM, 64);
  make_map2(enc, &tmG, d_in[5], DM, FF, 64, MPROMO);
  make_map2(enc, &tmU, d_in[6], DM, FF, 64, MPROMO);
  make_map2(enc, &tmD, d_in[7], FF, DM, 64, MPROMO);
  typedef const __nv_bfloat16* P;
  cudaLaunchConfig_t cfg = {};
  cfg.gridDim = dim3(NCTA + NSVC); cfg.blockDim = dim3(512); cfg.dynamicSmemBytes = SMEM_BYTES; cfg.stream = cudaStreamPerThread;
  cudaLaunchAttribute at[1];
  at[0].id = cudaLaunchAttributeClusterDimension;
  at[0].val.clusterDim.x = 2; at[0].val.clusterDim.y = 1; at[0].val.clusterDim.z = 1;
  cfg.attrs = at; cfg.numAttrs = 1;
  cudaLaunchKernelEx(&cfg, fused_kernel, (P)d_in[0], (P)d_in[1], (P)d_in[2], (P)d_in[4], (P)d_in[7], (__nv_bfloat16*)d_out, by_sm, tmX, tmW, tmWo, tmOut, tmG, tmU, tmD, tmR, tmWp);
}
```

```cpp
#include <cuda_runtime.h>
#include <cuda.h>
#include <cuda_bf16.h>
#include <stdint.h>

namespace {

template <int TA, int TB> __device__ __forceinline__ void wgmma_ss_n128(float (&d)[64], uint64_t da, uint64_t db) {
  asm volatile("wgmma.mma_async.sync.aligned.m64n128k16.f32.bf16.bf16 "
  "{%0,%1,%2,%3,%4,%5,%6,%7,%8,%9,%10,%11,%12,%13,%14,%15,%16,%17,%18,%19,%20,%21,%22,%23,%24,%25,%26,%27,%28,%29,%30,%31,%32,%33,%34,%35,%36,%37,%38,%39,%40,%41,%42,%43,%44,%45,%46,%47,%48,%49,%50,%51,%52,%53,%54,%55,%56,%57,%58,%59,%60,%61,%62,%63}, "
  "%64, %65, 1, 1, 1, %66, %67;"
  : "+f"(d[0]),"+f"(d[1]),"+f"(d[2]),"+f"(d[3]),"+f"(d[4]),"+f"(d[5]),"+f"(d[6]),"+f"(d[7]),"+f"(d[8]),"+f"(d[9]),"+f"(d[10]),"+f"(d[11]),"+f"(d[12]),"+f"(d[13]),"+f"(d[14]),"+f"(d[15]),"+f"(d[16]),"+f"(d[17]),"+f"(d[18]),"+f"(d[19]),"+f"(d[20]),"+f"(d[21]),"+f"(d[22]),"+f"(d[23]),"+f"(d[24]),"+f"(d[25]),"+f"(d[26]),"+f"(d[27]),"+f"(d[28]),"+f"(d[29]),"+f"(d[30]),"+f"(d[31]),"+f"(d[32]),"+f"(d[33]),"+f"(d[34]),"+f"(d[35]),"+f"(d[36]),"+f"(d[37]),"+f"(d[38]),"+f"(d[39]),"+f"(d[40]),"+f"(d[41]),"+f"(d[42]),"+f"(d[43]),"+f"(d[44]),"+f"(d[45]),"+f"(d[46]),"+f"(d[47]),"+f"(d[48]),"+f"(d[49]),"+f"(d[50]),"+f"(d[51]),"+f"(d[52]),"+f"(d[53]),"+f"(d[54]),"+f"(d[55]),"+f"(d[56]),"+f"(d[57]),"+f"(d[58]),"+f"(d[59]),"+f"(d[60]),"+f"(d[61]),"+f"(d[62]),"+f"(d[63])
  : "l"(da), "l"(db), "n"(TA), "n"(TB));
}
template <int TA, int TB> __device__ __forceinline__ void wgmma_ss_n64(float (&d)[32], uint64_t da, uint64_t db) {
  asm volatile("wgmma.mma_async.sync.aligned.m64n64k16.f32.bf16.bf16 "
  "{%0,%1,%2,%3,%4,%5,%6,%7,%8,%9,%10,%11,%12,%13,%14,%15,%16,%17,%18,%19,%20,%21,%22,%23,%24,%25,%26,%27,%28,%29,%30,%31}, "
  "%32, %33, 1, 1, 1, %34, %35;"
  : "+f"(d[0]),"+f"(d[1]),"+f"(d[2]),"+f"(d[3]),"+f"(d[4]),"+f"(d[5]),"+f"(d[6]),"+f"(d[7]),"+f"(d[8]),"+f"(d[9]),"+f"(d[10]),"+f"(d[11]),"+f"(d[12]),"+f"(d[13]),"+f"(d[14]),"+f"(d[15]),"+f"(d[16]),"+f"(d[17]),"+f"(d[18]),"+f"(d[19]),"+f"(d[20]),"+f"(d[21]),"+f"(d[22]),"+f"(d[23]),"+f"(d[24]),"+f"(d[25]),"+f"(d[26]),"+f"(d[27]),"+f"(d[28]),"+f"(d[29]),"+f"(d[30]),"+f"(d[31])
  : "l"(da), "l"(db), "n"(TA), "n"(TB));
}
template <int TA, int TB> __device__ __forceinline__ void wgmma_sz_n64(float (&d)[32], uint64_t da, uint64_t db) {
  asm volatile("wgmma.mma_async.sync.aligned.m64n64k16.f32.bf16.bf16 "
  "{%0,%1,%2,%3,%4,%5,%6,%7,%8,%9,%10,%11,%12,%13,%14,%15,%16,%17,%18,%19,%20,%21,%22,%23,%24,%25,%26,%27,%28,%29,%30,%31}, "
  "%32, %33, 0, 1, 1, %34, %35;"
  : "=f"(d[0]),"=f"(d[1]),"=f"(d[2]),"=f"(d[3]),"=f"(d[4]),"=f"(d[5]),"=f"(d[6]),"=f"(d[7]),"=f"(d[8]),"=f"(d[9]),"=f"(d[10]),"=f"(d[11]),"=f"(d[12]),"=f"(d[13]),"=f"(d[14]),"=f"(d[15]),"=f"(d[16]),"=f"(d[17]),"=f"(d[18]),"=f"(d[19]),"=f"(d[20]),"=f"(d[21]),"=f"(d[22]),"=f"(d[23]),"=f"(d[24]),"=f"(d[25]),"=f"(d[26]),"=f"(d[27]),"=f"(d[28]),"=f"(d[29]),"=f"(d[30]),"=f"(d[31])
  : "l"(da), "l"(db), "n"(TA), "n"(TB));
}
template <int TB> __device__ __forceinline__ void wgmma_rs_n72(float (&d)[36], uint32_t a0, uint32_t a1, uint32_t a2, uint32_t a3, uint64_t db) {
  asm volatile("wgmma.mma_async.sync.aligned.m64n72k16.f32.bf16.bf16 "
  "{%0,%1,%2,%3,%4,%5,%6,%7,%8,%9,%10,%11,%12,%13,%14,%15,%16,%17,%18,%19,%20,%21,%22,%23,%24,%25,%26,%27,%28,%29,%30,%31,%32,%33,%34,%35}, "
  "{%36,%37,%38,%39}, %40, 1, 1, 1, %41;"
  : "+f"(d[0]),"+f"(d[1]),"+f"(d[2]),"+f"(d[3]),"+f"(d[4]),"+f"(d[5]),"+f"(d[6]),"+f"(d[7]),"+f"(d[8]),"+f"(d[9]),"+f"(d[10]),"+f"(d[11]),"+f"(d[12]),"+f"(d[13]),"+f"(d[14]),"+f"(d[15]),"+f"(d[16]),"+f"(d[17]),"+f"(d[18]),"+f"(d[19]),"+f"(d[20]),"+f"(d[21]),"+f"(d[22]),"+f"(d[23]),"+f"(d[24]),"+f"(d[25]),"+f"(d[26]),"+f"(d[27]),"+f"(d[28]),"+f"(d[29]),"+f"(d[30]),"+f"(d[31]),"+f"(d[32]),"+f"(d[33]),"+f"(d[34]),"+f"(d[35])
  : "r"(a0), "r"(a1), "r"(a2), "r"(a3), "l"(db), "n"(TB));
}
template <int TB> __device__ __forceinline__ void wgmma_rz_n72(float (&d)[36], uint32_t a0, uint32_t a1, uint32_t a2, uint32_t a3, uint64_t db) {
  asm volatile("wgmma.mma_async.sync.aligned.m64n72k16.f32.bf16.bf16 "
  "{%0,%1,%2,%3,%4,%5,%6,%7,%8,%9,%10,%11,%12,%13,%14,%15,%16,%17,%18,%19,%20,%21,%22,%23,%24,%25,%26,%27,%28,%29,%30,%31,%32,%33,%34,%35}, "
  "{%36,%37,%38,%39}, %40, 0, 1, 1, %41;"
  : "=f"(d[0]),"=f"(d[1]),"=f"(d[2]),"=f"(d[3]),"=f"(d[4]),"=f"(d[5]),"=f"(d[6]),"=f"(d[7]),"=f"(d[8]),"=f"(d[9]),"=f"(d[10]),"=f"(d[11]),"=f"(d[12]),"=f"(d[13]),"=f"(d[14]),"=f"(d[15]),"=f"(d[16]),"=f"(d[17]),"=f"(d[18]),"=f"(d[19]),"=f"(d[20]),"=f"(d[21]),"=f"(d[22]),"=f"(d[23]),"=f"(d[24]),"=f"(d[25]),"=f"(d[26]),"=f"(d[27]),"=f"(d[28]),"=f"(d[29]),"=f"(d[30]),"=f"(d[31]),"=f"(d[32]),"=f"(d[33]),"=f"(d[34]),"=f"(d[35])
  : "r"(a0), "r"(a1), "r"(a2), "r"(a3), "l"(db), "n"(TB));
}
template <int TB> __device__ __forceinline__ void wgmma_rs_n40(float (&d)[20], uint32_t a0, uint32_t a1, uint32_t a2, uint32_t a3, uint64_t db) {
  asm volatile("wgmma.mma_async.sync.aligned.m64n40k16.f32.bf16.bf16 "
  "{%0,%1,%2,%3,%4,%5,%6,%7,%8,%9,%10,%11,%12,%13,%14,%15,%16,%17,%18,%19}, "
  "{%20,%21,%22,%23}, %24, 1, 1, 1, %25;"
  : "+f"(d[0]),"+f"(d[1]),"+f"(d[2]),"+f"(d[3]),"+f"(d[4]),"+f"(d[5]),"+f"(d[6]),"+f"(d[7]),"+f"(d[8]),"+f"(d[9]),"+f"(d[10]),"+f"(d[11]),"+f"(d[12]),"+f"(d[13]),"+f"(d[14]),"+f"(d[15]),"+f"(d[16]),"+f"(d[17]),"+f"(d[18]),"+f"(d[19])
  : "r"(a0), "r"(a1), "r"(a2), "r"(a3), "l"(db), "n"(TB));
}
template <int TB> __device__ __forceinline__ void wgmma_rz_n40(float (&d)[20], uint32_t a0, uint32_t a1, uint32_t a2, uint32_t a3, uint64_t db) {
  asm volatile("wgmma.mma_async.sync.aligned.m64n40k16.f32.bf16.bf16 "
  "{%0,%1,%2,%3,%4,%5,%6,%7,%8,%9,%10,%11,%12,%13,%14,%15,%16,%17,%18,%19}, "
  "{%20,%21,%22,%23}, %24, 0, 1, 1, %25;"
  : "=f"(d[0]),"=f"(d[1]),"=f"(d[2]),"=f"(d[3]),"=f"(d[4]),"=f"(d[5]),"=f"(d[6]),"=f"(d[7]),"=f"(d[8]),"=f"(d[9]),"=f"(d[10]),"=f"(d[11]),"=f"(d[12]),"=f"(d[13]),"=f"(d[14]),"=f"(d[15]),"=f"(d[16]),"=f"(d[17]),"=f"(d[18]),"=f"(d[19])
  : "r"(a0), "r"(a1), "r"(a2), "r"(a3), "l"(db), "n"(TB));
}
template <int TB> __device__ __forceinline__ void wgmma_rs_n128(float (&d)[64], uint32_t a0, uint32_t a1, uint32_t a2, uint32_t a3, uint64_t db) {
  asm volatile("wgmma.mma_async.sync.aligned.m64n128k16.f32.bf16.bf16 "
  "{%0,%1,%2,%3,%4,%5,%6,%7,%8,%9,%10,%11,%12,%13,%14,%15,%16,%17,%18,%19,%20,%21,%22,%23,%24,%25,%26,%27,%28,%29,%30,%31,%32,%33,%34,%35,%36,%37,%38,%39,%40,%41,%42,%43,%44,%45,%46,%47,%48,%49,%50,%51,%52,%53,%54,%55,%56,%57,%58,%59,%60,%61,%62,%63}, "
  "{%64,%65,%66,%67}, %68, 1, 1, 1, %69;"
  : "+f"(d[0]),"+f"(d[1]),"+f"(d[2]),"+f"(d[3]),"+f"(d[4]),"+f"(d[5]),"+f"(d[6]),"+f"(d[7]),"+f"(d[8]),"+f"(d[9]),"+f"(d[10]),"+f"(d[11]),"+f"(d[12]),"+f"(d[13]),"+f"(d[14]),"+f"(d[15]),"+f"(d[16]),"+f"(d[17]),"+f"(d[18]),"+f"(d[19]),"+f"(d[20]),"+f"(d[21]),"+f"(d[22]),"+f"(d[23]),"+f"(d[24]),"+f"(d[25]),"+f"(d[26]),"+f"(d[27]),"+f"(d[28]),"+f"(d[29]),"+f"(d[30]),"+f"(d[31]),"+f"(d[32]),"+f"(d[33]),"+f"(d[34]),"+f"(d[35]),"+f"(d[36]),"+f"(d[37]),"+f"(d[38]),"+f"(d[39]),"+f"(d[40]),"+f"(d[41]),"+f"(d[42]),"+f"(d[43]),"+f"(d[44]),"+f"(d[45]),"+f"(d[46]),"+f"(d[47]),"+f"(d[48]),"+f"(d[49]),"+f"(d[50]),"+f"(d[51]),"+f"(d[52]),"+f"(d[53]),"+f"(d[54]),"+f"(d[55]),"+f"(d[56]),"+f"(d[57]),"+f"(d[58]),"+f"(d[59]),"+f"(d[60]),"+f"(d[61]),"+f"(d[62]),"+f"(d[63])
  : "r"(a0), "r"(a1), "r"(a2), "r"(a3), "l"(db), "n"(TB));
}
template <int TA, int TB> __device__ __forceinline__ void wgmma_ss_n8(float (&d)[4], uint64_t da, uint64_t db) {
  asm volatile("wgmma.mma_async.sync.aligned.m64n8k16.f32.bf16.bf16 "
  "{%0,%1,%2,%3}, "
  "%4, %5, 1, 1, 1, %6, %7;"
  : "+f"(d[0]),"+f"(d[1]),"+f"(d[2]),"+f"(d[3])
  : "l"(da), "l"(db), "n"(TA), "n"(TB));
}
template <int TA, int TB> __device__ __forceinline__ void wgmma_ss_n16(float (&d)[8], uint64_t da, uint64_t db) {
  asm volatile("wgmma.mma_async.sync.aligned.m64n16k16.f32.bf16.bf16 "
  "{%0,%1,%2,%3,%4,%5,%6,%7}, "
  "%8, %9, 1, 1, 1, %10, %11;"
  : "+f"(d[0]),"+f"(d[1]),"+f"(d[2]),"+f"(d[3]),"+f"(d[4]),"+f"(d[5]),"+f"(d[6]),"+f"(d[7])
  : "l"(da), "l"(db), "n"(TA), "n"(TB));
}

constexpr int SEQ = 2048, DM = 1024, FF = 3584;
constexpr int NCTA = 128, NSVC = 4;
constexpr int NUNIT = 112;
constexpr uint32_t SLOT = 16384;
constexpr uint32_t MISC = 14 * SLOT;
constexpr uint32_t SMEM_BYTES = MISC + 3072;
constexpr uint32_t M_MOE = 0;
constexpr uint32_t M_BAR = 2048;
constexpr uint32_t M_DUM = 2048 + 1020;
constexpr uint32_t M_IDX = 2048 + 768;
constexpr uint32_t M_KEY = 2048 + 960;
#define R5 1
#define NQ (R5 ? 6 : 5)
constexpr int NF = 16 - NQ, NR = (NQ == 5 || R5) ? 4 : 3;
constexpr int B_FXQ = 0, B_FKV = 3, B_AST = 6, B_MOE = 7, B_MF = 8  , B_CQ = 12, B_XS = 13, B_DF = 14, B_ZOK = 15, B_FWO = 21  , B_FQ = B_FWO - NQ,
              B_UP = 37, B_FIN = 38, B_KVB = 39, B_ME = 40  , B_HF = 44, B_AF = 45  , B_AR = 50  , B_GO = 52,
              B_FAUX = 53, B_EAUX = 54, B_T0 = 55, B_DE = 56, B_EA = 57  , B_VAL = 62  ,
              B_E = 67  , B_STG = 70, B_EQ = 71  , B_EO = 76  , NBAR = 83, B_KV4 = 83, B_MS = 84,
              B_FV = 85  , B_EK = 88  , B_GQ = 91, B_GT = 92;
constexpr uint32_t MT = 9216, A_ONES = 12 * SLOT + 3 * MT, A_CS = A_ONES + 2048, A_ST = A_CS + 1536;
constexpr uint32_t A_TL = MISC + 2048 + 808;
constexpr int S_V0 = R5 ? 7 : 11, S_V1 = R5 ? 9 : 7;
constexpr uint32_t K_SLOTS = 0x8697A8u, V_SLOTS = 0x97A869u;
constexpr int C_B = 0, C_DONE = 32, NCNT = 2;
constexpr uint32_t QX_SLOTS = NQ == 5 ? 0x43102u : 0x354021u;
constexpr uint32_t QW_SLOTS = R5 ? 0xA9786Au : 0xB76A98u;
constexpr uint32_t qx(int k) { return (QX_SLOTS >> (4 * k)) & 15u; }
constexpr uint32_t qw(int k) { return (QW_SLOTS >> (4 * k)) & 15u; }
constexpr uint32_t S_KVB = R5 ? 1 : 8, S_D0 = R5 ? 11 : (NQ == 5 ? 5 : 1), S_D1 = R5 ? 2 : (NQ == 5 ? 11 : 2);
constexpr uint32_t S_M3 = R5 ? 11 : 5;
constexpr int WQ0 = NQ == 5 ? 1 : 3;
constexpr uint32_t wo_slot_c(int i) { return i >= 9 ? wo_slot_c(i - 9) : (i == 7 ? S_D0 : (i == 8 ? S_D1 : (((i & 1) || i + WQ0 == 1) ? qx((i + WQ0) >> 1) : qw((i + WQ0) >> 1)))); }
constexpr uint64_t wo_slots() { uint64_t t = 0; for (int i = 0; i < 16; i++) t |= (uint64_t)wo_slot_c(i) << (4 * i); return t; }
constexpr uint64_t WO_SLOTS = wo_slots();
constexpr uint32_t A_SLOTS = 0xDC000u | (S_KVB << 8) | (qw(NQ - 1) << 4) | qx(NQ - 1);
constexpr uint32_t SX14 = qx(NQ - 2), SX15 = qx(NQ - 1), SXQ0 = qx(0);
#define WOD 2
#define PLC 3
#define PFG1 10
#define PFNS1 150
#define PFG0 3
#define RS0 0
#define WPF 1
#define POLLNS 150
#define SVNS 100
#define MPROMO CU_TENSOR_MAP_L2_PROMOTION_L2_128B
#define MW0 0
#define PFILL 0
#define H2W (NQ - 3)
#define TOPW 1000
#define PFT 0
#define SV0 2
#define SV0A 14
#define SV0B 22
#define ASTE 2
#define PFS 1
#define PFTAB 0x0012222220000ull
#define HW 0
#define DPF 1
#define PROBE 0x8
#define OS1 0
#define YW 0
#define OS2 3
#define NOVAL 0
#define NDIR 1
#define I0 (2 + NDIR)
#define DW 0
#define OSP 1
#define NA 5
#define STAG 4
#define GOE 0
#define SVP 99
#define KEY1 0
#define HYB 0
#define DV 0
#define DVJ 4
#define DVK 10
#define FW 0
#define E1E 1
#define GATE 0
#define SVD 0
#define XPROMO CU_TENSOR_MAP_L2_PROMOTION_L2_128B
#define MC0 3
#define MX 0
#define OUTV 1
#define BW0 2
#define QL 1
#define NP 0
#define FINCP 0
#define DNS 0
#define WOK 99
#define WOD1 2
#define SVT 64
#define MRED 1
#define MRW -1
#define ST 0
#define RW 0
#define SL2 0
#define CQ4 0
#define VOL 0
#define FMC 0
#define KS 7
#define SQ 2
#define H2D 200
#define MRD 300
#define STP 0
#define TPNS 50
#define DLP 0
#define MFIN 0
#define MFD 300
#define SF 1
#define PH MFIN
#define RSL 0
#define PFW 3000
#define KVE 1
#define P2NS 0
#define OS3 4
#define PLP 2
#define FINJ 9
#define PFD 0
#define PFG 3
#define PFNS2 200
#define PFNS 250
#define MAP 2
#define RSNS 60
#define SVS 6
#define PRODLATE 0
#define MC 7
#define QE 0
#define TMP 1
#define TMPW 4
#define DS 15
#define RL 0
#define EV 0
#define LQ 0
#define SPL 0
#define HALFST 0
#define PHI2 1
#define E7 1
#define RF 1
#define RK 0
#define LE 1
#define SL7 0
#define XP 3
#define VR 4
#define KEEP 1
#define KP 4
#define KC 1
#define MS 0
constexpr int CON_REGS = 224, MOE_REGS = 40, PROD_REGS = 24;
constexpr uint32_t SPIN_MAX = 2000000;
constexpr uint32_t SENT = 0xFFFFFFFFu;

struct __align__(128) Scratch {
  uint4 o[NCTA * 2048];
  uint4 part[NCTA * 544];
  uint4 fin[8 * 640];
  float2 stats[SEQ];
  uint32_t key[SEQ];
  uint32_t cs[3 * DM];
  uint4 y[NCTA * 128];
  uint32_t h[56 * 256];
  uint32_t top[128];
  uint32_t cnt[NCNT * 32];
};
__device__ Scratch G;
#define TLS(th, i)
#define TLP_(i)
#define TLG(i)
#define TLDUMP()

__device__ __forceinline__ bool elect_one() {
  uint32_t p;
  asm volatile("{\n.reg .pred P;\nelect.sync _|P, 0xffffffff;\nselp.b32 %0, 1, 0, P;\n}" : "=r"(p));
  return p;
}
__device__ __forceinline__ void mbar_init(uint32_t b, uint32_t c) { asm volatile("mbarrier.init.shared::cta.b64 [%0], %1;" ::"r"(b), "r"(c) : "memory"); }
__device__ __forceinline__ void mbar_expect_tx(uint32_t b, uint32_t bytes) { asm volatile("mbarrier.arrive.expect_tx.shared::cta.b64 _, [%0], %1;" ::"r"(b), "r"(bytes) : "memory"); }
__device__ __forceinline__ void mbar_arrive(uint32_t b) { asm volatile("mbarrier.arrive.shared::cta.b64 _, [%0];" ::"r"(b) : "memory"); }
__device__ __forceinline__ void mbar_wait_b(uint32_t b, uint32_t parity) {
  asm volatile(
      "{\n.reg .pred p;\n.reg .u32 cnt;\nmov.u32 cnt, 0;\n"
      "LW:\nmbarrier.try_wait.parity.shared::cta.b64 p, [%0], %1;\n@p bra LD;\n"
      "add.u32 cnt, cnt, 1;\nsetp.lt.u32 p, cnt, 4000000;\n@p bra LW;\ntrap;\nLD:\n}" ::"r"(b), "r"(parity) : "memory");
}
__device__ __forceinline__ void mbar_wait(uint32_t b, uint32_t parity) {
  asm volatile("{\n.reg .pred p;\nLW:\nmbarrier.try_wait.parity.shared::cta.b64 p, [%0], %1;\n@!p bra LW;\n}" ::"r"(b), "r"(parity) : "memory");
}
__device__ __forceinline__ bool mbar_test(uint32_t b, uint32_t parity) {
  uint32_t r;
  asm volatile("{\n.reg .pred p;\nmbarrier.test_wait.parity.shared::cta.b64 p, [%1], %2;\nselp.b32 %0, 1, 0, p;\n}" : "=r"(r) : "r"(b), "r"(parity) : "memory");
  return r;
}
__device__ __forceinline__ uint32_t ev_arrive(uint32_t a) { uint32_t r; asm volatile("atom.shared.add.u32 %0, [%1], 1;" : "=r"(r) : "r"(a) : "memory"); return r; }
__device__ __forceinline__ void tma2d(uint32_t dst, const CUtensorMap* m, int c0, int c1, uint32_t bar) {
  asm volatile("cp.async.bulk.tensor.2d.shared::cluster.global.mbarrier::complete_tx::bytes [%0], [%1, {%3, %4}], [%2];" ::"r"(dst), "l"(m), "r"(bar), "r"(c0), "r"(c1) : "memory");
}
__device__ __forceinline__ void tma3d(uint32_t dst, const CUtensorMap* m, int c1, int c2, uint32_t bar) {
  asm volatile("cp.async.bulk.tensor.3d.shared::cluster.global.mbarrier::complete_tx::bytes [%0], [%1, {%3, %4, %5}], [%2];" ::"r"(dst), "l"(m), "r"(bar), "r"(0), "r"(c1), "r"(c2) : "memory");
}
__device__ __forceinline__ void tma3d_mc(uint32_t dst, const CUtensorMap* m, int c1, int c2, uint32_t bar) {
  asm volatile("cp.async.bulk.tensor.3d.shared::cluster.global.mbarrier::complete_tx::bytes.multicast::cluster [%0], [%1, {%3, %4, %5}], [%2], %6;" ::"r"(dst), "l"(m), "r"(bar), "r"(0), "r"(c1), "r"(c2), "h"((uint16_t)3) : "memory");
}
__device__ __forceinline__ void tma5d(uint32_t dst, const CUtensorMap* m, int c2, int c4, uint32_t bar, bool mc) {
  if (mc) asm volatile("cp.async.bulk.tensor.5d.shared::cluster.global.mbarrier::complete_tx::bytes.multicast::cluster [%0], [%1, {%3, %3, %4, %3, %5}], [%2], %6;" ::"r"(dst), "l"(m), "r"(bar), "r"(0), "r"(c2), "r"(c4), "h"((uint16_t)3) : "memory");
  else asm volatile("cp.async.bulk.tensor.5d.shared::cluster.global.mbarrier::complete_tx::bytes [%0], [%1, {%3, %3, %4, %3, %5}], [%2];" ::"r"(dst), "l"(m), "r"(bar), "r"(0), "r"(c2), "r"(c4) : "memory");
}
__device__ __forceinline__ void mbar_arrive_cta(uint32_t b, uint32_t cta) {
  asm volatile("{\n.reg .b32 ra;\nmapa.shared::cluster.u32 ra, %0, %1;\nmbarrier.arrive.shared::cluster.b64 _, [ra];\n}" ::"r"(b), "r"(cta) : "memory");
}
constexpr uint64_t POL_FIRST = 0x12F0000000000000ull;
__device__ __forceinline__ void tma2d_ef(uint32_t dst, const CUtensorMap* m, int c0, int c1, uint32_t bar) {
  asm volatile("cp.async.bulk.tensor.2d.shared::cluster.global.mbarrier::complete_tx::bytes.L2::cache_hint [%0], [%1, {%3, %4}], [%2], %5;" ::"r"(dst), "l"(m), "r"(bar), "r"(c0), "r"(c1), "l"(POL_FIRST) : "memory");
}
__device__ __forceinline__ void bulk_ld(uint32_t dst, const void* src, uint32_t bytes, uint32_t bar) {
  asm volatile("cp.async.bulk.shared::cluster.global.mbarrier::complete_tx::bytes [%0], [%1], %2, [%3];" ::"r"(dst), "l"(src), "r"(bytes), "r"(bar) : "memory");
}
__device__ __forceinline__ void bulk_ld_mc(uint32_t dst, const void* src, uint32_t bytes, uint32_t bar) {
  asm volatile("cp.async.bulk.shared::cluster.global.mbarrier::complete_tx::bytes.multicast::cluster [%0], [%1], %2, [%3], %4;" ::"r"(dst), "l"(src), "r"(bytes), "r"(bar), "h"((uint16_t)3) : "memory");
}
__device__ __forceinline__ void bulk_pf(const void* src, uint32_t bytes) { asm volatile("cp.async.bulk.prefetch.L2.global [%0], %1;" ::"l"(src), "r"(bytes) : "memory"); }
__device__ __forceinline__ void tma2d_pf(const CUtensorMap* m, int c0, int c1) {
  asm volatile("cp.async.bulk.prefetch.tensor.2d.L2.global [%0, {%1, %2}];" ::"l"(m), "r"(c0), "r"(c1) : "memory");
}
__device__ __forceinline__ void map_pf(const CUtensorMap* m) { asm volatile("prefetch.tensormap [%0];" ::"l"(m) : "memory"); }
__device__ __forceinline__ void line_pf(const void* p) { asm volatile("prefetch.global.L2 [%0];" ::"l"(p)); }
__device__ __forceinline__ void pf128(uint32_t dummy, const void* src) { asm volatile("cp.async.ca.shared.global.L2::128B [%0], [%1], 4;" ::"r"(dummy), "l"(src) : "memory"); }
__device__ __forceinline__ void pf256(uint32_t dummy, const void* src) { asm volatile("cp.async.ca.shared.global.L2::256B [%0], [%1], 4;" ::"r"(dummy), "l"(src) : "memory"); }
__device__ __forceinline__ void cp16x2(uint32_t dst, const void* src) {
  asm volatile("cp.async.cg.shared.global [%0], [%1], 16;\ncp.async.cg.shared.global [%0+4096], [%1+512], 16;" ::"r"(dst), "l"(src) : "memory");
}
constexpr uint32_t HI_SW128 = 0x40000000u | (1024 >> 4), HI_SW64 = 0x80000000u | (512 >> 4), HI_NOSW = 512 >> 4;
__device__ __forceinline__ uint64_t mkdesc(uint32_t lo, uint32_t hi) { uint64_t d; asm("mov.b64 %0, {%1, %2};" : "=l"(d) : "r"(lo), "r"(hi)); return d; }
__device__ __forceinline__ void wg_fence() { asm volatile("wgmma.fence.sync.aligned;" ::: "memory"); }
__device__ __forceinline__ void wg_commit() { asm volatile("wgmma.commit_group.sync.aligned;" ::: "memory"); }
template <int N> __device__ __forceinline__ void wg_wait() { asm volatile("wgmma.wait_group.sync.aligned %0;" ::"n"(N) : "memory"); }
template <int N> __device__ __forceinline__ void reg_fence(float (&a)[N]) {
#pragma unroll
  for (int i = 0; i < N; i++) asm volatile("" : "+f"(a[i])::"memory");
}
template <int ID, int N> __device__ __forceinline__ void bar_sync() { asm volatile("bar.sync %0, %1;" ::"n"(ID), "n"(N) : "memory"); }
__device__ __forceinline__ void fence_async_smem() { asm volatile("fence.proxy.async.shared::cta;" ::: "memory"); }
__device__ __forceinline__ void fence_async_gmem() { asm volatile("fence.proxy.async.global;" ::: "memory"); }
__device__ __forceinline__ uint32_t pack_bf16(float lo, float hi) { uint32_t r; asm("cvt.rn.bf16x2.f32 %0, %1, %2;" : "=r"(r) : "f"(hi), "f"(lo)); return r; }
__device__ __forceinline__ float bf_lo(uint32_t v) { return __uint_as_float(v << 16); }
__device__ __forceinline__ float bf_hi(uint32_t v) { return __uint_as_float(v & 0xFFFF0000u); }
__device__ __forceinline__ float bf_round(float v) { return bf_lo(pack_bf16(v, v)); }
__device__ __forceinline__ uint32_t bf_sub2(uint32_t a, uint32_t b) { uint32_t r; asm("sub.rn.bf16x2 %0, %1, %2;" : "=r"(r) : "r"(a), "r"(b)); return r; }
__device__ __forceinline__ float rcp(float v) { float r; asm("rcp.approx.ftz.f32 %0, %1;" : "=f"(r) : "f"(v)); return r; }
__device__ __forceinline__ float ex2(float v) { float r; asm("ex2.approx.ftz.f32 %0, %1;" : "=f"(r) : "f"(v)); return r; }
__device__ __forceinline__ float sigmoid(float v) { return rcp(1.f + ex2(v * -1.4426950408889634f)); }
__device__ __forceinline__ void stsm4(uint32_t a, uint32_t r0, uint32_t r1, uint32_t r2, uint32_t r3) {
  asm volatile("stmatrix.sync.aligned.m8n8.x4.shared.b16 [%0], {%1,%2,%3,%4};" ::"r"(a), "r"(r0), "r"(r1), "r"(r2), "r"(r3) : "memory");
}
__device__ __forceinline__ void stsm4t(uint32_t a, uint32_t r0, uint32_t r1, uint32_t r2, uint32_t r3) {
  asm volatile("stmatrix.sync.aligned.m8n8.x4.trans.shared.b16 [%0], {%1,%2,%3,%4};" ::"r"(a), "r"(r0), "r"(r1), "r"(r2), "r"(r3) : "memory");
}
__device__ __forceinline__ void ldsm4(uint32_t a, uint32_t& r0, uint32_t& r1, uint32_t& r2, uint32_t& r3) {
  asm volatile("ldmatrix.sync.aligned.m8n8.x4.shared.b16 {%0,%1,%2,%3}, [%4];" : "=r"(r0), "=r"(r1), "=r"(r2), "=r"(r3) : "r"(a) : "memory");
}
__device__ __forceinline__ uint32_t movmat(uint32_t a) { uint32_t d; asm volatile("movmatrix.sync.aligned.m8n8.trans.b16 %0, %1;" : "=r"(d) : "r"(a)); return d; }
__device__ __forceinline__ void sts_h(uint32_t a, float v) { asm volatile("st.shared.u16 [%0], %1;" ::"r"(a), "h"((uint16_t)pack_bf16(v, v)) : "memory"); }
__device__ __forceinline__ float2 lds_f2(uint32_t a) { float2 v; asm volatile("ld.shared.v2.f32 {%0,%1}, [%2];" : "=f"(v.x), "=f"(v.y) : "r"(a)); return v; }
__device__ __forceinline__ float lds_f(uint32_t a) { float v; asm volatile("ld.shared.f32 %0, [%1];" : "=f"(v) : "r"(a)); return v; }
__device__ __forceinline__ float4 lds_f4(uint32_t a) { float4 v; asm volatile("ld.shared.v4.f32 {%0,%1,%2,%3}, [%4];" : "=f"(v.x), "=f"(v.y), "=f"(v.z), "=f"(v.w) : "r"(a)); return v; }
__device__ __forceinline__ uint32_t lds_u(uint32_t a) { uint32_t v; asm volatile("ld.shared.u32 %0, [%1];" : "=r"(v) : "r"(a) : "memory"); return v; }
__device__ __forceinline__ uint4 lds_u4(uint32_t a) { uint4 v; asm volatile("ld.shared.v4.u32 {%0,%1,%2,%3}, [%4];" : "=r"(v.x), "=r"(v.y), "=r"(v.z), "=r"(v.w) : "r"(a) : "memory"); return v; }
__device__ __forceinline__ void sts_u(uint32_t a, uint32_t v) { asm volatile("st.shared.u32 [%0], %1;" ::"r"(a), "r"(v) : "memory"); }
__device__ __forceinline__ void sts_u4(uint32_t a, uint4 v) { asm volatile("st.shared.v4.u32 [%0], {%1,%2,%3,%4};" ::"r"(a), "r"(v.x), "r"(v.y), "r"(v.z), "r"(v.w) : "memory"); }
__device__ __forceinline__ uint4 ldx4(const void* p) { uint4 v; asm volatile("ld.relaxed.gpu.global.v4.u32 {%0,%1,%2,%3}, [%4];" : "=r"(v.x), "=r"(v.y), "=r"(v.z), "=r"(v.w) : "l"(p) : "memory"); return v; }
__device__ __forceinline__ uint2 ldx2(const void* p) { uint2 v; asm volatile("ld.relaxed.gpu.global.v2.u32 {%0,%1}, [%2];" : "=r"(v.x), "=r"(v.y) : "l"(p) : "memory"); return v; }
__device__ __forceinline__ uint32_t ldx1(const void* p) { uint32_t v; asm volatile("ld.relaxed.gpu.global.u32 %0, [%1];" : "=r"(v) : "l"(p) : "memory"); return v; }
__device__ __forceinline__ void stx4(void* p, uint32_t a, uint32_t b, uint32_t c, uint32_t d) { asm volatile("st.relaxed.gpu.global.v4.u32 [%0], {%1,%2,%3,%4};" ::"l"(p), "r"(a), "r"(b), "r"(c), "r"(d) : "memory"); }
__device__ __forceinline__ void stx2(void* p, uint32_t a, uint32_t b) { asm volatile("st.relaxed.gpu.global.v2.u32 [%0], {%1,%2};" ::"l"(p), "r"(a), "r"(b) : "memory"); }
__device__ __forceinline__ void stx1(void* p, uint32_t a) { asm volatile("st.relaxed.gpu.global.u32 [%0], %1;" ::"l"(p), "r"(a) : "memory"); }
__device__ __forceinline__ uint32_t umax4(uint4 v) { return max(max(v.x, v.y), max(v.z, v.w)); }
__device__ __forceinline__ uint32_t f2x(float f) { return min(__float_as_uint(f), 0xFFFFFFFEu); }
__device__ __forceinline__ void red4(float* p, float a, float b, float c, float d) { asm volatile("red.relaxed.gpu.global.add.v4.f32 [%0], {%1,%2,%3,%4};" ::"l"(p), "f"(a), "f"(b), "f"(c), "f"(d) : "memory"); }
__device__ __forceinline__ void cnt_arrive(int c) { asm volatile("red.release.gpu.global.add.u32 [%0], 1;" ::"l"(&G.cnt[c]) : "memory"); }
__device__ __forceinline__ void cnt_wait(int c, uint32_t target) {
#pragma unroll 1
  for (uint32_t it = 0; it < SPIN_MAX; it++) {
    uint32_t v;
    asm volatile("ld.acquire.gpu.global.u32 %0, [%1];" : "=r"(v) : "l"(&G.cnt[c]) : "memory");
    if (v >= target) break;
    __nanosleep(POLLNS);
  }
}
__device__ __forceinline__ void cnt_done() {
  uint32_t t;
  asm volatile("atom.acq_rel.gpu.global.add.u32 %0, [%1], 1;" : "=r"(t) : "l"(&G.cnt[C_DONE]) : "memory");
  if (t == NCTA + NSVC - 1) {
#pragma unroll 1
    for (int i = 0; i < NCNT; i++) G.cnt[i * 32] = 0;
  }
}
__device__ __forceinline__ float phi(float u, float rs, float rl) {
  float a = fmaf(u, rs, 1.000001f), e = ex2(u * rl), r;
  asm("add.sat.f32 %0, %1, 0f358637BD;" : "=f"(e) : "f"(e));
  asm("max.NaN.f32 %0, %1, %2;" : "=f"(r) : "f"(a), "f"(e));
  return r;
}

constexpr float LOG2E = 1.4426950408889634f, LN2 = 0.6931471805599453f;
__device__ __forceinline__ uint32_t phi2l(float u0, float rl0, float u1, float rl1) {
  const float l0 = u0 * rl0, l1 = u1 * rl1;
  float e0, e1;
  asm("{\n.reg .f32 t;\nabs.f32 t, %1;\nneg.f32 t, t;\nex2.approx.ftz.f32 %0, t;\n}" : "=f"(e0) : "f"(l0));
  asm("{\n.reg .f32 t;\nabs.f32 t, %1;\nneg.f32 t, t;\nex2.approx.ftz.f32 %0, t;\n}" : "=f"(e1) : "f"(l1));
  uint32_t e = pack_bf16(e0, e1), r;
  const uint32_t a = pack_bf16(fmaf(l0, LN2, 1.000001f), fmaf(l1, LN2, 1.000001f));
  asm("add.rn.bf16x2 %0, %0, %1;" : "+r"(e) : "r"(0x35863586u));
  asm("max.NaN.bf16x2 %0, %1, %2;" : "=r"(r) : "r"(a), "r"(e));
  return r;
}
template <bool V = false>
__device__ __forceinline__ uint32_t phi2(float u0, float rs0, float rl0, float u1, float rs1, float rl1) {
  float e0, e1;
  if (V) {
    asm volatile("{\n.reg .f32 t;\nabs.f32 t, %1;\nneg.f32 t, t;\nex2.approx.ftz.f32 %0, t;\n}" : "=f"(e0) : "f"(u0 * rl0));
    asm volatile("{\n.reg .f32 t;\nabs.f32 t, %1;\nneg.f32 t, t;\nex2.approx.ftz.f32 %0, t;\n}" : "=f"(e1) : "f"(u1 * rl1));
  } else {
    asm("{\n.reg .f32 t;\nabs.f32 t, %1;\nneg.f32 t, t;\nex2.approx.ftz.f32 %0, t;\n}" : "=f"(e0) : "f"(u0 * rl0));
    asm("{\n.reg .f32 t;\nabs.f32 t, %1;\nneg.f32 t, t;\nex2.approx.ftz.f32 %0, t;\n}" : "=f"(e1) : "f"(u1 * rl1));
  }
  uint32_t e = pack_bf16(e0, e1), r;
  const uint32_t a = pack_bf16(fmaf(u0, rs0, 1.000001f), fmaf(u1, rs1, 1.000001f));
  asm("add.rn.bf16x2 %0, %0, %1;" : "+r"(e) : "r"(0x35863586u));
  asm("max.NaN.bf16x2 %0, %1, %2;" : "=r"(r) : "r"(a), "r"(e));
  return r;
}

__device__ __forceinline__ int kstep1(int e, int hg) { return e < 14 ? (e < 2 * hg ? e : e + 2) : 2 * hg + e - 14; }
__device__ __forceinline__ int slab(int n, int hg) {
  return n + (((n + 7 - hg) * 37) >> 8);
}
__host__ __device__ constexpr uint32_t d_off(int i) { return i < 3 ? 12 * SLOT + (NR == 4 ? i : (i == 2 ? 0 : i + 1)) * MT : (i < 5 ? S_D0 * SLOT + (i - 3) * 8192 : S_D1 * SLOT + (i - 5) * 8192); }
__host__ __device__ constexpr uint32_t h_off(int i) { return i < 3 ? 12 * SLOT + i * MT + 8192 : (i < 5 ? A_ONES + (i - 3) * 1024 : MISC + M_MOE + (i - 5) * 1024); }
__device__ __forceinline__ uint32_t m_off(int r) { return r < 3 ? 12 * SLOT + r * MT : S_M3 * SLOT; }
__device__ __forceinline__ int x_slot(int e, int s) { return NQ == 5 ? (e < 14 ? s : e - 11) : (e < 13 ? s : 3 + s); }
__device__ __forceinline__ uint32_t wo_slot(int i) { return (uint32_t)(WO_SLOTS >> (4 * i)) & 15u; }

__global__ void __launch_bounds__(512, 1)
fused_kernel(const __nv_bfloat16* __restrict__ x, const __nv_bfloat16* __restrict__ wqkv, const __nv_bfloat16* __restrict__ wo,
             const __nv_bfloat16* __restrict__ wr, const __nv_bfloat16* __restrict__ wd, __nv_bfloat16* __restrict__ outp, const int by_sm,
             const __grid_constant__ CUtensorMap tmX, const __grid_constant__ CUtensorMap tmW,
             const __grid_constant__ CUtensorMap tmWo, const __grid_constant__ CUtensorMap tmOut,
             const __grid_constant__ CUtensorMap tmG, const __grid_constant__ CUtensorMap tmU,
             const __grid_constant__ CUtensorMap tmD, const __grid_constant__ CUtensorMap tmR,
             const __grid_constant__ CUtensorMap tmWp) {
  if (TMP && threadIdx.x == 32 * TMPW) { map_pf(&tmX); map_pf(&tmW); }
  extern __shared__ __align__(1024) uint8_t smem_raw[];
  const uint32_t sb = (uint32_t)__cvta_generic_to_shared(smem_raw);
  const uint32_t bars = sb + MISC + M_BAR;
  uint32_t smid;
  asm("mov.u32 %0, %%smid;" : "=r"(smid));
  const int tpc = smid >> 1;
  int cl = tpc + max(((tpc - 25) * 37) >> 8, 0);
  cl = tpc < 60 ? cl : cl - 1;
  cl = tpc < 62 ? cl : (tpc - 58) * 8;
  const int u = by_sm ? 2 * cl + (blockIdx.x & 1) : blockIdx.x;
  const int hg = (u >> 4) & 7, tb = u & 15;
  const int b = tb * 8 + hg;
  const int lane = threadIdx.x & 31;
  const int warp = __shfl_sync(~0u, threadIdx.x >> 5, 0);
  const int ltid = threadIdx.x;
  const int g = lane >> 2, t = lane & 3;
  const uint32_t d0 = (sb & 0x3FFFF) >> 4;
#define BAR(i) (bars + 8 * (i))
  TLS(0, 0);

  const int rank = u & 1;
  auto load_entry = [&](int e, int s) {
    const int k0 = kstep1(e, hg) * 64;
    mbar_expect_tx(BAR(B_FXQ + s), e < NF ? 2 * SLOT : SLOT);
    mbar_expect_tx(BAR(B_FKV + s), R5 ? SLOT : 2 * SLOT);
    if (R5 && e < 11) mbar_expect_tx(BAR(B_FV + s), SLOT);
    const uint32_t vb = R5 ? BAR(B_FV + s) : BAR(B_FKV + s);
    tma2d(sb + x_slot(e, s) * SLOT, &tmX, k0, tb * 128, BAR(B_FXQ + s));
    if (e < MC0 || !(MC & 1)) {
      if (e < NF) tma3d(sb + (3 + s) * SLOT, &tmW, k0, 2 * hg, BAR(B_FXQ + s));
      tma3d(sb + (6 + 2 * s) * SLOT, &tmW, k0, 16 + 2 * hg, BAR(B_FKV + s));
      tma3d(sb + (7 + 2 * s) * SLOT, &tmW, k0, 32 + 2 * hg, vb);
    } else {
      if (e < NF && (e & 1) == rank) tma3d_mc(sb + (3 + s) * SLOT, &tmW, k0, 2 * hg, BAR(B_FXQ + s));
      if (R5 && e >= 11) { if (rank == 0) tma3d_mc(sb + ((K_SLOTS >> (4 * (e - 10))) & 15u) * SLOT, &tmW, k0, 16 + 2 * hg, BAR(B_FKV + s)); }
      else tma3d_mc(sb + (6 + 2 * s + rank) * SLOT, &tmW, k0, 16 + 16 * rank + 2 * hg, rank ? vb : BAR(B_FKV + s));
    }
  };
  if (warp == FW && u < NCTA) {
    if (elect_one()) {
      mbar_init(BAR(B_FXQ), 1); mbar_init(BAR(B_FKV), 1);
      if (R5) mbar_init(BAR(B_FV), 1);
      load_entry(0, 0);
      asm volatile("fence.mbarrier_init.release.cluster;" ::: "memory");
      TLS(FW * 32, 61);
    }
    __syncwarp();
  }
  if (u >= NCTA) {
    const int j = u - NCTA;
    if (warp == 8 && elect_one()) {
#pragma unroll
      for (int i = 0; i < 13; i++) mbar_init(BAR(i), 1);
    }
    if (ltid < 64) sts_u4(sb + MISC + ltid * 16, make_uint4(0x3F803F80u, 0x3F803F80u, 0x3F803F80u, 0x3F803F80u));
    fence_async_smem();
    __syncthreads();
    if (warp < 4) {
      int s = 0, p = 0;
#pragma unroll 1
      for (int pass = 0; pass < 3; pass++) {
        float acc[4][4];
#pragma unroll
        for (int c = 0; c < 4; c++) acc[c][0] = acc[c][1] = acc[c][2] = acc[c][3] = 0.f;
#pragma unroll 1
        for (int k = 0; k < 16; k++) {
          mbar_wait(BAR(s), p);
          wg_fence();
#pragma unroll
          for (int c = 0; c < 4; c++)
#pragma unroll
            for (int kk = 0; kk < 4; kk++)
              wgmma_ss_n8<1, 0>(acc[c], mkdesc((d0 + s * 2048 + c * 512 + kk * 128) | (512u << 16), HI_SW128), mkdesc((d0 + (MISC >> 4)) | (1u << 16), HI_SW128));
          wg_commit();
          wg_wait<0>();
          if (ltid == 0) mbar_arrive(BAR(6 + s));
          if (++s == SVS) { s = 0; p ^= 1; }
        }
        uint32_t* pc = G.cs + (pass < 2 ? DM + pass * DM : 0) + j * 256 + warp * 16 + g;
#pragma unroll
        for (int c = 0; c < 4; c++) {
          reg_fence(acc[c]);
          const uint32_t v = __float_as_uint((t & 1) ? acc[c][2] : acc[c][0]);
          if (t < 2) stx1(pc + c * 64 + t * 8, v ? v : 0x80000000u);
        }
        TLS(0, 1 + pass);
      }
    } else if (warp >= 8 && j == 0) {
      const int wq = warp - 8;
      const uint32_t top = sb + MISC + 1024;
#pragma unroll 1
      for (uint32_t it = 0; it < SPIN_MAX; it++) {
        const uint4 v0 = ldx4(G.key + wq * 256 + lane * 4), v1 = ldx4(G.key + wq * 256 + 128 + lane * 4);
        uint32_t ok;
        asm volatile("{\n.reg .pred p, q;\nsetp.ne.u32 p, %1, 0;\nbar.red.and.pred q, 2, 256, p;\nselp.b32 %0, 1, 0, q;\n}" : "=r"(ok) : "r"((v0.x & v0.y & v0.z & v0.w & v1.x & v1.y & v1.z & v1.w) >> 27) : "memory");
        ok = __any_sync(~0u, ok);
        if (!ok && it) continue;
        TLS(256, 4);
        uint32_t np = 0u - (1u << 28), mine = 0;
#pragma unroll 1
        for (int r = 0; r < 8; r++) {
          const uint32_t m0 = __viaddmax_u32(v0.x, np, v0.y + np), m1 = __viaddmax_u32(v0.z, np, v0.w + np), m2 = __viaddmax_u32(v1.x, np, v1.y + np), m3 = __viaddmax_u32(v1.z, np, v1.w + np);
          np -= __reduce_max_sync(~0u, max(max(m0, m1), max(m2, m3)));
          if (g == r) mine = 0u - np;
        }
        if (t == 0) sts_u(top + (wq * 8 + g) * 4, mine);
        bar_sync<2, 256>();
        TLS(256, 5);
        int rk = 0;
#pragma unroll
        for (int i = 0; i < 4; i++) {
          const uint4 o = lds_u4(top + t * 64 + i * 16);
          rk += (o.x > mine) + (o.y > mine) + (o.z > mine) + (o.w > mine);
        }
        rk += __shfl_xor_sync(~0u, rk, 1);
        rk += __shfl_xor_sync(~0u, rk, 2);
        if (ok) { if (rk < 8) stx1(G.top + t * 32 + rk, mine); break; }
        __nanosleep(2500);
      }
      TLS(256, 7);
    } else if (warp == 4) {
      int s = 0, p = 1;
      if (SVD) __nanosleep(SVD);
#pragma unroll 1
      for (int i = 0; i < 48; i++) {
        mbar_wait(BAR(6 + s), p);
        if (j == 0 && i >= SV0A && i < SV0B) mbar_wait(BAR(s >= SV0 ? s - SV0 : s - SV0 + SVS), s >= SV0 ? p ^ 1 : p);
        if (elect_one()) {
          mbar_expect_tx(BAR(s), 2 * SLOT);
          const int ch = (i < 32 ? 16 + (i & 16) : 0) + j * 4, k0 = (i & 15) * 64;
          tma3d(sb + s * 2 * SLOT, &tmW, k0, ch, BAR(s));
          tma3d(sb + s * 2 * SLOT + SLOT, &tmW, k0, ch + 2, BAR(s));
        }
        if (++s == SVS) { s = 0; p ^= 1; }
      }
    }
    if (ltid == 0) cnt_wait(C_DONE, NCTA);
    __syncthreads();
    const uint4 zero = make_uint4(0, 0, 0, 0);
    if (ltid < 128) reinterpret_cast<uint4*>(G.key)[j * 128 + ltid] = zero;
    else if (ltid < 320) reinterpret_cast<uint4*>(G.cs)[j * 192 + ltid - 128] = zero;
    else if (ltid < 322) reinterpret_cast<uint4*>(G.top)[j * 8 + ltid - 320] = zero;
    if (ltid == 0) { cnt_done(); TLDUMP(); }
    return;
  }

  if (warp == 12) {
    if (elect_one()) {
#pragma unroll
      for (int i = 1; i < 7; i++) if (i != B_FKV) mbar_init(BAR(i), 1);
      if (R5) { mbar_init(BAR(B_FV + 1), 1); mbar_init(BAR(B_FV + 2), 1); }
      if (E1E) load_entry(1, 1);
      asm volatile("fence.mbarrier_init.release.cluster;" ::: "memory");
    }
  } else if (warp >= 13) {
    if (elect_one()) {
      if (warp == 15) {
#pragma unroll
        for (int i = B_FAUX; i < NBAR; i++) mbar_init(BAR(i), i < B_E || !MC ? 2 : 4);
        mbar_init(BAR(B_KV4), 4); mbar_init(BAR(B_MS), 2); mbar_init(BAR(B_GQ), 1); mbar_init(BAR(B_GT), 1);
        if (R5) { mbar_init(BAR(B_EK), 4); mbar_init(BAR(B_EK + 1), 4); mbar_init(BAR(B_EK + 2), 4); }
      } else {
#pragma unroll
        for (int i = 0; i < 23; i++) mbar_init(BAR((warp == 13 ? 7 : 30) + i), 1);
      }
      asm volatile("fence.mbarrier_init.release.cluster;" ::: "memory");
    }
  }
  __syncthreads();
  if (MC) asm volatile("barrier.cluster.arrive.relaxed.aligned;" ::: "memory");

  const bool unit = u < NUNIT;
  const int dcol = (u & 15) * 64, drow = (u >> 4) * 448;
  if (warp >= 12) {
    asm volatile("setmaxnreg.dec.sync.aligned.u32 %0;" ::"n"(PROD_REGS));
    if (MC && warp != 12) asm volatile("barrier.cluster.wait.aligned;" ::: "memory");
    if (warp == 12) {
      int s = 1 + E1E, p = 1, pn = 3;
#pragma unroll 1
      for (int e = 1 + E1E; e < 16; e++) {
        if (MC && e == MC0) asm volatile("barrier.cluster.wait.aligned;" ::: "memory");
        if (e == GATE) mbar_wait(BAR(B_FXQ), 0);
        mbar_wait(BAR(B_E + s), p);
        if (elect_one()) {
          load_entry(e, s);
          if (NR == 4 && e == 11) mbar_arrive(BAR(B_ME + 3));
          if (e == ASTE) {
            mbar_expect_tx(BAR(B_AST), 2 * SLOT + 2048);
            bulk_ld(sb + 12 * SLOT, x + (size_t)b * 16 * DM, 2 * SLOT, BAR(B_AST));
            bulk_ld(sb + MISC + M_MOE, wr, 2048, BAR(B_AST));
          } else if (e >= 3) {
            if (e < 6) bulk_pf(wqkv + (size_t)((e - 2) * 256 + 2 * b) * 3 * DM, 2 * 3 * DM * 2);
            if (e < 7) bulk_pf(wo + (size_t)((e - 3) * 256 + 2 * b) * DM, 2 * DM * 2);
            if (NUNIT) {
#pragma unroll 1
              for (int i = (PFTAB >> (4 * (e - 3))) & 15; i > 0; i--, pn++) {
                if (pn >= 16) { if (!(MX & 8)) tma2d_pf(&tmD, dcol, drow + (pn - 16) * 64); }
                else if (unit && !(MX & 2)) tma2d_pf(rank ? &tmU : &tmG, (u >> 1) * 64, pn * 64);
              }
            }
          }
        }
        if (R5 && e >= 11) {
          mbar_wait(BAR(B_EK + (s == 2 ? 0 : s + 1)), e >= 14);
          if (elect_one()) {
            mbar_expect_tx(BAR(B_FV + s), SLOT);
            if (rank) tma3d_mc(sb + ((V_SLOTS >> (4 * (e - 10))) & 15u) * SLOT, &tmW, kstep1(e, hg) * 64, 32 + 2 * hg, BAR(B_FV + s));
          }
        }
        if (++s == 3) { s = 0; p ^= 1; }
      }
#pragma unroll 1
      for (int k = 0; k < NQ; k++) {
        if (k == 0) mbar_wait(BAR(B_E + 1), 0);
        if (k == 1) mbar_wait(BAR(B_EK + 2), 1);
        if (k == 2) mbar_wait(BAR(B_EK + 0), 0);
        if (k == 3) mbar_wait(BAR(B_STG), 0);
        if (k == 5) mbar_wait(BAR(B_EQ), 0);
        if (elect_one()) {
          const int k0 = kstep1(NF + k, hg) * 64;
          mbar_expect_tx(BAR(B_FQ + k), SLOT);
          if (!(MC & 2)) tma3d(sb + ((QW_SLOTS >> (4 * k)) & 15u) * SLOT, &tmW, k0, 2 * hg, BAR(B_FQ + k));
          else if ((k & 1) == rank) tma3d_mc(sb + ((QW_SLOTS >> (4 * k)) & 15u) * SLOT, &tmW, k0, 2 * hg, BAR(B_FQ + k));
        }
      }
#pragma unroll 1
      for (int i = 0; i < 16; i++) {
        mbar_wait(i < 7 ? BAR(B_EQ + ((i + WQ0) >> 1)) : (i < 9 ? BAR(B_DE) : BAR(B_EO + i - 9)), 0);
        if (i == WOK) mbar_wait(BAR(B_KVB), 0);
        mbar_wait(BAR(B_FWO + i - (i < WOK ? WOD1 : WOD)), 0);
        if (elect_one()) {
          mbar_expect_tx(BAR(B_FWO + i), SLOT);
#pragma unroll
          for (int hf = 0; hf < ((MC & 4) ? 1 : 2); hf++) {
            const int n = 2 * i + ((MC & 4) ? rank : hf), m = slab(n - 4, hg), hd = n < 4 ? 4 * hg + n : 4 * (m & 7) + (m >> 3);
            if (i < 2 + NDIR) tma5d(sb + wo_slot(i) * SLOT + (n & 1) * 8192, &tmWp, hd * 4, 2 * hg, BAR(B_FWO + i), MC & 4);
            else if (MC & 4) tma3d_mc(sb + wo_slot(i) * SLOT + rank * 8192, &tmWo, hd * 32, 2 * hg, BAR(B_FWO + i));
            else tma3d(sb + wo_slot(i) * SLOT + hf * 8192, &tmWo, hd * 32, 2 * hg, BAR(B_FWO + i));
          }
        }
      }
    } else if (warp == 13) {
      if (elect_one()) {
        map_pf(rank ? &tmU : &tmG); map_pf(&tmR); map_pf(&tmD); map_pf(&tmWo); map_pf(&tmWp); map_pf(&tmOut);
      }
      bar_sync<6, 64>();
      if (elect_one()) {
        cnt_wait(C_B, NCTA);
        fence_async_gmem();
        mbar_expect_tx(BAR(B_FAUX), 1024);
        bulk_ld(sb + A_ST, G.stats + tb * 128, 1024, BAR(B_FAUX));
      }
      __syncwarp();
      TLS(416, 68);
#pragma unroll 1
      for (int m = 1; m < 4; m++) {
        const int part = m == 3 ? 0 : m;
        uint4 c;
#pragma unroll 1
        for (uint32_t it = 0; it < SPIN_MAX; it++) {
          c = ldx4(G.cs + part * DM + hg * 128 + lane * 4);
          if (__all_sync(~0u, min(min(c.x, c.y), min(c.z, c.w)))) break;
          __nanosleep(POLLNS);
        }
        if (CQ4 && part == 0) {
          const uint32_t o = sb + A_CS + (lane >> 2) * 64 + (lane & 1) * 32 + ((lane >> 1) & 1) * 8;
          asm volatile("st.shared.v2.u32 [%0], {%1,%2};\nst.shared.v2.u32 [%0+16], {%3,%4};" ::"r"(o), "r"(c.x), "r"(c.y), "r"(c.z), "r"(c.w) : "memory");
        } else sts_u4(sb + A_CS + part * 512 + lane * 16, c);
        __syncwarp();
        if (m > 1 && lane == 0) mbar_arrive(BAR(m == 2 ? B_FAUX : B_CQ));
        TLS(416, 71 + m);
      }
      mbar_wait(BAR(B_XS), 1);
      if (elect_one()) asm volatile("red.relaxed.gpu.global.add.u32 [%0], 1;" ::"l"(&G.cnt[C_DONE]) : "memory");
    } else if (warp == 14) {
      const uint4 sent = make_uint4(SENT, SENT, SENT, SENT);
      uint4* ro = G.o + (tb * 32 + hg) * 512 + lane;
      uint4* rp = G.part + b * 544 + lane;
      if (RSL) bar_sync<5, 160>(); else mbar_wait(BAR(B_AST), 0);
#pragma unroll 1
      for (int i = RS0; i < 40; i++) {
        uint4* q = i < 32 ? ro + (i >> 3) * 4096 + (i & 7) * 64 : rp + (i - 32) * 64;
        q[0] = sent; q[32] = sent;
        __nanosleep(RSNS);
      }
      rp[512] = sent;
#pragma unroll
      for (int i = 0; i < 4; i++) G.y[u * 128 + i * 32 + lane] = sent;
      if (unit) reinterpret_cast<uint4*>(G.h)[u * 32 + lane] = sent;
      G.fin[hg * 640 + tb * 40 + lane] = sent;
      if (lane < 8) G.fin[hg * 640 + tb * 40 + 32 + lane] = sent;
      if (!RSL) bar_sync<5, 160>();
      __syncwarp();
      TLS(448, 67);
      if (lane == 0) cnt_arrive(C_B);
      __syncwarp();
      TLS(448, 32);
      asm volatile("bar.arrive 6, 64;" ::: "memory");
    } else {
      const uint32_t stg = sb + 12 * SLOT;
      auto load_a = [&](int n, int r) {
        mbar_expect_tx(BAR(B_MF + r), (MX & 2) ? 1024 : MT);
        if (!(MX & 2)) tma2d_ef(sb + m_off(r), rank ? &tmU : &tmG, (u >> 1) * 64, n * 64, BAR(B_MF + r));
      };
      mbar_wait(BAR(B_XS), 0);
      if (unit) {
#pragma unroll 1
        for (int i = 0; i < 3; i++) {
          if (elect_one()) load_a(i, i);
          __nanosleep(PFILL);
        }
      }
      uint32_t key;
#pragma unroll 1
      for (uint32_t it = 0; it < SPIN_MAX; it++) {
        key = ldx1(G.top + ((u >> 1) & 3) * 32 + (lane & 7));
        if (__all_sync(~0u, key)) break;
        __nanosleep(TPNS);
      }
      TLS(480, 66);
      if (lane < 8) sts_u(sb + MISC + M_IDX + lane * 4, key);
      __syncwarp();
      if (lane == 0) mbar_arrive(BAR(B_XS));
      if (unit) {
        int tok[8];
#pragma unroll
        for (int i = 0; i < 8; i++) tok[i] = ~__shfl_sync(~0u, key, i) & 2047;
        int r = 0, p = 0;
#pragma unroll 1
        for (int n = 0; n < 16; n++) {
          if (n >= 3) mbar_wait(BAR(B_ME + r), r == 3 ? p : p ^ 1);
          if (elect_one()) {
            if (n >= 3) load_a(n, r);
#pragma unroll
            for (int i = 0; i < 8; i++) tma2d(sb + m_off(r) + 8192 + i * 128, &tmR, n * 64, tok[i], BAR(B_MF + r));
          }
          if (++r == NR) { r = 0; p ^= 1; }
        }
      }
      if (NUNIT) {
        if (lane == 0) mbar_expect_tx(BAR(B_DF), (MX & 8) ? 0 : 7 * 8192);
#pragma unroll 1
        for (int i = 0; i < 7; i++) {
          if (NR == 4) {
            if (i >= 3) mbar_wait(i < 5 ? BAR(B_ME + 3) : (R5 ? BAR(B_EQ + 1) : BAR(B_STG)), 0);
            else if (unit) mbar_wait(BAR(B_ME + i), 1);
          } else {
            if (i >= 3) mbar_wait(BAR(B_EQ + ((i - 3) >> 1)), 0);
            else if (unit) mbar_wait(BAR(B_ME + (i == 2 ? 0 : i + 1)), i == 2);
          }
          if (!(MX & 8) && elect_one()) tma2d_ef(sb + d_off(i), &tmD, dcol, drow + i * 64, BAR(B_DF));
          if (DNS) __nanosleep(DNS);
        }
      }
    }
    if (warp == 14) {
      if (DPF && NUNIT && !(MX & 8)) {
        mbar_wait(DS ? BAR(B_MS) : (DPF == 1 ? BAR(B_FQ) : BAR(B_T0)), 0);
#pragma unroll 1
        for (int pf = 0; pf < 7; pf++) { pf256(sb + MISC + M_DUM, wd + (size_t)(drow + pf * 64 + rank * 32 + lane) * DM + (dcol & ~127)); __nanosleep(PFNS2); }
      }
      const uint32_t* src = reinterpret_cast<const uint32_t*>(G.part + ((lane >> 3) * 32 + hg) * 544 + 512) + tb * 8 + (lane & 7);
      mbar_wait(BAR(B_EQ + MRW), 0);
      if (MRD) __nanosleep(MRD);
      uint32_t z0, z1, z2, z3;
#pragma unroll 1
      for (uint32_t it = 0; it < SPIN_MAX; it++) {
        z0 = ldx1(src); z1 = ldx1(src + 8 * 2176); z2 = ldx1(src + 16 * 2176); z3 = ldx1(src + 24 * 2176);
        if (!__any_sync(~0u, max(max(z0, z1), max(z2, z3)) == SENT)) break;
      }
      if (MRED == 2 && elect_one()) mbar_arrive(BAR(B_ZOK));
      float zz = (__uint_as_float(z0) + __uint_as_float(z1)) + (__uint_as_float(z2) + __uint_as_float(z3));
      zz += __shfl_xor_sync(~0u, zz, 8);
      zz += __shfl_xor_sync(~0u, zz, 16);
      stx1(reinterpret_cast<uint32_t*>(G.fin + hg * 640) + (tb >> 2) * 640 + 512 + ((tb >> 1) & 1) * 64 + (lane & 1) * 32 + (tb & 1) * 16 + ((lane & 7) >> 1) * 4 + (lane >> 3),
           pack_bf16(zz, zz));
      TLS(448, 12);
    }
    if (!MFIN && (warp == 13 || warp == 14)) {
      mbar_wait(BAR(B_EQ + H2W), 0);
      if (H2D) __nanosleep(H2D);
#pragma unroll 1
      for (uint32_t it = 0; it < SPIN_MAX; it++) {
        if (warp == 14 && elect_one()) {
          mbar_expect_tx(BAR(B_FIN), 10240);
          if (FMC && MC && it == 0) bulk_ld_mc(sb + S_KVB * SLOT + rank * 5120, G.fin + hg * 640 + rank * 320, 5120, BAR(B_FIN));
          else bulk_ld(sb + S_KVB * SLOT, G.fin + hg * 640, 10240, BAR(B_FIN));
        }
        mbar_wait(BAR(B_FIN), it & 1);
        uint32_t m = 0;
#pragma unroll
        for (int i = 0; i < 10; i++) m = max(m, lds_u(sb + S_KVB * SLOT + (i * 64 + ltid - 416) * 16 + (g >> 1) * 4));
        uint32_t bad;
        asm volatile("{\n.reg .pred p, q;\nsetp.eq.u32 p, %1, 0xFFFFFFFF;\nbar.red.or.pred q, 7, 64, p;\nselp.b32 %0, 1, 0, q;\n}" : "=r"(bad) : "r"(m) : "memory");
        if (!__any_sync(~0u, bad)) break;
      }
      if (warp == 14 && elect_one()) mbar_arrive(BAR(B_KVB));
      TLS(448, 14);
    }
    if (PH && (warp == 13 || warp == 14)) {
      bar_sync<3, 192>();
      mbar_wait(BAR(B_STG), 0);
#pragma unroll 1
      for (uint32_t it = 0; NUNIT && it < SPIN_MAX; it++) {
        if (elect_one()) {
          const uint32_t* ph = G.h + (u >> 4) * 7 * 256;
          if (warp == 13) { mbar_expect_tx(BAR(B_HF), 7168); bulk_ld(sb + h_off(3), ph + 768, 2048, BAR(B_HF)); bulk_ld(sb + h_off(5), ph + 1280, 2048, BAR(B_HF)); }
          else { bulk_ld(sb + h_off(0), ph, 1024, BAR(B_HF)); bulk_ld(sb + h_off(1), ph + 256, 1024, BAR(B_HF)); bulk_ld(sb + h_off(2), ph + 512, 1024, BAR(B_HF)); }
        }
        mbar_wait(BAR(B_HF), it & 1);
        uint32_t m = 0;
#pragma unroll
        for (int i = 0; i < 7; i++) m = max(m, lds_u(sb + h_off(i) + (ltid - 416) * 16 + (g >> 1) * 4));
        uint32_t bad;
        asm volatile("{\n.reg .pred p, q;\nsetp.eq.u32 p, %1, 0xFFFFFFFF;\nbar.red.or.pred q, 7, 64, p;\nselp.b32 %0, 1, 0, q;\n}" : "=r"(bad) : "r"(m) : "memory");
        if (!__any_sync(~0u, bad)) break;
        __nanosleep(POLLNS);
      }
      if (warp == 14 && elect_one()) mbar_arrive(BAR(B_KVB));
    }
    __syncwarp();
    if (warp >= 13) {
      const char* og = reinterpret_cast<const char*>(G.o + tb * 16384);
      auto probe = [&](uint32_t m) {
        const char* p = og + m * 8192u + (lane & 15) * 512 + 496;
#pragma unroll 1
        for (uint32_t it = 0; it < SPIN_MAX; it++)
          if (!__any_sync(~0u, ldx1(p) == SENT)) break;
      };
      if (warp == 15) {
        int r = 0, p = 1;
        mbar_wait(BAR(B_EAUX), 0);
#pragma unroll 1
        for (int i = I0; i < 16; i++) {
          const uint32_t dst = sb + ((A_SLOTS >> (4 * r)) & 15u) * SLOT, m0 = slab(2 * i - 4, hg), m1 = slab(2 * i - 3, hg);
          if (i == I0 + 3) mbar_wait(BAR(B_DE), 0);
          mbar_wait(BAR(B_EA + r), p);
          if ((PROBE >> i) & 1) probe(lane < 16 ? m0 : m1);
          if (elect_one()) {
            mbar_expect_tx(BAR(B_AF + r), SLOT);
            bulk_ld(dst, og + m0 * 8192u, 8192, BAR(B_AF + r)); bulk_ld(dst + 8192, og + m1 * 8192u, 8192, BAR(B_AF + r));
          }
          if (++r == NA) { r = 0; p ^= 1; }
        }
      } else {
        const uint32_t lo = lane * 32 + g * 4, hb = sb + (warp - 13) * 8192;
        uint32_t ph = 0;
        int r = 0, p = 0;
#pragma unroll 1
        for (int i = I0; i < 16; i++) {
          const uint32_t mine = hb + ((A_SLOTS >> (4 * r)) & 15u) * SLOT;
          auto bad = [&]() {
            uint32_t v[8];
#pragma unroll
            for (int j = 0; j < 8; j++) v[j] = lds_u(mine + lo + j * 1024);
            return __any_sync(~0u, max(max(max(v[0], v[1]), max(v[2], v[3])), max(max(v[4], v[5]), max(v[6], v[7]))) == SENT);
          };
          mbar_wait(BAR(B_AF + r), p);
          if (!NOVAL && bad()) {
            const uint32_t m = slab(2 * i - 17 + warp, hg);
#pragma unroll 1
            for (uint32_t it = 0; it < 64; it++) {
              probe(m);
              if (elect_one()) { mbar_expect_tx(BAR(B_AR + warp - 13), 8192); bulk_ld(mine, og + m * 8192u, 8192, BAR(B_AR + warp - 13)); }
              mbar_wait(BAR(B_AR + warp - 13), ph);
              ph ^= 1;
              if (!bad()) break;
            }
          }
          if (elect_one()) mbar_arrive(BAR(B_VAL + r));
          if (++r == NA) { r = 0; p ^= 1; }
        }
      }
    }
  } else if (warp >= 8) {
    asm volatile("setmaxnreg.dec.sync.aligned.u32 %0;" ::"n"(MOE_REGS));
    if (MC) asm volatile("barrier.cluster.wait.aligned;" ::: "memory");
    const int aw = warp - 8;
    const uint32_t mbuf = sb + MISC + M_MOE, stg = sb + 12 * SLOT;
    mbar_wait(BAR(B_AST), 0);
    TLS(288, 64);
    {
      float v[16];
#pragma unroll
      for (int r = 0; r < 16; r++) v[r] = 0.f;
      const uint32_t base = stg + aw * 4 * 2048 + lane * 8;
#pragma unroll 1
      for (int c = 0; c < 8; c++) {
        const float2 w2 = lds_f2(mbuf + c * 256 + lane * 8);
        const float w[4] = {bf_lo(__float_as_uint(w2.x)), bf_hi(__float_as_uint(w2.x)), bf_lo(__float_as_uint(w2.y)), bf_hi(__float_as_uint(w2.y))};
        v[12] += (w[0] + w[1]) + (w[2] + w[3]);
#pragma unroll
        for (int r = 0; r < 4; r++) {
          const float2 x2 = lds_f2(base + r * 2048 + c * 256);
#pragma unroll
          for (int e = 0; e < 2; e++) {
            const uint32_t xx = __float_as_uint(e ? x2.y : x2.x);
            const float lo = bf_lo(xx), hi = bf_hi(xx);
            v[r] += lo; v[4 + r] = fmaf(lo, lo, v[4 + r]); v[8 + r] = fmaf(lo, w[2 * e], v[8 + r]);
            v[r] += hi; v[4 + r] = fmaf(hi, hi, v[4 + r]); v[8 + r] = fmaf(hi, w[2 * e + 1], v[8 + r]);
          }
        }
      }
#pragma unroll
      for (int l = 0; l < 4; l++) {
        const int n = 8 >> l;
        const bool up = lane & (2 * n);
#pragma unroll
        for (int r = 0; r < 8; r++) {
          if (r < n) { const float a = v[r], c = v[n + r]; v[r] = (up ? c : a) + __shfl_xor_sync(~0u, up ? a : c, 2 * n); }
        }
      }
      v[0] += __shfl_xor_sync(~0u, v[0], 1);
      const float sx = __shfl_sync(~0u, v[0], 2 * t), sq = __shfl_sync(~0u, v[0], 8 + 2 * t), sw = __shfl_sync(~0u, v[0], 16 + 2 * t), ws = __shfl_sync(~0u, v[0], 24);
      if (lane < 4) {
        const int row = b * 16 + aw * 4 + lane;
        const float mean = sx * (1.f / DM);
        const float var = fmaxf(fmaf(-mean, mean, sq * (1.f / DM)), 0.f);
        float sd;
        asm("sqrt.approx.ftz.f32 %0, %1;" : "=f"(sd) : "f"(bf_round(bf_round(var) + 1e-5f)));
        const float rstd = rcp(bf_round(sd));
        const float mb = bf_round(mean);
        uint32_t rb = pack_bf16(fmaf(-mb, ws, sw) * rstd, 0.f) & 0xFFFFu;
        rb = (rb & 0x8000u) ? (~rb & 0xFFFFu) : (rb | 0x8000u);
        const uint32_t key = (1u << 27) | (rb << 11) | (uint32_t)(2047 - row);
        if (KEY1) sts_u(sb + MISC + M_KEY + (aw * 4 + lane) * 4, key); else stx1(G.key + row, key);
        G.stats[row] = make_float2(mb, SL2 ? rstd * LOG2E : rstd);
      }
    }
    bar_sync<2, 128>();
    if (KEY1 && ltid < 272) stx1(G.key + b * 16 + lane, lds_u(sb + MISC + M_KEY + lane * 4));
    TLS(288, 65);
    sts_u4(sb + A_ONES + (ltid - 256) * 16, make_uint4(0x3F803F80u, 0x3F803F80u, 0x3F803F80u, 0x3F803F80u));
    fence_async_smem();
    asm volatile("bar.arrive 5, 160;" ::: "memory");
    if (ltid == 256) { if (unit && rank == 0) mbar_expect_tx(BAR(B_UP), 2048); mbar_arrive(BAR(B_XS)); }
    bar_sync<2, 128>();
    mbar_wait(BAR(B_XS), 1);
    TLS(288, 70);
    if (NUNIT) {
      if (unit) {
        int r = 0, p = 0;
        uint32_t rel = 0;
        float acc[8];
        uint2 s0, s1;
#pragma unroll
        for (int i = 0; i < 8; i++) acc[i] = 0.f;
        if (MS == 16) mbar_wait(BAR(B_T0), 0); else if (MS) mbar_wait(BAR(B_MS), 0);
#pragma unroll 1
        for (int n = 0; n < 16; n++) {
          if (n == 15) {
            mbar_wait(BAR(B_FAUX), 0);
            s0 = ldx2(G.stats + (~lds_u(sb + MISC + M_IDX + t * 8) & 2047)); s1 = ldx2(G.stats + (~lds_u(sb + MISC + M_IDX + t * 8 + 4) & 2047));
            if (SL2) { s0.y = __float_as_uint(__uint_as_float(s0.y) * LN2); s1.y = __float_as_uint(__uint_as_float(s1.y) * LN2); }
          }
          mbar_wait(BAR(B_MF + r), p);
          if (!(n & 3)) TLS(288, 56 + (n >> 2));
          const uint32_t mo = m_off(r) >> 4, da = (d0 + mo) | (512u << 16), db = (d0 + mo + 512) | (1u << 16);
          const uint32_t hb = 0x40000000u | ((A_ONES >> 4) - 512 - mo);
          wg_fence();
#pragma unroll
          for (int kk = 0; kk < ((MX & 1) ? 1 : 4); kk++) wgmma_ss_n16<1, 0>(acc, mkdesc(da + kk * 128, HI_SW128), mkdesc(db + kk * 2, hb));
          wg_commit();
          wg_wait<1>();
          if (n > 0 && !rel && ltid == 256) mbar_arrive(BAR(B_ME + (r == 0 ? NR - 1 : r - 1)));
          rel = 0;
          const int r0 = r;
          if (++r == NR) { r = 0; p ^= 1; }
        }
        wg_wait<0>();
        reg_fence(acc);
        {
          if (!MW0 && !rel && ltid == 256) mbar_arrive(BAR(B_ME + 15 % NR));
          TLS(288, 71);
          const float v0 = bf_round(fmaf(-__uint_as_float(s0.x), acc[4], acc[0]) * __uint_as_float(s0.y));
          const float v1 = bf_round(fmaf(-__uint_as_float(s1.x), acc[4], acc[1]) * __uint_as_float(s1.y));
          const float v2 = bf_round(fmaf(-__uint_as_float(s0.x), acc[6], acc[2]) * __uint_as_float(s0.y));
          const float v3 = bf_round(fmaf(-__uint_as_float(s1.x), acc[6], acc[3]) * __uint_as_float(s1.y));
          if (rank) {
            asm volatile("{\n.reg .b32 ra, rb;\nmapa.shared::cluster.u32 ra, %0, 0;\nmapa.shared::cluster.u32 rb, %1, 0;\n"
                         "st.async.weak.shared::cluster.mbarrier::complete_tx::bytes.v4.f32 [ra], {%2, %3, %4, %5}, [rb];\n}"
                         ::"r"(mbuf + (ltid - 256) * 16), "r"(BAR(B_UP)), "f"(v0), "f"(v1), "f"(v2), "f"(v3) : "memory");
          } else {
            const float g0 = bf_round(v0 * sigmoid(v0)), g1 = bf_round(v1 * sigmoid(v1)), g2 = bf_round(v2 * sigmoid(v2)), g3 = bf_round(v3 * sigmoid(v3));
            mbar_wait(BAR(B_UP), 0);
            const uint4 uu = lds_u4(mbuf + (ltid - 256) * 16);
            const uint32_t h0 = movmat(pack_bf16(g0 * __uint_as_float(uu.x), g1 * __uint_as_float(uu.y)));
            const uint32_t h1 = movmat(pack_bf16(g2 * __uint_as_float(uu.z), g3 * __uint_as_float(uu.w)));
            uint32_t* ph = G.h + (u >> 1) * 256 + g * 32 + t;
            stx1(ph + ((2 * aw) ^ g) * 4, h0); stx1(ph + ((2 * aw + 1) ^ g) * 4, h1);
          }
          TLS(288, 60);
        }
      }
    }
    if (PH) asm volatile("bar.arrive 3, 192;" ::: "memory");
    {
      const int wd_ = ltid & 63;
      const uint32_t* src = reinterpret_cast<const uint32_t*>(G.part + hg * 544 + (aw >> 1) * 256 + tb * 16) + wd_;
      mbar_wait(MRED == 2 ? BAR(B_ZOK) : BAR(B_EQ + MRW), 0);
      if (MRD) __nanosleep(MRD);
      TLS(256, 48);
      uint32_t v[16];
#pragma unroll 1
      for (uint32_t it = 0; it < SPIN_MAX; it++) {
        uint32_t m = 0;
#pragma unroll
        for (int i = 0; i < 16; i++) v[i] = ldx1(src + i * 8 * 2176);
#pragma unroll
        for (int i = 0; i < 16; i++) m = max(m, v[i]);
        if (!__any_sync(~0u, m == SENT)) break;
      }
      TLS(256, 55);
      float lo[4], hi[4];
#pragma unroll
      for (int i = 0; i < 4; i++) {
        lo[i] = (bf_lo(v[4 * i]) + bf_lo(v[4 * i + 1])) + (bf_lo(v[4 * i + 2]) + bf_lo(v[4 * i + 3]));
        hi[i] = (bf_hi(v[4 * i]) + bf_hi(v[4 * i + 1])) + (bf_hi(v[4 * i + 2]) + bf_hi(v[4 * i + 3]));
      }
      stx1(reinterpret_cast<uint32_t*>(G.fin + hg * 640) + (tb >> 2) * 640 + ((tb >> 1) & 1) * 64 + (tb & 1) * 16 + (aw >> 1) * 32 + ((wd_ >> 2) & 3) * 128 + (wd_ >> 4) * 4 + (wd_ & 3),
           pack_bf16((lo[0] + lo[1]) + (lo[2] + lo[3]), (hi[0] + hi[1]) + (hi[2] + hi[3])));
      TLS(256, 5);
    }
    if (NUNIT) {
      mbar_wait(BAR(B_STG), 0);
      bar_sync<2, 128>();
      if (HW) __nanosleep(HW);
#pragma unroll 1
      for (uint32_t it = 0; it < SPIN_MAX; it++) {
        if (elect_one()) {
          const uint32_t* ph = G.h + (u >> 4) * 7 * 256;
          if (aw == 3) { mbar_expect_tx(BAR(B_HF), 7168); bulk_ld(sb + h_off(3), ph + 768, 2048, BAR(B_HF)); bulk_ld(sb + h_off(5), ph + 1280, 2048, BAR(B_HF)); }
          else bulk_ld(stg + aw * MT + 8192, ph + aw * 256, 1024, BAR(B_HF));
        }
        mbar_wait(BAR(B_HF), it & 1);
        const uint32_t o = (ltid & 63) * 16 + (g >> 1) * 4, o2 = o + (aw >> 1) * 1024;
        const uint32_t m = max(max(lds_u(sb + h_off(0) + (aw >> 1) * MT + o), lds_u(sb + h_off(2) + o)), max(lds_u(sb + h_off(3) + o2), lds_u(sb + h_off(5) + o2)));
        uint32_t bad;
        asm volatile("{\n.reg .pred p, q;\nsetp.eq.u32 p, %1, 0xFFFFFFFF;\nbar.red.or.pred q, 2, 128, p;\nselp.b32 %0, 1, 0, q;\n}" : "=r"(bad) : "r"(m) : "memory");
        if (!__any_sync(~0u, bad)) break;
        __nanosleep(POLLNS);
      }
      TLS(288, 62);
      float acc[4] = {0.f, 0.f, 0.f, 0.f};
      mbar_wait(BAR(B_DF), 0);
      TLS(288, 63);
#pragma unroll 1
      for (int i = 0; i < 7; i++) {
        const uint32_t da = (d0 + (d_off(i) >> 4)) | (512u << 16), db = (d0 + (h_off(i) >> 4)) | (1u << 16);
        wg_fence();
#pragma unroll
        for (int kk = 0; kk < ((MX & 4) ? 1 : 4); kk++) wgmma_ss_n8<1, 0>(acc, mkdesc(da + kk * 128, HI_SW128), mkdesc(db + kk * 2, HI_SW128));
        wg_commit();
      }
      wg_wait<0>();
      reg_fence(acc);
      if (ltid < 258) { if (MC) mbar_arrive_cta(BAR(B_DE), ltid & 1); else mbar_arrive(BAR(B_DE)); }
      {
        uint32_t* py = reinterpret_cast<uint32_t*>(G.y) + u * 512 + t * 128 + aw * 16 + g;
        stx1(py, f2x(acc[0])); stx1(py + 64, f2x(acc[1])); stx1(py + 8, f2x(acc[2])); stx1(py + 72, f2x(acc[3]));
      }
      TLS(288, 69);
      const uint32_t key = lds_u(sb + MISC + M_IDX + (lane & 7) * 4);
      uint32_t rb = (key >> 11) & 0xFFFFu;
      rb = (rb & 0x8000u) ? (rb & 0x7FFFu) : (~rb & 0xFFFFu);
      const float sg = bf_round(sigmoid(__uint_as_float(rb << 16)));
      uint32_t hits = __ballot_sync(~0u, ((~key >> 7) & 15) == tb) & 255u;
      const uint32_t* py = reinterpret_cast<const uint32_t*>(G.y) + (2 * hg + (aw >> 1)) * 512 + (ltid & 63);
      if (hits) {
        sts_u4(mbuf + (ltid - 256) * 16, make_uint4(0, 0, 0, 0));
        bar_sync<2, 128>();
        if (YW >= 0) mbar_wait(BAR(B_EO + YW), 0); else if (YW == -2) mbar_wait(BAR(B_EAUX), 0);
      }
#pragma unroll 1
      while (hits) {
        const int n0 = __ffs(hits) - 1;
        hits &= hits - 1;
        const int n1 = hits ? __ffs(hits) - 1 : n0;
        hits &= hits - 1;
        uint32_t v[16];
#pragma unroll 1
        for (uint32_t it = 0; it < SPIN_MAX; it++) {
          uint32_t m = 0;
#pragma unroll
          for (int i = 0; i < 8; i++) { v[i] = ldx1(py + n0 * 64 + i * 8192); v[8 + i] = ldx1(py + n1 * 64 + i * 8192); }
#pragma unroll
          for (int i = 0; i < 16; i++) m = max(m, v[i]);
          if (!__any_sync(~0u, m == SENT)) break;
          __nanosleep(POLLNS);
        }
#pragma unroll
        for (int e = 0; e < 2; e++) {
          const uint32_t* w8 = v + 8 * e;
          const float y = ((__uint_as_float(w8[0]) + __uint_as_float(w8[1])) + (__uint_as_float(w8[2]) + __uint_as_float(w8[3]))) +
                          ((__uint_as_float(w8[4]) + __uint_as_float(w8[5])) + (__uint_as_float(w8[6]) + __uint_as_float(w8[7])));
          const int n = e ? n1 : n0;
          sts_h(mbuf + (aw >> 1) * 1024 + n * 128 + ((((ltid >> 3) & 7) ^ n) << 4) + (lane & 7) * 2, bf_round(y) * __shfl_sync(~0u, sg, n));
        }
      }
    }
    if (!NUNIT && ltid < 258) mbar_arrive(BAR(B_DE));
    fence_async_smem();
    bar_sync<2, 128>();
    TLS(288, 33);
    if (ltid == 288) mbar_arrive(BAR(B_MOE));
  } else {
    asm volatile("setmaxnreg.inc.sync.aligned.u32 %0;" ::"n"(CON_REGS));
    if (MC) asm volatile("barrier.cluster.wait.aligned;" ::: "memory");
    const int w = warp >> 2, wq = warp & 3, tid = ltid;
    const bool lead = (tid & 127) == 0;
    const uint32_t dA = (d0 + w * 512) | (1u << 16);
    const uint32_t dB = d0 | (512u << 16);
    auto release = [&](int bar) { if (lead) mbar_arrive(BAR(bar)); };
    auto release2 = [&](int bar) {
      if (MC) { if ((tid & 127) < 2) mbar_arrive_cta(BAR(bar), tid & 1); } else release(bar);
    };
    float aq[64], ak[64], av[64];
#pragma unroll
    for (int i = 0; i < 64; i++) aq[i] = ak[i] = av[i] = 0.f;
    auto q_step = [&](uint32_t bar, int p, uint32_t xs, uint32_t qs) {
      mbar_wait_b(bar, p);
      wg_fence();
#pragma unroll
      for (int kk = 0; kk < 4; kk++)
        wgmma_ss_n128<0, 1>(aq, mkdesc(dA + xs * 1024 + kk * 2, HI_SW128), mkdesc(dB + qs * 1024 + kk * 128, HI_SW128));
      wg_commit();
    };
    const uint32_t dT = dB + w * 512, dX = d0 | (1u << 16);
    auto t_step = [&](float (&a)[64], uint32_t ws, uint32_t xs) {
      wg_fence();
#pragma unroll
      for (int kk = 0; kk < 4; kk++)
        wgmma_ss_n128<1, 0>(a, mkdesc(dT + ws * 1024 + kk * 128, HI_SW128), mkdesc(dX + xs * 1024 + kk * 2, HI_SW128));
      wg_commit();
    };
    {
      int s = 0, p = 0, sp = 2;
#pragma unroll 1
      for (int e = 0; e < NF; e++) {
        TLS(0, 16 + e);
        if (((MS && MS < NF) || (DS && DS < NF)) && e == (MS ? MS : DS)) release(B_MS);
        q_step(BAR(B_FXQ + s), p, s, 3 + s);
        wg_wait<1>();
        if (e > 0) release2(B_E + sp);
        mbar_wait(BAR(B_FKV + s), p);
        t_step(ak, 6 + 2 * s, s);
        if (R5) mbar_wait(BAR(B_FV + s), p);
        t_step(av, 7 + 2 * s, s);
        if (R5 && e == NF - 1) { wg_wait<1>(); release2(B_EK + s); }
        sp = s;
        if (++s == 3) { s = 0; p ^= 1; }
      }
#pragma unroll 1
      for (int e = NF; e < 16; e++) {
        TLS(0, 16 + e);
        if (((MS >= NF && MS < 16) || DS >= NF) && e == (MS ? MS : DS)) release(B_MS);
        if (ST && e == 16 - ST && w == 1) mbar_wait(BAR(B_GT), 0);
        mbar_wait(BAR(B_FXQ + s), p);
        mbar_wait(BAR(B_FKV + s), p);
        t_step(ak, R5 ? (K_SLOTS >> (4 * (e - 10))) & 15u : 6 + 2 * s, x_slot(e, s));
        wg_wait<1>();
        release2(B_E + sp);
        if (R5) mbar_wait(BAR(B_FV + s), p);
        t_step(av, R5 ? (V_SLOTS >> (4 * (e - 10))) & 15u : 7 + 2 * s, x_slot(e, s));
        if (ST && e == 15 && tid == 0) mbar_arrive(BAR(B_GT));
        if (R5) { wg_wait<1>(); release2(B_EK + s); }
        sp = s;
        if (++s == 3) { s = 0; p ^= 1; }
      }
    }
    const uint32_t aux = sb;
    mbar_wait(BAR(B_FAUX), 0);
    const int row0 = w * 64 + wq * 16 + g;
    const float ck0 = lds_f(aux + A_CS + 512 + row0 * 4), ck1 = lds_f(aux + A_CS + 512 + (row0 + 8) * 4);
    const float cv0 = lds_f(aux + A_CS + 1024 + row0 * 4), cv1 = lds_f(aux + A_CS + 1024 + (row0 + 8) * 4);
    const uint32_t moff = (uint32_t)(w * 64 + wq * 16 + (lane & 15)) * 128 + (((lane >> 4) ^ (lane & 7)) << 4);
    const uint32_t sta = aux + A_ST + t * 16;
    float kvp[36], ao[64];
    uint32_t xr[32];
    float nm0, nm1, rs0, rs1, rl0, rl1;
    auto row_stats = [&]() {
      const float2 st0 = lds_f2(aux + A_ST + row0 * 8), st1 = lds_f2(aux + A_ST + (row0 + 8) * 8);
      nm0 = -st0.x; nm1 = -st1.x;
      if (SL2) { rl0 = st0.y; rl1 = st1.y; rs0 = rl0 * LN2; rs1 = rl1 * LN2; }
      else { rs0 = st0.y; rs1 = st1.y; rl0 = rs0 * LOG2E; rl1 = rs1 * LOG2E; }
    };
    auto ld_x = [&]() {
#pragma unroll
      for (int j = 0; j < 16; j += 2) ldsm4(sb + (j < 8 ? SX14 : SX15) * SLOT + (moff ^ ((j & 7) << 4)), xr[2 * j], xr[2 * j + 1], xr[2 * j + 2], xr[2 * j + 3]);
    };
    auto resid = [&]() {
      const float c0 = 1.f + rs0, c1 = 1.f + rs1, e0 = nm0 * rs0, e1 = nm1 * rs1;
#pragma unroll
      for (int j = 0; j < 16; j++) {
        ao[4 * j + 0] = fmaf(bf_lo(xr[2 * j]), c0, e0); ao[4 * j + 1] = fmaf(bf_hi(xr[2 * j]), c0, e0);
        ao[4 * j + 2] = fmaf(bf_lo(xr[2 * j + 1]), c1, e1); ao[4 * j + 3] = fmaf(bf_hi(xr[2 * j + 1]), c1, e1);
      }
    };
    {
      uint32_t pa[32];
      float4 st[16];
      auto ld = [&](int j) { st[j] = lds_f4(sta + j * 64); };
      auto k_blk = [&](int c) {
#pragma unroll
        for (int i = 0; i < 2; i++) {
          const float4 u = st[2 * c + i];
          const float l0 = u.y * LOG2E, l1 = u.w * LOG2E;
          const float* a = ak + 8 * c + 4 * i;
          pa[4 * c + 2 * i] = SL2 ? phi2l(fmaf(-u.x, ck0, a[0]), u.y, fmaf(-u.z, ck0, a[1]), u.w) : phi2<(VOL & 1) != 0>(fmaf(-u.x, ck0, a[0]), u.y, l0, fmaf(-u.z, ck0, a[1]), u.w, l1);
          pa[4 * c + 2 * i + 1] = SL2 ? phi2l(fmaf(-u.x, ck1, a[2]), u.y, fmaf(-u.z, ck1, a[3]), u.w) : phi2<(VOL & 1) != 0>(fmaf(-u.x, ck1, a[2]), u.y, l0, fmaf(-u.z, ck1, a[3]), u.w, l1);
        }
      };
      const uint32_t voff = sb + w * 8192 + (uint32_t)(8 * (lane >> 4) + (lane & 7)) * 128 + (((2 * wq + ((lane >> 3) & 1)) ^ (lane & 7)) << 4);
      auto v_blk = [&](int c) {
        uint32_t r[4];
#pragma unroll
        for (int i = 0; i < 2; i++) {
          const float4 u = st[2 * c + i];
          const float* a = av + 8 * c + 4 * i;
          r[2 * i] = pack_bf16(fmaf(-u.x, cv0, a[0]) * u.y, fmaf(-u.z, cv0, a[1]) * u.w);
          r[2 * i + 1] = pack_bf16(fmaf(-u.x, cv1, a[2]) * u.y, fmaf(-u.z, cv1, a[3]) * u.w);
        }
        stsm4t(voff + (c < 4 ? S_V0 : S_V1) * SLOT + (c & 3) * 2048, r[0], r[1], r[2], r[3]);
      };
      auto kv_mma = [&](int c) {
        const uint32_t bo = (c < 4 ? S_V0 : S_V1) * 1024 + w * 512 + (c & 3) * 128;
        const uint64_t bb = mkdesc((d0 + bo) | (((A_ONES >> 4) - bo) << 16), HI_SW128);
        if (c == 0) wgmma_rz_n72<1>(kvp, pa[4 * c], pa[4 * c + 1], pa[4 * c + 2], pa[4 * c + 3], bb);
        else wgmma_rs_n72<1>(kvp, pa[4 * c], pa[4 * c + 1], pa[4 * c + 2], pa[4 * c + 3], bb);
      };
      ld(0); ld(1);
      wg_wait<0>();
      reg_fence(ak); reg_fence(av);
      TLS(0, 2);
      if (!R5) release2(B_E);
      release(B_T0);
      if (LQ) { v_blk(0); ld(2); ld(3); } else { ld(2); ld(3); v_blk(0); }
      ld(4); ld(5); v_blk(1); k_blk(0);
      ld(6); ld(7); v_blk(2); ld(8); ld(9); v_blk(3); k_blk(1);
      ld(10); ld(11); v_blk(4); ld(12); ld(13); v_blk(5); k_blk(2);
      ld(14); ld(15); v_blk(6); v_blk(7); k_blk(3);
      if (RL) { ld(8); ld(9); }
#pragma unroll
      for (int c = 4; c < KS; c++) k_blk(c);
      TLS(0, 3);
      fence_async_smem();
      asm volatile("bar.sync %0, 128;" ::"r"(3 + w) : "memory");
      if (XP == 0) ld_x();
      wg_fence();
#pragma unroll
      for (int c = 0; c < KS; c++) kv_mma(c);
      wg_commit();
#pragma unroll
      for (int c = KS; c < 8; c++) {
        if (RL && c < 7) { ld(2 * c + 2); ld(2 * c + 3); }
        k_blk(c);
        wg_fence();
        kv_mma(c);
        wg_commit();
      }
      if (XP == 3 && (RK == 0 || RK == 9)) ld_x();
      if (QE) { q_step(BAR(B_FQ), 0, SXQ0, QW_SLOTS & 15u); wg_wait<1>(); } else wg_wait<0>();
      reg_fence(kvp);
      auto hand_back = [&]() { release2(B_STG); __syncwarp(); };
      if (!SF) hand_back();
      TLS(0, 4);
      uint4* pp = G.part + b * 544;
      uint32_t pk[8];
#pragma unroll
      for (int j = 0; j < 8; j++) pk[j] = wq >= 2 ? pack_bf16(kvp[16 + 2 * j], kvp[17 + 2 * j]) : pack_bf16(kvp[2 * j], kvp[2 * j + 1]);
      stx4(pp + tid, pk[0], pk[2], pk[4], pk[6]);
      stx4(pp + 256 + tid, pk[1], pk[3], pk[5], pk[7]);
      if (t == 0) stx2(reinterpret_cast<uint2*>(pp + 512) + (tid >> 2), f2x(kvp[32]), f2x(kvp[34]));
      if (SF == 1) hand_back();
      if (XP == 1) ld_x();
      if (!QE) q_step(BAR(B_FQ), 0, SXQ0, QW_SLOTS & 15u);
      if (XP == 2) ld_x();
      if (SF == 2) hand_back();
      if (RK == 0 || RK == 9) {
        uint32_t chk = 0;
#pragma unroll
        for (int j = 0; j < 8; j++) chk ^= xr[4 * j];
        asm volatile("{\n.reg .pred p;\nsetp.eq.u32 p, %0, 0x7FC17FC3;\n@p st.shared.u32 [%1], %0;\n}" ::"r"(chk), "r"(sb + MISC + M_DUM) : "memory");
      }
      const int wd_ = wq * 16 + (lane & 15);
      const uint32_t* src = reinterpret_cast<const uint32_t*>(G.part + ((lane >> 4) * 64 + hg) * 544 + w * 256 + tb * 16) + wd_;
      uint32_t* fin = reinterpret_cast<uint32_t*>(G.fin + hg * 640) + (tb >> 2) * 640 + ((tb >> 1) & 1) * 64 + (tb & 1) * 16 + w * 32 + ((wd_ >> 2) & 3) * 128 + wq * 4 + (wd_ & 3);
      uint32_t v[8];
      auto part_load = [&]() {
#pragma unroll
        for (int i = 0; i < 8; i++) v[i] = ldx1(src + i * 8 * 2176);
      };
#pragma unroll
      for (int k = 1; k < NQ; k++) {
        if (SQ && k == NQ - SQ && w == 1) mbar_wait(BAR(B_GQ), 0);
        q_step(BAR(B_FQ + k), 0, (QX_SLOTS >> (4 * k)) & 15u, (QW_SLOTS >> (4 * k)) & 15u);
        if (SQ && k == NQ - 1 && tid == 0) mbar_arrive(BAR(B_GQ));
        TLS(0, 48 + k);
        if (!MRED && k == PLP) part_load();
        if (!MRED && k == PLC) {
#pragma unroll 1
          for (uint32_t it = 0; it < SPIN_MAX; it++) {
            if (!__any_sync(~0u, max(max(max(v[0], v[1]), max(v[2], v[3])), max(max(v[4], v[5]), max(v[6], v[7]))) == SENT)) break;
            part_load();
          }
          float lo = ((bf_lo(v[0]) + bf_lo(v[1])) + (bf_lo(v[2]) + bf_lo(v[3]))) + ((bf_lo(v[4]) + bf_lo(v[5])) + (bf_lo(v[6]) + bf_lo(v[7])));
          float hi = ((bf_hi(v[0]) + bf_hi(v[1])) + (bf_hi(v[2]) + bf_hi(v[3]))) + ((bf_hi(v[4]) + bf_hi(v[5])) + (bf_hi(v[6]) + bf_hi(v[7])));
          lo += __shfl_xor_sync(~0u, lo, 16); hi += __shfl_xor_sync(~0u, hi, 16);
          if (lane < 16) stx1(fin, pack_bf16(lo, hi));
          TLS(0, 5);
        }
        wg_wait<1>();
        release2(B_EQ + k - 1);
        if (k == RK) { row_stats(); ld_x(); resid(); reg_fence(ao); }
      }
      TLS(0, 13);
      mbar_wait(BAR(B_CQ), 0);
    }
    wg_wait<0>();
    reg_fence(aq);
    TLS(0, 15);
    if (RK == 0 || RK == 9) row_stats();
    uint32_t pq[32];
#pragma unroll
    for (int j = 0; j < 16; j += 2) {
      float4 c4;
      if (CQ4) c4 = lds_f4(aux + A_CS + (j * 8 + 4 * t) * 4);
      else { const float2 ca = lds_f2(aux + A_CS + (j * 8 + 2 * t) * 4), cb = lds_f2(aux + A_CS + (j * 8 + 8 + 2 * t) * 4); c4 = make_float4(ca.x, ca.y, cb.x, cb.y); }
#pragma unroll
      for (int i = 0; i < 2; i++) {
        const float cx = i ? c4.z : c4.x, cy = i ? c4.w : c4.y;
        const float* a = aq + 4 * (j + i);
        pq[2 * (j + i)] = SL2 ? phi2l(fmaf(nm0, cx, a[0]), rl0, fmaf(nm0, cy, a[1]), rl0) : phi2<(VOL & 2) != 0>(fmaf(nm0, cx, a[0]), rs0, rl0, fmaf(nm0, cy, a[1]), rs0, rl0);
        pq[2 * (j + i) + 1] = SL2 ? phi2l(fmaf(nm1, cx, a[2]), rl1, fmaf(nm1, cy, a[3]), rl1) : phi2<(VOL & 2) != 0>(fmaf(nm1, cx, a[2]), rs1, rl1, fmaf(nm1, cy, a[3]), rs1, rl1);
      }
    }
    TLS(0, 6);
    if (RK == 9) { resid(); if (RF) reg_fence(ao); }
    mbar_wait_b(BAR(MFIN ? B_KV4 : B_KVB), 0);
    TLS(0, 7);
    uint32_t of[32];
    uint4* mine = G.o + (tb * 32 + hg) * 512 + warp * 64 + g * 4 + (t ^ (g >> 1));
    const uint32_t dW = d0 | (256u << 16);
    auto o_store = [&](int h) {
#pragma unroll
      for (int c = 0; c < 2; c++) stx4(mine + h * 4096 + c * 32, of[8 * h + c], of[8 * h + 2 + c], of[8 * h + 4 + c], of[8 * h + 6 + c]);
    };
    auto out_step = [&](uint32_t slot, const uint32_t* a) {
      const uint32_t d = dW + slot * 1024;
      wg_fence();
#pragma unroll
      for (int kk = 0; kk < 4; kk++) wgmma_rs_n128<1>(ao, a[4 * kk], a[4 * kk + 1], a[4 * kk + 2], a[4 * kk + 3], mkdesc(d + (kk >> 1) * 512 + (kk & 1) * 128, HI_SW128));
      wg_commit();
    };
    uint4 v[NDIR][4];
    auto ld_o = [&](int k) {
      const uint4* p0 = mine + (slab(2 * k, hg) - hg) * 512;
      const uint4* p1 = mine + (slab(2 * k + 1, hg) - hg) * 512;
      v[k][0] = ldx4(p0); v[k][1] = ldx4(p0 + 32); v[k][2] = ldx4(p1); v[k][3] = ldx4(p1 + 32);
    };
    auto ld_all = [&]() {
#pragma unroll
      for (int k = 0; k < NDIR; k++) ld_o(k);
    };
    {
      float oa[4][20];
      const uint32_t dK = (d0 + S_KVB * 1024) | (8u << 16);
      wg_fence();
#pragma unroll
      for (int h = 0; h < 4; h++) {
        wgmma_rz_n40<1>(oa[h], pq[8 * h], pq[8 * h + 1], pq[8 * h + 2], pq[8 * h + 3], mkdesc(dK + h * 160, HI_NOSW));
        wgmma_rs_n40<1>(oa[h], pq[8 * h + 4], pq[8 * h + 5], pq[8 * h + 6], pq[8 * h + 7], mkdesc(dK + h * 160 + 16, HI_NOSW));
        if (h == 0 || h == 3) wg_commit();
      }
      auto norm = [&](int h) {
        const float r0 = SL2 ? rcp(fmaf(oa[h][16], LOG2E, 1e-6f * LOG2E)) : rcp(oa[h][16] + 1e-6f);
        const float r1 = SL2 ? rcp(fmaf(oa[h][18], LOG2E, 1e-6f * LOG2E)) : rcp(oa[h][18] + 1e-6f);
#pragma unroll
        for (int j = 0; j < 4; j++) {
          of[8 * h + 2 * j] = pack_bf16(oa[h][4 * j] * r0, oa[h][4 * j + 1] * r0);
          of[8 * h + 2 * j + 1] = pack_bf16(oa[h][4 * j + 2] * r1, oa[h][4 * j + 3] * r1);
        }
      };
      wg_wait<1>();
      reg_fence(oa[0]);
      norm(0);
      if (LE == 4) ld_all();
      o_store(0);
      if (LE == 3) ld_all();
      TLS(0, 8);
      wg_wait<0>();
      reg_fence(oa[1]); reg_fence(oa[2]); reg_fence(oa[3]);
      TLP_(0);
      release(B_EAUX);
      norm(1);
      if (OS1 == 3) o_store(1);
      if (E7 && NP == 0 && SL7 && hg == 7) o_store(1);
      if (NP == 0) { norm(2); norm(3); }
      if (E7 && NP == 0 && SL7 && hg == 7) { o_store(2); o_store(3); }
      TLP_(1);
      mbar_wait_b(BAR(B_FWO), 0);
      TLP_(2);
      if (RK == 0) resid();
      if (LE == 2) ld_all();
      TLP_(3);
      out_step(WO_SLOTS & 15u, of);
      TLP_(4);
      if (NP == 1) { norm(2); norm(3); }
      if (LE == 1) ld_all();
      if (LE == 5) ld_o(0);
    }
    if (OS1 == 0) o_store(1);
    mbar_wait(BAR(B_FWO + 1), 0);
    TLP_(5);
    out_step((WO_SLOTS >> 4) & 15u, of + 16);
    TLP_(6);
    const bool early = SL7 && hg == 7;
    if (OS1 == 1 && !(E7 && early)) o_store(1);
    TLP_(7);
    if (early && !E7) { o_store(2); o_store(3); }
    {
      if (DW) __nanosleep(DW);
      if (LE == 0) ld_all();
      if (LE == 5 && NDIR > 1) ld_o(NDIR - 1);
      if (OS1 == 2 && !(E7 && early)) o_store(1);
#pragma unroll
      for (int k = 0; k < NDIR; k++) {
#pragma unroll 1
        for (uint32_t it = 0; it < SPIN_MAX; it++) {
          if (!__any_sync(~0u, max(max(v[k][0].x, v[k][1].x), max(v[k][2].x, v[k][3].x)) == SENT)) break;
#pragma unroll
          for (int j = k; j < (LE == 5 ? k + 1 : NDIR); j++) ld_o(j);
        }
        TLP_(8);
        const uint32_t a[16] = {v[k][0].x, v[k][1].x, v[k][0].y, v[k][1].y, v[k][0].z, v[k][1].z, v[k][0].w, v[k][1].w,
                                v[k][2].x, v[k][3].x, v[k][2].y, v[k][3].y, v[k][2].z, v[k][3].z, v[k][2].w, v[k][3].w};
        mbar_wait(BAR(B_FWO + 2 + k), 0);
        TLS(0, 34 + k);
        out_step((WO_SLOTS >> (8 + 4 * k)) & 15u, a);
        TLP_(9);
        if (k) { wg_wait<1>(); release2(B_EO); }
      }
      if (!early) o_store(2);
    }
    auto routed = [&]() {
      mbar_wait(BAR(B_MOE), 0);
      const float2 kk = lds_f2(sb + MISC + M_IDX + t * 8);
      const int k0 = (int)(~__float_as_uint(kk.x) & 2047u) - tb * 128, k1 = (int)(~__float_as_uint(kk.y) & 2047u) - tb * 128;
      if (NUNIT && __any_sync(~0u, (k0 >> 6) == w || (k1 >> 6) == w)) {
        const uint32_t a0 = (k0 == row0 ? 0x3F80u : 0u) | (k1 == row0 ? 0x3F800000u : 0u);
        const uint32_t a1 = (k0 == row0 + 8 ? 0x3F80u : 0u) | (k1 == row0 + 8 ? 0x3F800000u : 0u);
        wg_fence();
        wgmma_rs_n128<1>(ao, a0, a1, 0u, 0u, mkdesc((d0 + ((MISC + M_MOE) >> 4)) | (64u << 16), 0x40000000u));
        wg_commit();
      }
    };
    auto out_half = [&](int h, const float* v) {
      const uint32_t ost = sb + (w ? S_D1 : S_D0) * SLOT + wq * 4096 + h * 2048;
#pragma unroll
      for (int j = 0; j < 8; j += 2)
        stsm4(ost + ((moff & 2047) ^ (j << 4)), pack_bf16(v[4 * j], v[4 * j + 1]), pack_bf16(v[4 * j + 2], v[4 * j + 3]),
              pack_bf16(v[4 * j + 4], v[4 * j + 5]), pack_bf16(v[4 * j + 6], v[4 * j + 7]));
      if (OUTV == 3 || (OUTV == 4 && h == 0)) {
        __syncwarp();
        __nv_bfloat16* dst = outp + (size_t)(tb * 128 + warp * 16 + (lane >> 3)) * DM + hg * 128 + h * 64 + (lane & 7) * 8;
#pragma unroll
        for (int i = 0; i < 4; i++) {
          const int r = 4 * i + (lane >> 3);
          const uint4 u4 = lds_u4(ost + r * 128 + (((lane & 7) ^ (r & 7)) << 4));
          asm volatile("st.global.v4.u32 [%0], {%1,%2,%3,%4};" ::"l"(dst + (size_t)i * 4 * DM), "r"(u4.x), "r"(u4.y), "r"(u4.z), "r"(u4.w) : "memory");
        }
        return;
      }
      fence_async_smem();
      __syncwarp();
      if (elect_one()) {
        asm volatile("cp.async.bulk.tensor.2d.global.shared::cta.bulk_group [%0, {%2, %3}], [%1];" ::"l"(&tmOut), "r"(ost), "r"(hg * 128 + h * 64), "r"(tb * 128 + warp * 16) : "memory");
        if (h) asm volatile("cp.async.bulk.commit_group;\ncp.async.bulk.wait_group.read 0;" ::: "memory");
      }
      __syncwarp();
    };
    bool done = false;
    {
      const uint32_t dO = (d0 + w * 256) | (1u << 16);
      auto step = [&](int i, int r, int p, uint32_t as, uint32_t ws) {
        mbar_wait(BAR(B_FWO + i), 0);
        mbar_wait(BAR(B_VAL + r), p);
        TLS(0, 32 + i);
        const uint32_t da = dO + as * 1024, db = dW + ws * 1024;
        wg_fence();
#pragma unroll
        for (int kk = 0; kk < 4; kk++)
          wgmma_ss_n128<0, 1>(ao, mkdesc(da + (kk >> 1) * 512 + (kk & 1) * 2, HI_SW64), mkdesc(db + (kk >> 1) * 512 + (kk & 1) * 128, HI_SW128));
        wg_commit();
      };
      uint64_t tbl = WO_SLOTS >> (4 * I0);
      int r = 0, p = 0, rp = 0;
#pragma unroll 1
      for (int i = I0; i < 12; i++) {
        step(i, r, p, (A_SLOTS >> (4 * r)) & 15u, (uint32_t)tbl & 15u);
        tbl >>= 4;
#pragma unroll
        for (int c = 0; c < 2; c++)
          if (i == OS3 + c && !early) stx4(mine + 3 * 4096 + c * 32, of[24 + c], of[26 + c], of[28 + c], of[30 + c]);
        wg_wait<1>();
        if (i > I0) release(B_EA + rp);
        rp = r;
        if (++r == NA) { r = 0; p ^= 1; }
        if (i >= 3 && i <= 9) release2(B_EO + i - 3);
      }
      if (SPL && w == 1) {
        float bl[32], bh[32];
        mbar_wait(BAR(B_GO), 0);
        routed();
#pragma unroll
        for (int h = 0; h < 2; h++) {
#pragma unroll
          for (int i = 12; i < 16; i++) {
            const int r_ = (i - I0) % NA;
            if (h == 0) { mbar_wait(BAR(B_FWO + i), 0); mbar_wait(BAR(B_VAL + r_), ((i - I0) / NA) & 1); }
            const uint32_t da = dO + ((A_SLOTS >> (4 * r_)) & 15u) * 1024, db = dW + ((uint32_t)(WO_SLOTS >> (4 * i)) & 15u) * 1024 + h * 256;
            if (h == 0 || i == 12) wg_fence();
#pragma unroll
            for (int kk = 0; kk < 4; kk++) {
              const uint64_t a = mkdesc(da + (kk >> 1) * 512 + (kk & 1) * 2, HI_SW64), bb = mkdesc(db + (kk >> 1) * 512 + (kk & 1) * 128, HI_SW128);
              if (i == 12 && kk == 0) wgmma_sz_n64<0, 1>(h ? bh : bl, a, bb); else wgmma_ss_n64<0, 1>(h ? bh : bl, a, bb);
            }
          }
          wg_commit();
        }
        wg_wait<1>();
        reg_fence(ao); reg_fence(bl);
#pragma unroll
        for (int j = 0; j < 32; j++) bl[j] += ao[j];
        out_half(0, bl);
        wg_wait<0>();
        reg_fence(bh);
#pragma unroll
        for (int j = 0; j < 32; j++) bh[j] += ao[32 + j];
        out_half(1, bh);
        done = true;
      } else
#pragma unroll
      for (int i = 12; i < 16; i++) {
        if (i == 16 - STAG && w == 1) mbar_wait(BAR(B_GO), 0);
        step(i, (i - I0) % NA, ((i - I0) / NA) & 1, (A_SLOTS >> (4 * ((i - I0) % NA))) & 15u, (uint32_t)(WO_SLOTS >> (4 * i)) & 15u);
        if (STAG && i == 15 - GOE && tid == 0) mbar_arrive(BAR(B_GO));
      }
    }
    if (!done) {
      routed();
      wg_wait<0>();
      reg_fence(ao);
      TLS(0, 10);
      out_half(0, ao);
      out_half(1, ao + 32);
    }
    TLS(0, 11);
    TLS(128, 9);
  }
}

typedef CUresult (*EncFn)(CUtensorMap*, CUtensorMapDataType, cuuint32_t, void*, const cuuint64_t*, const cuuint64_t*, const cuuint32_t*,
                          const cuuint32_t*, CUtensorMapInterleave, CUtensorMapSwizzle, CUtensorMapL2promotion, CUtensorMapFloatOOBfill);

void make_map2(EncFn enc, CUtensorMap* m, void* p, uint64_t rows, uint64_t cols, uint32_t brows, CUtensorMapL2promotion promo) {
  cuuint64_t gd[2] = {cols, rows}, gs[1] = {cols * 2};
  cuuint32_t bd[2] = {64, brows}, es[2] = {1, 1};
  enc(m, CU_TENSOR_MAP_DATA_TYPE_BFLOAT16, 2, p, gd, gs, bd, es, CU_TENSOR_MAP_INTERLEAVE_NONE, CU_TENSOR_MAP_SWIZZLE_128B, promo,
      CU_TENSOR_MAP_FLOAT_OOB_FILL_NONE);
}
void make_map3(EncFn enc, CUtensorMap* m, void* p, uint64_t rows, uint64_t cols, uint32_t brows) {
  cuuint64_t gd[3] = {64, rows, cols / 64}, gs[2] = {cols * 2, 128};
  cuuint32_t bd[3] = {64, brows, 2}, es[3] = {1, 1, 1};
  enc(m, CU_TENSOR_MAP_DATA_TYPE_BFLOAT16, 3, p, gd, gs, bd, es, CU_TENSOR_MAP_INTERLEAVE_NONE, CU_TENSOR_MAP_SWIZZLE_128B,
      CU_TENSOR_MAP_L2_PROMOTION_L2_256B, CU_TENSOR_MAP_FLOAT_OOB_FILL_NONE);
}

}

extern "C" void kernel_launch(void* const* d_in, const int* in_sizes, int n_in, void* d_out, int out_size) {
  static EncFn enc = nullptr;
  static int by_sm = 0;
  if (!enc) {
    void* fn = nullptr;
    cudaDriverEntryPointQueryResult qr;
    cudaGetDriverEntryPoint("cuTensorMapEncodeTiled", &fn, cudaEnableDefault, &qr);
    enc = (EncFn)fn;
    int dev = 0, sms = 0;
    cudaGetDevice(&dev);
    cudaDeviceGetAttribute(&sms, cudaDevAttrMultiProcessorCount, dev);
    by_sm = MAP == 2 && sms == NCTA + NSVC;
    cudaFuncSetAttribute(fused_kernel, cudaFuncAttributeMaxDynamicSharedMemorySize, SMEM_BYTES);
  }
  CUtensorMap tmX, tmW, tmWo, tmOut, tmG, tmU, tmD, tmR, tmWp;
  {
    cuuint64_t gd[5] = {64, 2, 128, 4, 16}, gs[4] = {2048, 16384, 4096, 128};
    cuuint32_t bd[5] = {64, 2, 4, 4, 2}, es[5] = {1, 1, 1, 1, 1};
    enc(&tmWp, CU_TENSOR_MAP_DATA_TYPE_BFLOAT16, 5, d_in[2], gd, gs, bd, es, CU_TENSOR_MAP_INTERLEAVE_NONE, CU_TENSOR_MAP_SWIZZLE_128B,
        CU_TENSOR_MAP_L2_PROMOTION_L2_256B, CU_TENSOR_MAP_FLOAT_OOB_FILL_NONE);
  }
  make_map2(enc, &tmR, d_in[0], SEQ, DM, 1, CU_TENSOR_MAP_L2_PROMOTION_L2_128B);
  make_map2(enc, &tmX, d_in[0], SEQ, DM, 128, XPROMO);
  make_map3(enc, &tmW, d_in[1], DM, 3 * DM, 64);
  make_map3(enc, &tmWo, d_in[2], DM, DM, 32);
  if (OUTV) make_map2(enc, &tmOut, d_out, SEQ, DM, 16, CU_TENSOR_MAP_L2_PROMOTION_L2_128B); else make_map3(enc, &tmOut, d_out, SEQ, DM, 64);
  make_map2(enc, &tmG, d_in[5], DM, FF, 64, MPROMO);
  make_map2(enc, &tmU, d_in[6], DM, FF, 64, MPROMO);
  make_map2(enc, &tmD, d_in[7], FF, DM, 64, MPROMO);
  typedef const __nv_bfloat16* P;
  cudaLaunchConfig_t cfg = {};
  cfg.gridDim = dim3(NCTA + NSVC); cfg.blockDim = dim3(512); cfg.dynamicSmemBytes = SMEM_BYTES; cfg.stream = cudaStreamPerThread;
  cudaLaunchAttribute at[1];
  at[0].id = cudaLaunchAttributeClusterDimension;
  at[0].val.clusterDim.x = 2; at[0].val.clusterDim.y = 1; at[0].val.clusterDim.z = 1;
  cfg.attrs = at; cfg.numAttrs = 1;
  cudaLaunchKernelEx(&cfg, fused_kernel, (P)d_in[0], (P)d_in[1], (P)d_in[2], (P)d_in[4], (P)d_in[7], (__nv_bfloat16*)d_out, by_sm, tmX, tmW, tmWo, tmOut, tmG, tmU, tmD, tmR, tmWp);
}
```

```cpp
#include <cuda_runtime.h>
#include <cuda.h>
#include <cuda_bf16.h>
#include <stdint.h>

#define WK 0
#define OEF 0
namespace {

template <int TA, int TB> __device__ __forceinline__ void wgmma_ss_n128(float (&d)[64], uint64_t da, uint64_t db) {
  asm volatile("wgmma.mma_async.sync.aligned.m64n128k16.f32.bf16.bf16 "
  "{%0,%1,%2,%3,%4,%5,%6,%7,%8,%9,%10,%11,%12,%13,%14,%15,%16,%17,%18,%19,%20,%21,%22,%23,%24,%25,%26,%27,%28,%29,%30,%31,%32,%33,%34,%35,%36,%37,%38,%39,%40,%41,%42,%43,%44,%45,%46,%47,%48,%49,%50,%51,%52,%53,%54,%55,%56,%57,%58,%59,%60,%61,%62,%63}, "
  "%64, %65, 1, 1, 1, %66, %67;"
  : "+f"(d[0]),"+f"(d[1]),"+f"(d[2]),"+f"(d[3]),"+f"(d[4]),"+f"(d[5]),"+f"(d[6]),"+f"(d[7]),"+f"(d[8]),"+f"(d[9]),"+f"(d[10]),"+f"(d[11]),"+f"(d[12]),"+f"(d[13]),"+f"(d[14]),"+f"(d[15]),"+f"(d[16]),"+f"(d[17]),"+f"(d[18]),"+f"(d[19]),"+f"(d[20]),"+f"(d[21]),"+f"(d[22]),"+f"(d[23]),"+f"(d[24]),"+f"(d[25]),"+f"(d[26]),"+f"(d[27]),"+f"(d[28]),"+f"(d[29]),"+f"(d[30]),"+f"(d[31]),"+f"(d[32]),"+f"(d[33]),"+f"(d[34]),"+f"(d[35]),"+f"(d[36]),"+f"(d[37]),"+f"(d[38]),"+f"(d[39]),"+f"(d[40]),"+f"(d[41]),"+f"(d[42]),"+f"(d[43]),"+f"(d[44]),"+f"(d[45]),"+f"(d[46]),"+f"(d[47]),"+f"(d[48]),"+f"(d[49]),"+f"(d[50]),"+f"(d[51]),"+f"(d[52]),"+f"(d[53]),"+f"(d[54]),"+f"(d[55]),"+f"(d[56]),"+f"(d[57]),"+f"(d[58]),"+f"(d[59]),"+f"(d[60]),"+f"(d[61]),"+f"(d[62]),"+f"(d[63])
  : "l"(da), "l"(db), "n"(TA), "n"(TB));
}
template <int TA, int TB> __device__ __forceinline__ void wgmma_ss_n64(float (&d)[32], uint64_t da, uint64_t db) {
  asm volatile("wgmma.mma_async.sync.aligned.m64n64k16.f32.bf16.bf16 "
  "{%0,%1,%2,%3,%4,%5,%6,%7,%8,%9,%10,%11,%12,%13,%14,%15,%16,%17,%18,%19,%20,%21,%22,%23,%24,%25,%26,%27,%28,%29,%30,%31}, "
  "%32, %33, 1, 1, 1, %34, %35;"
  : "+f"(d[0]),"+f"(d[1]),"+f"(d[2]),"+f"(d[3]),"+f"(d[4]),"+f"(d[5]),"+f"(d[6]),"+f"(d[7]),"+f"(d[8]),"+f"(d[9]),"+f"(d[10]),"+f"(d[11]),"+f"(d[12]),"+f"(d[13]),"+f"(d[14]),"+f"(d[15]),"+f"(d[16]),"+f"(d[17]),"+f"(d[18]),"+f"(d[19]),"+f"(d[20]),"+f"(d[21]),"+f"(d[22]),"+f"(d[23]),"+f"(d[24]),"+f"(d[25]),"+f"(d[26]),"+f"(d[27]),"+f"(d[28]),"+f"(d[29]),"+f"(d[30]),"+f"(d[31])
  : "l"(da), "l"(db), "n"(TA), "n"(TB));
}
template <int TA, int TB> __device__ __forceinline__ void wgmma_sz_n64(float (&d)[32], uint64_t da, uint64_t db) {
  asm volatile("wgmma.mma_async.sync.aligned.m64n64k16.f32.bf16.bf16 "
  "{%0,%1,%2,%3,%4,%5,%6,%7,%8,%9,%10,%11,%12,%13,%14,%15,%16,%17,%18,%19,%20,%21,%22,%23,%24,%25,%26,%27,%28,%29,%30,%31}, "
  "%32, %33, 0, 1, 1, %34, %35;"
  : "=f"(d[0]),"=f"(d[1]),"=f"(d[2]),"=f"(d[3]),"=f"(d[4]),"=f"(d[5]),"=f"(d[6]),"=f"(d[7]),"=f"(d[8]),"=f"(d[9]),"=f"(d[10]),"=f"(d[11]),"=f"(d[12]),"=f"(d[13]),"=f"(d[14]),"=f"(d[15]),"=f"(d[16]),"=f"(d[17]),"=f"(d[18]),"=f"(d[19]),"=f"(d[20]),"=f"(d[21]),"=f"(d[22]),"=f"(d[23]),"=f"(d[24]),"=f"(d[25]),"=f"(d[26]),"=f"(d[27]),"=f"(d[28]),"=f"(d[29]),"=f"(d[30]),"=f"(d[31])
  : "l"(da), "l"(db), "n"(TA), "n"(TB));
}
template <int TB> __device__ __forceinline__ void wgmma_rs_n72(float (&d)[36], uint32_t a0, uint32_t a1, uint32_t a2, uint32_t a3, uint64_t db) {
  asm volatile("wgmma.mma_async.sync.aligned.m64n72k16.f32.bf16.bf16 "
  "{%0,%1,%2,%3,%4,%5,%6,%7,%8,%9,%10,%11,%12,%13,%14,%15,%16,%17,%18,%19,%20,%21,%22,%23,%24,%25,%26,%27,%28,%29,%30,%31,%32,%33,%34,%35}, "
  "{%36,%37,%38,%39}, %40, 1, 1, 1, %41;"
  : "+f"(d[0]),"+f"(d[1]),"+f"(d[2]),"+f"(d[3]),"+f"(d[4]),"+f"(d[5]),"+f"(d[6]),"+f"(d[7]),"+f"(d[8]),"+f"(d[9]),"+f"(d[10]),"+f"(d[11]),"+f"(d[12]),"+f"(d[13]),"+f"(d[14]),"+f"(d[15]),"+f"(d[16]),"+f"(d[17]),"+f"(d[18]),"+f"(d[19]),"+f"(d[20]),"+f"(d[21]),"+f"(d[22]),"+f"(d[23]),"+f"(d[24]),"+f"(d[25]),"+f"(d[26]),"+f"(d[27]),"+f"(d[28]),"+f"(d[29]),"+f"(d[30]),"+f"(d[31]),"+f"(d[32]),"+f"(d[33]),"+f"(d[34]),"+f"(d[35])
  : "r"(a0), "r"(a1), "r"(a2), "r"(a3), "l"(db), "n"(TB));
}
template <int TB> __device__ __forceinline__ void wgmma_rz_n72(float (&d)[36], uint32_t a0, uint32_t a1, uint32_t a2, uint32_t a3, uint64_t db) {
  asm volatile("wgmma.mma_async.sync.aligned.m64n72k16.f32.bf16.bf16 "
  "{%0,%1,%2,%3,%4,%5,%6,%7,%8,%9,%10,%11,%12,%13,%14,%15,%16,%17,%18,%19,%20,%21,%22,%23,%24,%25,%26,%27,%28,%29,%30,%31,%32,%33,%34,%35}, "
  "{%36,%37,%38,%39}, %40, 0, 1, 1, %41;"
  : "=f"(d[0]),"=f"(d[1]),"=f"(d[2]),"=f"(d[3]),"=f"(d[4]),"=f"(d[5]),"=f"(d[6]),"=f"(d[7]),"=f"(d[8]),"=f"(d[9]),"=f"(d[10]),"=f"(d[11]),"=f"(d[12]),"=f"(d[13]),"=f"(d[14]),"=f"(d[15]),"=f"(d[16]),"=f"(d[17]),"=f"(d[18]),"=f"(d[19]),"=f"(d[20]),"=f"(d[21]),"=f"(d[22]),"=f"(d[23]),"=f"(d[24]),"=f"(d[25]),"=f"(d[26]),"=f"(d[27]),"=f"(d[28]),"=f"(d[29]),"=f"(d[30]),"=f"(d[31]),"=f"(d[32]),"=f"(d[33]),"=f"(d[34]),"=f"(d[35])
  : "r"(a0), "r"(a1), "r"(a2), "r"(a3), "l"(db), "n"(TB));
}
template <int TB> __device__ __forceinline__ void wgmma_rs_n40(float (&d)[20], uint32_t a0, uint32_t a1, uint32_t a2, uint32_t a3, uint64_t db) {
  asm volatile("wgmma.mma_async.sync.aligned.m64n40k16.f32.bf16.bf16 "
  "{%0,%1,%2,%3,%4,%5,%6,%7,%8,%9,%10,%11,%12,%13,%14,%15,%16,%17,%18,%19}, "
  "{%20,%21,%22,%23}, %24, 1, 1, 1, %25;"
  : "+f"(d[0]),"+f"(d[1]),"+f"(d[2]),"+f"(d[3]),"+f"(d[4]),"+f"(d[5]),"+f"(d[6]),"+f"(d[7]),"+f"(d[8]),"+f"(d[9]),"+f"(d[10]),"+f"(d[11]),"+f"(d[12]),"+f"(d[13]),"+f"(d[14]),"+f"(d[15]),"+f"(d[16]),"+f"(d[17]),"+f"(d[18]),"+f"(d[19])
  : "r"(a0), "r"(a1), "r"(a2), "r"(a3), "l"(db), "n"(TB));
}
template <int TB> __device__ __forceinline__ void wgmma_rz_n40(float (&d)[20], uint32_t a0, uint32_t a1, uint32_t a2, uint32_t a3, uint64_t db) {
  asm volatile("wgmma.mma_async.sync.aligned.m64n40k16.f32.bf16.bf16 "
  "{%0,%1,%2,%3,%4,%5,%6,%7,%8,%9,%10,%11,%12,%13,%14,%15,%16,%17,%18,%19}, "
  "{%20,%21,%22,%23}, %24, 0, 1, 1, %25;"
  : "=f"(d[0]),"=f"(d[1]),"=f"(d[2]),"=f"(d[3]),"=f"(d[4]),"=f"(d[5]),"=f"(d[6]),"=f"(d[7]),"=f"(d[8]),"=f"(d[9]),"=f"(d[10]),"=f"(d[11]),"=f"(d[12]),"=f"(d[13]),"=f"(d[14]),"=f"(d[15]),"=f"(d[16]),"=f"(d[17]),"=f"(d[18]),"=f"(d[19])
  : "r"(a0), "r"(a1), "r"(a2), "r"(a3), "l"(db), "n"(TB));
}
template <int TB> __device__ __forceinline__ void wgmma_rs_n128(float (&d)[64], uint32_t a0, uint32_t a1, uint32_t a2, uint32_t a3, uint64_t db) {
  asm volatile("wgmma.mma_async.sync.aligned.m64n128k16.f32.bf16.bf16 "
  "{%0,%1,%2,%3,%4,%5,%6,%7,%8,%9,%10,%11,%12,%13,%14,%15,%16,%17,%18,%19,%20,%21,%22,%23,%24,%25,%26,%27,%28,%29,%30,%31,%32,%33,%34,%35,%36,%37,%38,%39,%40,%41,%42,%43,%44,%45,%46,%47,%48,%49,%50,%51,%52,%53,%54,%55,%56,%57,%58,%59,%60,%61,%62,%63}, "
  "{%64,%65,%66,%67}, %68, 1, 1, 1, %69;"
  : "+f"(d[0]),"+f"(d[1]),"+f"(d[2]),"+f"(d[3]),"+f"(d[4]),"+f"(d[5]),"+f"(d[6]),"+f"(d[7]),"+f"(d[8]),"+f"(d[9]),"+f"(d[10]),"+f"(d[11]),"+f"(d[12]),"+f"(d[13]),"+f"(d[14]),"+f"(d[15]),"+f"(d[16]),"+f"(d[17]),"+f"(d[18]),"+f"(d[19]),"+f"(d[20]),"+f"(d[21]),"+f"(d[22]),"+f"(d[23]),"+f"(d[24]),"+f"(d[25]),"+f"(d[26]),"+f"(d[27]),"+f"(d[28]),"+f"(d[29]),"+f"(d[30]),"+f"(d[31]),"+f"(d[32]),"+f"(d[33]),"+f"(d[34]),"+f"(d[35]),"+f"(d[36]),"+f"(d[37]),"+f"(d[38]),"+f"(d[39]),"+f"(d[40]),"+f"(d[41]),"+f"(d[42]),"+f"(d[43]),"+f"(d[44]),"+f"(d[45]),"+f"(d[46]),"+f"(d[47]),"+f"(d[48]),"+f"(d[49]),"+f"(d[50]),"+f"(d[51]),"+f"(d[52]),"+f"(d[53]),"+f"(d[54]),"+f"(d[55]),"+f"(d[56]),"+f"(d[57]),"+f"(d[58]),"+f"(d[59]),"+f"(d[60]),"+f"(d[61]),"+f"(d[62]),"+f"(d[63])
  : "r"(a0), "r"(a1), "r"(a2), "r"(a3), "l"(db), "n"(TB));
}
template <int TA, int TB> __device__ __forceinline__ void wgmma_ss_n8(float (&d)[4], uint64_t da, uint64_t db) {
  asm volatile("wgmma.mma_async.sync.aligned.m64n8k16.f32.bf16.bf16 "
  "{%0,%1,%2,%3}, "
  "%4, %5, 1, 1, 1, %6, %7;"
  : "+f"(d[0]),"+f"(d[1]),"+f"(d[2]),"+f"(d[3])
  : "l"(da), "l"(db), "n"(TA), "n"(TB));
}
template <int TA, int TB> __device__ __forceinline__ void wgmma_ss_n16(float (&d)[8], uint64_t da, uint64_t db) {
  asm volatile("wgmma.mma_async.sync.aligned.m64n16k16.f32.bf16.bf16 "
  "{%0,%1,%2,%3,%4,%5,%6,%7}, "
  "%8, %9, 1, 1, 1, %10, %11;"
  : "+f"(d[0]),"+f"(d[1]),"+f"(d[2]),"+f"(d[3]),"+f"(d[4]),"+f"(d[5]),"+f"(d[6]),"+f"(d[7])
  : "l"(da), "l"(db), "n"(TA), "n"(TB));
}

constexpr int SEQ = 2048, DM = 1024, FF = 3584;
constexpr int NCTA = 128, NSVC = 4;
constexpr int NUNIT = 112;
constexpr uint32_t SLOT = 16384;
constexpr uint32_t MISC = 14 * SLOT;
constexpr uint32_t SMEM_BYTES = MISC + 3072;
constexpr uint32_t M_MOE = 0;
constexpr uint32_t M_BAR = 2048;
constexpr uint32_t M_DUM = 2048 + 1020;
constexpr uint32_t M_IDX = 2048 + 768;
constexpr uint32_t M_KEY = 2048 + 960;
#define R5 1
#define NQ (R5 ? 6 : 5)
constexpr int NF = 16 - NQ, NR = (NQ == 5 || R5) ? 4 : 3;
constexpr int B_FXQ = 0, B_FKV = 3, B_AST = 6, B_MOE = 7, B_MF = 8  , B_CQ = 12, B_XS = 13, B_DF = 14, B_ZOK = 15, B_FWO = 21  , B_FQ = B_FWO - NQ,
              B_UP = 37, B_FIN = 38, B_KVB = 39, B_ME = 40  , B_HF = 44, B_AF = 45  , B_AR = 50  , B_GO = 52,
              B_FAUX = 53, B_EAUX = 54, B_T0 = 55, B_DE = 56, B_EA = 57  , B_VAL = 62  ,
              B_E = 67  , B_STG = 70, B_EQ = 71  , B_EO = 76  , NBAR = 83, B_KV4 = 83, B_MS = 84,
              B_FV = 85  , B_EK = 88  , B_GQ = 91, B_GT = 92;
constexpr uint32_t MT = 9216, A_ONES = 12 * SLOT + 3 * MT, A_CS = A_ONES + 2048, A_ST = A_CS + 1536;
constexpr uint32_t A_TL = MISC + 2048 + 808;
constexpr int S_V0 = R5 ? 7 : 11, S_V1 = R5 ? 9 : 7;
constexpr uint32_t K_SLOTS = 0x8697A8u, V_SLOTS = 0x97A869u;
constexpr int C_B = 0, C_DONE = 32, NCNT = 2;
constexpr uint32_t QX_SLOTS = NQ == 5 ? 0x43102u : 0x354021u;
constexpr uint32_t QW_SLOTS = R5 ? 0xA9786Au : 0xB76A98u;
constexpr uint32_t qx(int k) { return (QX_SLOTS >> (4 * k)) & 15u; }
constexpr uint32_t qw(int k) { return (QW_SLOTS >> (4 * k)) & 15u; }
constexpr uint32_t S_KVB = R5 ? 1 : 8, S_D0 = R5 ? 11 : (NQ == 5 ? 5 : 1), S_D1 = R5 ? 2 : (NQ == 5 ? 11 : 2);
constexpr uint32_t S_M3 = R5 ? 11 : 5;
constexpr int WQ0 = NQ == 5 ? 1 : 3;
constexpr uint32_t wo_slot_c(int i) { return i >= 9 ? wo_slot_c(i - 9) : (i == 7 ? S_D0 : (i == 8 ? S_D1 : (((i & 1) || i + WQ0 == 1) ? qx((i + WQ0) >> 1) : qw((i + WQ0) >> 1)))); }
constexpr uint64_t wo_slots() { uint64_t t = 0; for (int i = 0; i < 16; i++) t |= (uint64_t)wo_slot_c(i) << (4 * i); return t; }
constexpr uint64_t WO_SLOTS = wo_slots();
constexpr uint32_t A_SLOTS = 0xDC000u | (S_KVB << 8) | (qw(NQ - 1) << 4) | qx(NQ - 1);
constexpr uint32_t SX14 = qx(NQ - 2), SX15 = qx(NQ - 1), SXQ0 = qx(0);
#define WOD 2
#define PLC 3
#define RS0 0
#define POLLNS 150
#define MPROMO CU_TENSOR_MAP_L2_PROMOTION_L2_128B
#define MW0 0
#define PFILL 0
#define H2W (NQ - 3)
#define SV0 2
#define SV0A 14
#define SV0B 22
#define ASTE 2
#define PFS 1
#define PFTAB 0x0012222220000ull
#define HW 0
#define DPF 1
#define PROBE 0x8
#define OS1 0
#define YW 0
#define NOVAL 0
#define NDIR 1
#define I0 (2 + NDIR)
#define DW 0
#define NA 5
#define STAG 4
#define GOE 0
#define KEY1 0
#define HYB 0
#define FW 0
#define E1E 1
#define GATE 0
#define SVD 0
#define XPROMO CU_TENSOR_MAP_L2_PROMOTION_L2_128B
#define MC0 3
#define MX 0
#define OUTV 1
#define NP 0
#define FINCP 0
#define DNS 0
#define WOK 99
#define WOD1 2
#define MRED 1
#define MRW -1
#define ST 0
#define RW 0
#define SL2 0
#define CQ4 0
#define VOL 0
#define FMC 0
#define KO 0
#define KS 7
#define SQ 2
#define H2D 200
#define MRC 0
#define H2C 0
#define MRD 300
#define STP 0
#define TPNS 50
#define MFIN 0
#define MFD 300
#define SF 1
#define PH MFIN
#define RSL 0
#define OS3 4
#define PLP 2
#define PFNS2 200
#define MAP 2
#define RSNS 60
#define SVS 6
#define MC 7
#define QE 0
#define TMP 1
#define TMPW 4
#define DS 15
#define RL 0
#define EV 0
#define LQ 0
#define SPL 0
#define PHI2 1
#define E7 1
#define RF 1
#define RK 0
#define LE 1
#define SL7 0
#define XP 3
#define MS 0
constexpr int CON_REGS = 224, MOE_REGS = 40, PROD_REGS = 24;
constexpr uint32_t SPIN_MAX = 2000000;
constexpr uint32_t SENT = 0xFFFFFFFFu;

struct __align__(128) Scratch {
  uint4 o[NCTA * 2048];
  uint4 part[NCTA * 544];
  uint4 fin[8 * 640];
  float2 stats[SEQ];
  uint32_t key[SEQ];
  uint32_t cs[3 * DM];
  uint4 y[NCTA * 128];
  uint32_t h[56 * 256];
  uint32_t top[128];
  uint32_t cnt[NCNT * 32];
};
__device__ Scratch G;
#define TLS(th, i)
#define TLP_(i)
#define TLG(i)
#define TLDUMP()

__device__ __forceinline__ bool elect_one() {
  uint32_t p;
  asm volatile("{\n.reg .pred P;\nelect.sync _|P, 0xffffffff;\nselp.b32 %0, 1, 0, P;\n}" : "=r"(p));
  return p;
}
__device__ __forceinline__ void mbar_init(uint32_t b, uint32_t c) { asm volatile("mbarrier.init.shared::cta.b64 [%0], %1;" ::"r"(b), "r"(c) : "memory"); }
__device__ __forceinline__ void mbar_expect_tx(uint32_t b, uint32_t bytes) { asm volatile("mbarrier.arrive.expect_tx.shared::cta.b64 _, [%0], %1;" ::"r"(b), "r"(bytes) : "memory"); }
__device__ __forceinline__ void mbar_arrive(uint32_t b) { asm volatile("mbarrier.arrive.shared::cta.b64 _, [%0];" ::"r"(b) : "memory"); }
__device__ __forceinline__ void mbar_wait_b(uint32_t b, uint32_t parity) {
  asm volatile(
      "{\n.reg .pred p;\n.reg .u32 cnt;\nmov.u32 cnt, 0;\n"
      "LW:\nmbarrier.try_wait.parity.shared::cta.b64 p, [%0], %1;\n@p bra LD;\n"
      "add.u32 cnt, cnt, 1;\nsetp.lt.u32 p, cnt, 4000000;\n@p bra LW;\ntrap;\nLD:\n}" ::"r"(b), "r"(parity) : "memory");
}
__device__ __forceinline__ void mbar_wait(uint32_t b, uint32_t parity) {
  asm volatile("{\n.reg .pred p;\nLW:\nmbarrier.try_wait.parity.shared::cta.b64 p, [%0], %1;\n@!p bra LW;\n}" ::"r"(b), "r"(parity) : "memory");
}
__device__ __forceinline__ bool mbar_test(uint32_t b, uint32_t parity) {
  uint32_t r;
  asm volatile("{\n.reg .pred p;\nmbarrier.test_wait.parity.shared::cta.b64 p, [%1], %2;\nselp.b32 %0, 1, 0, p;\n}" : "=r"(r) : "r"(b), "r"(parity) : "memory");
  return r;
}
__device__ __forceinline__ uint32_t ev_arrive(uint32_t a) { uint32_t r; asm volatile("atom.shared.add.u32 %0, [%1], 1;" : "=r"(r) : "r"(a) : "memory"); return r; }
__device__ __forceinline__ void tma2d(uint32_t dst, const CUtensorMap* m, int c0, int c1, uint32_t bar) {
  asm volatile("cp.async.bulk.tensor.2d.shared::cluster.global.mbarrier::complete_tx::bytes [%0], [%1, {%3, %4}], [%2];" ::"r"(dst), "l"(m), "r"(bar), "r"(c0), "r"(c1) : "memory");
}
__device__ __forceinline__ void tma3d(uint32_t dst, const CUtensorMap* m, int c1, int c2, uint32_t bar) {
  asm volatile("cp.async.bulk.tensor.3d.shared::cluster.global.mbarrier::complete_tx::bytes [%0], [%1, {%3, %4, %5}], [%2];" ::"r"(dst), "l"(m), "r"(bar), "r"(0), "r"(c1), "r"(c2) : "memory");
}
__device__ __forceinline__ void tma3d_mc(uint32_t dst, const CUtensorMap* m, int c1, int c2, uint32_t bar) {
  asm volatile("cp.async.bulk.tensor.3d.shared::cluster.global.mbarrier::complete_tx::bytes.multicast::cluster [%0], [%1, {%3, %4, %5}], [%2], %6;" ::"r"(dst), "l"(m), "r"(bar), "r"(0), "r"(c1), "r"(c2), "h"((uint16_t)3) : "memory");
}
__device__ __forceinline__ void tma5d(uint32_t dst, const CUtensorMap* m, int c2, int c4, uint32_t bar, bool mc) {
  if (mc) asm volatile("cp.async.bulk.tensor.5d.shared::cluster.global.mbarrier::complete_tx::bytes.multicast::cluster [%0], [%1, {%3, %3, %4, %3, %5}], [%2], %6;" ::"r"(dst), "l"(m), "r"(bar), "r"(0), "r"(c2), "r"(c4), "h"((uint16_t)3) : "memory");
  else asm volatile("cp.async.bulk.tensor.5d.shared::cluster.global.mbarrier::complete_tx::bytes [%0], [%1, {%3, %3, %4, %3, %5}], [%2];" ::"r"(dst), "l"(m), "r"(bar), "r"(0), "r"(c2), "r"(c4) : "memory");
}
__device__ __forceinline__ void mbar_arrive_cta(uint32_t b, uint32_t cta) {
  asm volatile("{\n.reg .b32 ra;\nmapa.shared::cluster.u32 ra, %0, %1;\nmbarrier.arrive.shared::cluster.b64 _, [ra];\n}" ::"r"(b), "r"(cta) : "memory");
}
constexpr uint64_t POL_FIRST = 0x12F0000000000000ull;
__device__ __forceinline__ void tma2d_ef(uint32_t dst, const CUtensorMap* m, int c0, int c1, uint32_t bar) {
  asm volatile("cp.async.bulk.tensor.2d.shared::cluster.global.mbarrier::complete_tx::bytes.L2::cache_hint [%0], [%1, {%3, %4}], [%2], %5;" ::"r"(dst), "l"(m), "r"(bar), "r"(c0), "r"(c1), "l"(POL_FIRST) : "memory");
}
__device__ __forceinline__ void bulk_ld(uint32_t dst, const void* src, uint32_t bytes, uint32_t bar) {
  asm volatile("cp.async.bulk.shared::cluster.global.mbarrier::complete_tx::bytes [%0], [%1], %2, [%3];" ::"r"(dst), "l"(src), "r"(bytes), "r"(bar) : "memory");
}
__device__ __forceinline__ void bulk_ld_mc(uint32_t dst, const void* src, uint32_t bytes, uint32_t bar) {
  asm volatile("cp.async.bulk.shared::cluster.global.mbarrier::complete_tx::bytes.multicast::cluster [%0], [%1], %2, [%3], %4;" ::"r"(dst), "l"(src), "r"(bytes), "r"(bar), "h"((uint16_t)3) : "memory");
}
__device__ __forceinline__ void bulk_pf(const void* src, uint32_t bytes) { asm volatile("cp.async.bulk.prefetch.L2.global [%0], %1;" ::"l"(src), "r"(bytes) : "memory"); }
__device__ __forceinline__ void tma2d_pf(const CUtensorMap* m, int c0, int c1) {
  asm volatile("cp.async.bulk.prefetch.tensor.2d.L2.global [%0, {%1, %2}];" ::"l"(m), "r"(c0), "r"(c1) : "memory");
}
__device__ __forceinline__ void map_pf(const CUtensorMap* m) { asm volatile("prefetch.tensormap [%0];" ::"l"(m) : "memory"); }
__device__ __forceinline__ void line_pf(const void* p) { asm volatile("prefetch.global.L2 [%0];" ::"l"(p)); }
__device__ __forceinline__ void pf128(uint32_t dummy, const void* src) { asm volatile("cp.async.ca.shared.global.L2::128B [%0], [%1], 4;" ::"r"(dummy), "l"(src) : "memory"); }
__device__ __forceinline__ void pf256(uint32_t dummy, const void* src) { asm volatile("cp.async.ca.shared.global.L2::256B [%0], [%1], 4;" ::"r"(dummy), "l"(src) : "memory"); }
__device__ __forceinline__ void cp16x2(uint32_t dst, const void* src) {
  asm volatile("cp.async.cg.shared.global [%0], [%1], 16;\ncp.async.cg.shared.global [%0+4096], [%1+512], 16;" ::"r"(dst), "l"(src) : "memory");
}
constexpr uint32_t HI_SW128 = 0x40000000u | (1024 >> 4), HI_SW64 = 0x80000000u | (512 >> 4), HI_NOSW = 512 >> 4;
__device__ __forceinline__ uint64_t mkdesc(uint32_t lo, uint32_t hi) { uint64_t d; asm("mov.b64 %0, {%1, %2};" : "=l"(d) : "r"(lo), "r"(hi)); return d; }
__device__ __forceinline__ void wg_fence() { asm volatile("wgmma.fence.sync.aligned;" ::: "memory"); }
__device__ __forceinline__ void wg_commit() { asm volatile("wgmma.commit_group.sync.aligned;" ::: "memory"); }
template <int N> __device__ __forceinline__ void wg_wait() { asm volatile("wgmma.wait_group.sync.aligned %0;" ::"n"(N) : "memory"); }
template <int N> __device__ __forceinline__ void reg_fence(float (&a)[N]) {
#pragma unroll
  for (int i = 0; i < N; i++) asm volatile("" : "+f"(a[i])::"memory");
}
template <int ID, int N> __device__ __forceinline__ void bar_sync() { asm volatile("bar.sync %0, %1;" ::"n"(ID), "n"(N) : "memory"); }
__device__ __forceinline__ void fence_async_smem() { asm volatile("fence.proxy.async.shared::cta;" ::: "memory"); }
__device__ __forceinline__ void fence_async_gmem() { asm volatile("fence.proxy.async.global;" ::: "memory"); }
__device__ __forceinline__ uint32_t pack_bf16(float lo, float hi) { uint32_t r; asm("cvt.rn.bf16x2.f32 %0, %1, %2;" : "=r"(r) : "f"(hi), "f"(lo)); return r; }
__device__ __forceinline__ float bf_lo(uint32_t v) { return __uint_as_float(v << 16); }
__device__ __forceinline__ float bf_hi(uint32_t v) { return __uint_as_float(v & 0xFFFF0000u); }
__device__ __forceinline__ float bf_round(float v) { return bf_lo(pack_bf16(v, v)); }
__device__ __forceinline__ uint32_t bf_sub2(uint32_t a, uint32_t b) { uint32_t r; asm("sub.rn.bf16x2 %0, %1, %2;" : "=r"(r) : "r"(a), "r"(b)); return r; }
__device__ __forceinline__ float rcp(float v) { float r; asm("rcp.approx.ftz.f32 %0, %1;" : "=f"(r) : "f"(v)); return r; }
__device__ __forceinline__ float ex2(float v) { float r; asm("ex2.approx.ftz.f32 %0, %1;" : "=f"(r) : "f"(v)); return r; }
__device__ __forceinline__ float sigmoid(float v) { return rcp(1.f + ex2(v * -1.4426950408889634f)); }
__device__ __forceinline__ void stsm4(uint32_t a, uint32_t r0, uint32_t r1, uint32_t r2, uint32_t r3) {
  asm volatile("stmatrix.sync.aligned.m8n8.x4.shared.b16 [%0], {%1,%2,%3,%4};" ::"r"(a), "r"(r0), "r"(r1), "r"(r2), "r"(r3) : "memory");
}
__device__ __forceinline__ void stsm4t(uint32_t a, uint32_t r0, uint32_t r1, uint32_t r2, uint32_t r3) {
  asm volatile("stmatrix.sync.aligned.m8n8.x4.trans.shared.b16 [%0], {%1,%2,%3,%4};" ::"r"(a), "r"(r0), "r"(r1), "r"(r2), "r"(r3) : "memory");
}
__device__ __forceinline__ void ldsm4(uint32_t a, uint32_t& r0, uint32_t& r1, uint32_t& r2, uint32_t& r3) {
  asm volatile("ldmatrix.sync.aligned.m8n8.x4.shared.b16 {%0,%1,%2,%3}, [%4];" : "=r"(r0), "=r"(r1), "=r"(r2), "=r"(r3) : "r"(a) : "memory");
}
__device__ __forceinline__ uint32_t movmat(uint32_t a) { uint32_t d; asm volatile("movmatrix.sync.aligned.m8n8.trans.b16 %0, %1;" : "=r"(d) : "r"(a)); return d; }
__device__ __forceinline__ void sts_h(uint32_t a, float v) { asm volatile("st.shared.u16 [%0], %1;" ::"r"(a), "h"((uint16_t)pack_bf16(v, v)) : "memory"); }
__device__ __forceinline__ float2 lds_f2(uint32_t a) { float2 v; asm volatile("ld.shared.v2.f32 {%0,%1}, [%2];" : "=f"(v.x), "=f"(v.y) : "r"(a)); return v; }
__device__ __forceinline__ float lds_f(uint32_t a) { float v; asm volatile("ld.shared.f32 %0, [%1];" : "=f"(v) : "r"(a)); return v; }
__device__ __forceinline__ float4 lds_f4(uint32_t a) { float4 v; asm volatile("ld.shared.v4.f32 {%0,%1,%2,%3}, [%4];" : "=f"(v.x), "=f"(v.y), "=f"(v.z), "=f"(v.w) : "r"(a)); return v; }
__device__ __forceinline__ uint32_t lds_u(uint32_t a) { uint32_t v; asm volatile("ld.shared.u32 %0, [%1];" : "=r"(v) : "r"(a) : "memory"); return v; }
__device__ __forceinline__ uint4 lds_u4(uint32_t a) { uint4 v; asm volatile("ld.shared.v4.u32 {%0,%1,%2,%3}, [%4];" : "=r"(v.x), "=r"(v.y), "=r"(v.z), "=r"(v.w) : "r"(a) : "memory"); return v; }
__device__ __forceinline__ void sts_u(uint32_t a, uint32_t v) { asm volatile("st.shared.u32 [%0], %1;" ::"r"(a), "r"(v) : "memory"); }
__device__ __forceinline__ void sts_u4(uint32_t a, uint4 v) { asm volatile("st.shared.v4.u32 [%0], {%1,%2,%3,%4};" ::"r"(a), "r"(v.x), "r"(v.y), "r"(v.z), "r"(v.w) : "memory"); }
__device__ __forceinline__ uint4 ldx4(const void* p) { uint4 v; asm volatile("ld.relaxed.gpu.global.v4.u32 {%0,%1,%2,%3}, [%4];" : "=r"(v.x), "=r"(v.y), "=r"(v.z), "=r"(v.w) : "l"(p) : "memory"); return v; }
__device__ __forceinline__ uint2 ldx2(const void* p) { uint2 v; asm volatile("ld.relaxed.gpu.global.v2.u32 {%0,%1}, [%2];" : "=r"(v.x), "=r"(v.y) : "l"(p) : "memory"); return v; }
__device__ __forceinline__ uint32_t ldx1(const void* p) { uint32_t v; asm volatile("ld.relaxed.gpu.global.u32 %0, [%1];" : "=r"(v) : "l"(p) : "memory"); return v; }
__device__ __forceinline__ void stx4(void* p, uint32_t a, uint32_t b, uint32_t c, uint32_t d) {
  asm volatile("st.relaxed.gpu.global.v4.u32 [%0], {%1,%2,%3,%4};" ::"l"(p), "r"(a), "r"(b), "r"(c), "r"(d) : "memory");
}
__device__ __forceinline__ void stx2(void* p, uint32_t a, uint32_t b) { asm volatile("st.relaxed.gpu.global.v2.u32 [%0], {%1,%2};" ::"l"(p), "r"(a), "r"(b) : "memory"); }
__device__ __forceinline__ void stx1(void* p, uint32_t a) { asm volatile("st.relaxed.gpu.global.u32 [%0], %1;" ::"l"(p), "r"(a) : "memory"); }
__device__ __forceinline__ uint32_t umax4(uint4 v) { return max(max(v.x, v.y), max(v.z, v.w)); }
__device__ __forceinline__ uint32_t f2x(float f) { return min(__float_as_uint(f), 0xFFFFFFFEu); }
__device__ __forceinline__ void red4(float* p, float a, float b, float c, float d) { asm volatile("red.relaxed.gpu.global.add.v4.f32 [%0], {%1,%2,%3,%4};" ::"l"(p), "f"(a), "f"(b), "f"(c), "f"(d) : "memory"); }
__device__ __forceinline__ void cnt_arrive(int c) { asm volatile("red.release.gpu.global.add.u32 [%0], 1;" ::"l"(&G.cnt[c]) : "memory"); }
__device__ __forceinline__ void cnt_wait(int c, uint32_t target) {
#pragma unroll 1
  for (uint32_t it = 0; it < SPIN_MAX; it++) {
    uint32_t v;
    asm volatile("ld.acquire.gpu.global.u32 %0, [%1];" : "=r"(v) : "l"(&G.cnt[c]) : "memory");
    if (v >= target) break;
    __nanosleep(POLLNS);
  }
}
__device__ __forceinline__ void spin_cycles(uint32_t n) {
  uint32_t t0, t1;
  asm volatile("mov.u32 %0, %%clock;" : "=r"(t0));
#pragma unroll 1
  do { __nanosleep(20); asm volatile("mov.u32 %0, %%clock;" : "=r"(t1)); } while (t1 - t0 < n);
}
__device__ __forceinline__ void cnt_done() {
  uint32_t t;
  asm volatile("atom.acq_rel.gpu.global.add.u32 %0, [%1], 1;" : "=r"(t) : "l"(&G.cnt[C_DONE]) : "memory");
  if (t == NCTA + NSVC - 1) {
#pragma unroll 1
    for (int i = 0; i < NCNT; i++) G.cnt[i * 32] = 0;
  }
}
__device__ __forceinline__ float phi(float u, float rs, float rl) {
  float a = fmaf(u, rs, 1.000001f), e = ex2(u * rl), r;
  asm("add.sat.f32 %0, %1, 0f358637BD;" : "=f"(e) : "f"(e));
  asm("max.NaN.f32 %0, %1, %2;" : "=f"(r) : "f"(a), "f"(e));
  return r;
}

constexpr float LOG2E = 1.4426950408889634f, LN2 = 0.6931471805599453f;
__device__ __forceinline__ uint32_t phi2l(float u0, float rl0, float u1, float rl1) {
  const float l0 = u0 * rl0, l1 = u1 * rl1;
  float e0, e1;
  asm("{\n.reg .f32 t;\nabs.f32 t, %1;\nneg.f32 t, t;\nex2.approx.ftz.f32 %0, t;\n}" : "=f"(e0) : "f"(l0));
  asm("{\n.reg .f32 t;\nabs.f32 t, %1;\nneg.f32 t, t;\nex2.approx.ftz.f32 %0, t;\n}" : "=f"(e1) : "f"(l1));
  uint32_t e = pack_bf16(e0, e1), r;
  const uint32_t a = pack_bf16(fmaf(l0, LN2, 1.000001f), fmaf(l1, LN2, 1.000001f));
  asm("add.rn.bf16x2 %0, %0, %1;" : "+r"(e) : "r"(0x35863586u));
  asm("max.NaN.bf16x2 %0, %1, %2;" : "=r"(r) : "r"(a), "r"(e));
  return r;
}
template <bool V = false>
__device__ __forceinline__ uint32_t phi2(float u0, float rs0, float rl0, float u1, float rs1, float rl1) {
  float e0, e1;
  if (V) {
    asm volatile("{\n.reg .f32 t;\nabs.f32 t, %1;\nneg.f32 t, t;\nex2.approx.ftz.f32 %0, t;\n}" : "=f"(e0) : "f"(u0 * rl0));
    asm volatile("{\n.reg .f32 t;\nabs.f32 t, %1;\nneg.f32 t, t;\nex2.approx.ftz.f32 %0, t;\n}" : "=f"(e1) : "f"(u1 * rl1));
  } else {
    asm("{\n.reg .f32 t;\nabs.f32 t, %1;\nneg.f32 t, t;\nex2.approx.ftz.f32 %0, t;\n}" : "=f"(e0) : "f"(u0 * rl0));
    asm("{\n.reg .f32 t;\nabs.f32 t, %1;\nneg.f32 t, t;\nex2.approx.ftz.f32 %0, t;\n}" : "=f"(e1) : "f"(u1 * rl1));
  }
  uint32_t e = pack_bf16(e0, e1), r;
  const uint32_t a = pack_bf16(fmaf(u0, rs0, 1.000001f), fmaf(u1, rs1, 1.000001f));
  asm("add.rn.bf16x2 %0, %0, %1;" : "+r"(e) : "r"(0x35863586u));
  asm("max.NaN.bf16x2 %0, %1, %2;" : "=r"(r) : "r"(a), "r"(e));
  return r;
}

__device__ __forceinline__ int kstep1(int e, int hg) { return e < 14 ? (e < 2 * hg ? e : e + 2) : 2 * hg + e - 14; }
__device__ __forceinline__ int slab(int n, int hg) {
  return n + (((n + 7 - hg) * 37) >> 8);
}
__host__ __device__ constexpr uint32_t d_off(int i) { return i < 3 ? 12 * SLOT + (NR == 4 ? i : (i == 2 ? 0 : i + 1)) * MT : (i < 5 ? S_D0 * SLOT + (i - 3) * 8192 : S_D1 * SLOT + (i - 5) * 8192); }
__host__ __device__ constexpr uint32_t h_off(int i) { return i < 3 ? 12 * SLOT + i * MT + 8192 : (i < 5 ? A_ONES + (i - 3) * 1024 : MISC + M_MOE + (i - 5) * 1024); }
__device__ __forceinline__ uint32_t m_off(int r) { return r < 3 ? 12 * SLOT + r * MT : S_M3 * SLOT; }
__device__ __forceinline__ int x_slot(int e, int s) { return NQ == 5 ? (e < 14 ? s : e - 11) : (e < 13 ? s : 3 + s); }
__device__ __forceinline__ uint32_t wo_slot(int i) { return (uint32_t)(WO_SLOTS >> (4 * i)) & 15u; }

__global__ void __launch_bounds__(512, 1)
fused_kernel(const __nv_bfloat16* __restrict__ x, const __nv_bfloat16* __restrict__ wqkv, const __nv_bfloat16* __restrict__ wo,
             const __nv_bfloat16* __restrict__ wr, const __nv_bfloat16* __restrict__ wd, __nv_bfloat16* __restrict__ outp, const int by_sm,
             const __grid_constant__ CUtensorMap tmX, const __grid_constant__ CUtensorMap tmW,
             const __grid_constant__ CUtensorMap tmWo, const __grid_constant__ CUtensorMap tmOut,
             const __grid_constant__ CUtensorMap tmG, const __grid_constant__ CUtensorMap tmU,
             const __grid_constant__ CUtensorMap tmD, const __grid_constant__ CUtensorMap tmR,
             const __grid_constant__ CUtensorMap tmWp) {
  if (TMP && threadIdx.x == 32 * TMPW) { map_pf(&tmX); map_pf(&tmW); }
  extern __shared__ __align__(1024) uint8_t smem_raw[];
  const uint32_t sb = (uint32_t)__cvta_generic_to_shared(smem_raw);
  const uint32_t bars = sb + MISC + M_BAR;
  uint32_t smid;
  asm("mov.u32 %0, %%smid;" : "=r"(smid));
  const int tpc = smid >> 1;
  int cl = tpc + max(((tpc - 25) * 37) >> 8, 0);
  cl = tpc < 60 ? cl : cl - 1;
  cl = tpc < 62 ? cl : (tpc - 58) * 8;
  const int u = by_sm ? 2 * cl + (blockIdx.x & 1) : blockIdx.x;
  const int hg = (u >> 4) & 7, tb = u & 15;
  const int b = tb * 8 + hg;
  const int lane = threadIdx.x & 31;
  const int warp = __shfl_sync(~0u, threadIdx.x >> 5, 0);
  const int ltid = threadIdx.x;
  const int g = lane >> 2, t = lane & 3;
  const uint32_t d0 = (sb & 0x3FFFF) >> 4;
#define BAR(i) (bars + 8 * (i))
  TLS(0, 0);

  const int rank = u & 1;
  auto load_entry = [&](int e, int s) {
    const int k0 = kstep1(e, hg) * 64;
    mbar_expect_tx(BAR(B_FXQ + s), e < NF ? 2 * SLOT : SLOT);
    mbar_expect_tx(BAR(B_FKV + s), R5 ? SLOT : 2 * SLOT);
    if (R5 && e < 11) mbar_expect_tx(BAR(B_FV + s), SLOT);
    const uint32_t vb = R5 ? BAR(B_FV + s) : BAR(B_FKV + s);
    tma2d(sb + x_slot(e, s) * SLOT, &tmX, k0, tb * 128, BAR(B_FXQ + s));
    if (e < MC0 || !(MC & 1)) {
      if (e < NF) tma3d(sb + (3 + s) * SLOT, &tmW, k0, 2 * hg, BAR(B_FXQ + s));
      tma3d(sb + (6 + 2 * s) * SLOT, &tmW, k0, 16 + 2 * hg, BAR(B_FKV + s));
      tma3d(sb + (7 + 2 * s) * SLOT, &tmW, k0, 32 + 2 * hg, vb);
    } else {
      if (e < NF && (e & 1) == rank) tma3d_mc(sb + (3 + s) * SLOT, &tmW, k0, 2 * hg, BAR(B_FXQ + s));
      if (R5 && e >= 11) { if (rank == 0) tma3d_mc(sb + ((K_SLOTS >> (4 * (e - 10))) & 15u) * SLOT, &tmW, k0, 16 + 2 * hg, BAR(B_FKV + s)); }
      else tma3d_mc(sb + (6 + 2 * s + rank) * SLOT, &tmW, k0, 16 + 16 * rank + 2 * hg, rank ? vb : BAR(B_FKV + s));
    }
  };
  if (warp == FW && u < NCTA) {
    if (elect_one()) {
      mbar_init(BAR(B_FXQ), 1); mbar_init(BAR(B_FKV), 1);
      if (R5) mbar_init(BAR(B_FV), 1);
      load_entry(0, 0);
      asm volatile("fence.mbarrier_init.release.cluster;" ::: "memory");
      TLS(FW * 32, 61);
    }
    __syncwarp();
  }
  if (u >= NCTA) {
    const int j = u - NCTA;
    if (warp == 8 && elect_one()) {
#pragma unroll
      for (int i = 0; i < 13; i++) mbar_init(BAR(i), 1);
    }
    if (ltid < 64) sts_u4(sb + MISC + ltid * 16, make_uint4(0x3F803F80u, 0x3F803F80u, 0x3F803F80u, 0x3F803F80u));
    fence_async_smem();
    __syncthreads();
    if (warp < 4) {
      int s = 0, p = 0;
#pragma unroll 1
      for (int pass = 0; pass < 3; pass++) {
        float acc[4][4];
#pragma unroll
        for (int c = 0; c < 4; c++) acc[c][0] = acc[c][1] = acc[c][2] = acc[c][3] = 0.f;
#pragma unroll 1
        for (int k = 0; k < 16; k++) {
          mbar_wait(BAR(s), p);
          wg_fence();
#pragma unroll
          for (int c = 0; c < 4; c++)
#pragma unroll
            for (int kk = 0; kk < 4; kk++)
              wgmma_ss_n8<1, 0>(acc[c], mkdesc((d0 + s * 2048 + c * 512 + kk * 128) | (512u << 16), HI_SW128), mkdesc((d0 + (MISC >> 4)) | (1u << 16), HI_SW128));
          wg_commit();
          wg_wait<0>();
          if (ltid == 0) mbar_arrive(BAR(6 + s));
          if (++s == SVS) { s = 0; p ^= 1; }
        }
        uint32_t* pc = G.cs + (pass < 2 ? DM + pass * DM : 0) + j * 256 + warp * 16 + g;
#pragma unroll
        for (int c = 0; c < 4; c++) {
          reg_fence(acc[c]);
          const uint32_t v = __float_as_uint((t & 1) ? acc[c][2] : acc[c][0]);
          if (t < 2) stx1(pc + c * 64 + t * 8, v ? v : 0x80000000u);
        }
        TLS(0, 1 + pass);
      }
    } else if (warp >= 8 && j == 0) {
      const int wq = warp - 8;
      const uint32_t top = sb + MISC + 1024;
#pragma unroll 1
      for (uint32_t it = 0; it < SPIN_MAX; it++) {
        const uint4 v0 = ldx4(G.key + wq * 256 + lane * 4), v1 = ldx4(G.key + wq * 256 + 128 + lane * 4);
        uint32_t ok;
        asm volatile("{\n.reg .pred p, q;\nsetp.ne.u32 p, %1, 0;\nbar.red.and.pred q, 2, 256, p;\nselp.b32 %0, 1, 0, q;\n}" : "=r"(ok) : "r"((v0.x & v0.y & v0.z & v0.w & v1.x & v1.y & v1.z & v1.w) >> 27) : "memory");
        ok = __any_sync(~0u, ok);
        if (!ok && it) continue;
        TLS(256, 4);
        uint32_t np = 0u - (1u << 28), mine = 0;
#pragma unroll 1
        for (int r = 0; r < 8; r++) {
          const uint32_t m0 = __viaddmax_u32(v0.x, np, v0.y + np), m1 = __viaddmax_u32(v0.z, np, v0.w + np), m2 = __viaddmax_u32(v1.x, np, v1.y + np), m3 = __viaddmax_u32(v1.z, np, v1.w + np);
          np -= __reduce_max_sync(~0u, max(max(m0, m1), max(m2, m3)));
          if (g == r) mine = 0u - np;
        }
        if (t == 0) sts_u(top + (wq * 8 + g) * 4, mine);
        bar_sync<2, 256>();
        TLS(256, 5);
        int rk = 0;
#pragma unroll
        for (int i = 0; i < 4; i++) {
          const uint4 o = lds_u4(top + t * 64 + i * 16);
          rk += (o.x > mine) + (o.y > mine) + (o.z > mine) + (o.w > mine);
        }
        rk += __shfl_xor_sync(~0u, rk, 1);
        rk += __shfl_xor_sync(~0u, rk, 2);
        if (ok) { if (rk < 8) stx1(G.top + t * 32 + rk, mine); break; }
        __nanosleep(2500);
      }
      TLS(256, 7);
    } else if (warp == 4) {
      int s = 0, p = 1;
      if (SVD) __nanosleep(SVD);
#pragma unroll 1
      for (int i = 0; i < 48; i++) {
        mbar_wait(BAR(6 + s), p);
        if (j == 0 && i >= SV0A && i < SV0B) mbar_wait(BAR(s >= SV0 ? s - SV0 : s - SV0 + SVS), s >= SV0 ? p ^ 1 : p);
        if (elect_one()) {
          mbar_expect_tx(BAR(s), 2 * SLOT);
          const int ch = (i < 32 ? 16 + (i & 16) : 0) + j * 4, k0 = (i & 15) * 64;
          tma3d(sb + s * 2 * SLOT, &tmW, k0, ch, BAR(s));
          tma3d(sb + s * 2 * SLOT + SLOT, &tmW, k0, ch + 2, BAR(s));
        }
        if (++s == SVS) { s = 0; p ^= 1; }
      }
    }
    if (ltid == 0) cnt_wait(C_DONE, NCTA);
    __syncthreads();
    const uint4 zero = make_uint4(0, 0, 0, 0);
    if (ltid < 128) reinterpret_cast<uint4*>(G.key)[j * 128 + ltid] = zero;
    else if (ltid < 320) reinterpret_cast<uint4*>(G.cs)[j * 192 + ltid - 128] = zero;
    else if (ltid < 322) reinterpret_cast<uint4*>(G.top)[j * 8 + ltid - 320] = zero;
    if (ltid == 0) { cnt_done(); TLDUMP(); }
    return;
  }

  if (warp == 12) {
    if (elect_one()) {
#pragma unroll
      for (int i = 1; i < 7; i++) if (i != B_FKV) mbar_init(BAR(i), 1);
      if (R5) { mbar_init(BAR(B_FV + 1), 1); mbar_init(BAR(B_FV + 2), 1); }
      if (E1E) load_entry(1, 1);
      asm volatile("fence.mbarrier_init.release.cluster;" ::: "memory");
    }
  } else if (warp >= 13) {
    if (elect_one()) {
      if (warp == 15) {
#pragma unroll
        for (int i = B_FAUX; i < NBAR; i++) mbar_init(BAR(i), i < B_E || !MC ? 2 : 4);
        mbar_init(BAR(B_KV4), 4); mbar_init(BAR(B_MS), 2); mbar_init(BAR(B_GQ), 1); mbar_init(BAR(B_GT), 1);
        if (R5) { mbar_init(BAR(B_EK), 4); mbar_init(BAR(B_EK + 1), 4); mbar_init(BAR(B_EK + 2), 4); }
      } else {
#pragma unroll
        for (int i = 0; i < 23; i++) mbar_init(BAR((warp == 13 ? 7 : 30) + i), 1);
      }
      asm volatile("fence.mbarrier_init.release.cluster;" ::: "memory");
    }
  }
  __syncthreads();
  if (MC) asm volatile("barrier.cluster.arrive.relaxed.aligned;" ::: "memory");

  const bool unit = u < NUNIT;
  const int dcol = (u & 15) * 64, drow = (u >> 4) * 448;
  if (warp >= 12) {
    asm volatile("setmaxnreg.dec.sync.aligned.u32 %0;" ::"n"(PROD_REGS));
    if (MC && warp != 12) asm volatile("barrier.cluster.wait.aligned;" ::: "memory");
    if (warp == 12) {
      int s = 1 + E1E, p = 1, pn = 3;
#pragma unroll 1
      for (int e = 1 + E1E; e < 16; e++) {
        if (MC && e == MC0) asm volatile("barrier.cluster.wait.aligned;" ::: "memory");
        if (e == GATE) mbar_wait(BAR(B_FXQ), 0);
        mbar_wait(BAR(B_E + s), p);
        if (elect_one()) {
          load_entry(e, s);
          if (NR == 4 && e == 11) mbar_arrive(BAR(B_ME + 3));
          if (e == ASTE) {
            mbar_expect_tx(BAR(B_AST), 2 * SLOT + 2048);
            bulk_ld(sb + 12 * SLOT, x + (size_t)b * 16 * DM, 2 * SLOT, BAR(B_AST));
            bulk_ld(sb + MISC + M_MOE, wr, 2048, BAR(B_AST));
          } else if (e >= 3) {
            if (e < 6) bulk_pf(wqkv + (size_t)((e - 2) * 256 + 2 * b) * 3 * DM, 2 * 3 * DM * 2);
            if (e < 7) bulk_pf(wo + (size_t)((e - 3) * 256 + 2 * b) * DM, 2 * DM * 2);
            if (NUNIT) {
#pragma unroll 1
              for (int i = (PFTAB >> (4 * (e - 3))) & 15; i > 0; i--, pn++) {
                if (pn >= 16) { if (!(MX & 8)) tma2d_pf(&tmD, dcol, drow + (pn - 16) * 64); }
                else if (unit && !(MX & 2)) tma2d_pf(rank ? &tmU : &tmG, (u >> 1) * 64, pn * 64);
              }
            }
          }
        }
        if (R5 && e >= 11) {
          mbar_wait(BAR(B_EK + (s == 2 ? 0 : s + 1)), e >= 14);
          if (elect_one()) {
            mbar_expect_tx(BAR(B_FV + s), SLOT);
            if (rank) tma3d_mc(sb + ((V_SLOTS >> (4 * (e - 10))) & 15u) * SLOT, &tmW, kstep1(e, hg) * 64, 32 + 2 * hg, BAR(B_FV + s));
          }
        }
        if (++s == 3) { s = 0; p ^= 1; }
      }
#pragma unroll 1
      for (int k = 0; k < NQ; k++) {
        if (k == 0) mbar_wait(BAR(B_E + 1), 0);
        if (k == 1) mbar_wait(BAR(B_EK + 2), 1);
        if (k == 2) mbar_wait(BAR(B_EK + 0), 0);
        if (k == 3) mbar_wait(BAR(B_STG), 0);
        if (k == 5) mbar_wait(BAR(B_EQ), 0);
        if (elect_one()) {
          const int k0 = kstep1(NF + k, hg) * 64;
          mbar_expect_tx(BAR(B_FQ + k), SLOT);
          if (!(MC & 2)) tma3d(sb + ((QW_SLOTS >> (4 * k)) & 15u) * SLOT, &tmW, k0, 2 * hg, BAR(B_FQ + k));
          else if ((k & 1) == rank) tma3d_mc(sb + ((QW_SLOTS >> (4 * k)) & 15u) * SLOT, &tmW, k0, 2 * hg, BAR(B_FQ + k));
        }
      }
#pragma unroll 1
      for (int i = 0; i < 16; i++) {
        mbar_wait(i < 7 ? BAR(B_EQ + ((i + WQ0) >> 1)) : (i < 9 ? BAR(B_DE) : BAR(B_EO + i - 9)), 0);
        if (i == WOK) mbar_wait(BAR(B_KVB), 0);
        mbar_wait(BAR(B_FWO + i - (i < WOK ? WOD1 : WOD)), 0);
        if (elect_one()) {
          mbar_expect_tx(BAR(B_FWO + i), SLOT);
#pragma unroll
          for (int hf = 0; hf < ((MC & 4) ? 1 : 2); hf++) {
            const int n = 2 * i + ((MC & 4) ? rank : hf), m = slab(n - 4, hg), hd = n < 4 ? 4 * hg + n : 4 * (m & 7) + (m >> 3);
            if (i < 2 + NDIR) tma5d(sb + wo_slot(i) * SLOT + (n & 1) * 8192, &tmWp, hd * 4, 2 * hg, BAR(B_FWO + i), MC & 4);
            else if (MC & 4) tma3d_mc(sb + wo_slot(i) * SLOT + rank * 8192, &tmWo, hd * 32, 2 * hg, BAR(B_FWO + i));
            else tma3d(sb + wo_slot(i) * SLOT + hf * 8192, &tmWo, hd * 32, 2 * hg, BAR(B_FWO + i));
          }
        }
      }
    } else if (warp == 13) {
      if (elect_one()) {
        map_pf(rank ? &tmU : &tmG); map_pf(&tmR); map_pf(&tmD); map_pf(&tmWo); map_pf(&tmWp); map_pf(&tmOut);
      }
      bar_sync<6, 64>();
      if (elect_one()) {
        cnt_wait(C_B, NCTA);
        fence_async_gmem();
        mbar_expect_tx(BAR(B_FAUX), 1024);
        bulk_ld(sb + A_ST, G.stats + tb * 128, 1024, BAR(B_FAUX));
      }
      __syncwarp();
      TLS(416, 68);
#pragma unroll 1
      for (int m = 1; m < 4; m++) {
        const int part = m == 3 ? 0 : m;
        uint4 c;
#pragma unroll 1
        for (uint32_t it = 0; it < SPIN_MAX; it++) {
          c = ldx4(G.cs + part * DM + hg * 128 + lane * 4);
          if (__all_sync(~0u, min(min(c.x, c.y), min(c.z, c.w)))) break;
          __nanosleep(POLLNS);
        }
        if (CQ4 && part == 0) {
          const uint32_t o = sb + A_CS + (lane >> 2) * 64 + (lane & 1) * 32 + ((lane >> 1) & 1) * 8;
          asm volatile("st.shared.v2.u32 [%0], {%1,%2};\nst.shared.v2.u32 [%0+16], {%3,%4};" ::"r"(o), "r"(c.x), "r"(c.y), "r"(c.z), "r"(c.w) : "memory");
        } else sts_u4(sb + A_CS + part * 512 + lane * 16, c);
        __syncwarp();
        if (m > 1 && lane == 0) mbar_arrive(BAR(m == 2 ? B_FAUX : B_CQ));
        TLS(416, 71 + m);
      }
      mbar_wait(BAR(B_XS), 1);
      if (elect_one()) asm volatile("red.relaxed.gpu.global.add.u32 [%0], 1;" ::"l"(&G.cnt[C_DONE]) : "memory");
    } else if (warp == 14) {
      const uint4 sent = make_uint4(SENT, SENT, SENT, SENT);
      uint4* ro = G.o + (tb * 32 + hg) * 512 + lane;
      uint4* rp = G.part + b * 544 + lane;
      if (RSL) bar_sync<5, 160>(); else mbar_wait(BAR(B_AST), 0);
#pragma unroll 1
      for (int i = RS0; i < 40; i++) {
        uint4* q = i < 32 ? ro + (i >> 3) * 4096 + (i & 7) * 64 : rp + (i - 32) * 64;
        q[0] = sent; q[32] = sent;
        __nanosleep(RSNS);
      }
      rp[512] = sent;
#pragma unroll
      for (int i = 0; i < 4; i++) G.y[u * 128 + i * 32 + lane] = sent;
      if (unit) reinterpret_cast<uint4*>(G.h)[u * 32 + lane] = sent;
      G.fin[hg * 640 + tb * 40 + lane] = sent;
      if (lane < 8) G.fin[hg * 640 + tb * 40 + 32 + lane] = sent;
      if (!RSL) bar_sync<5, 160>();
      __syncwarp();
      TLS(448, 67);
      if (lane == 0) cnt_arrive(C_B);
      __syncwarp();
      TLS(448, 32);
      asm volatile("bar.arrive 6, 64;" ::: "memory");
    } else {
      const uint32_t stg = sb + 12 * SLOT;
      auto load_a = [&](int n, int r) {
        mbar_expect_tx(BAR(B_MF + r), (MX & 2) ? 1024 : MT);
        if (!(MX & 2)) tma2d_ef(sb + m_off(r), rank ? &tmU : &tmG, (u >> 1) * 64, n * 64, BAR(B_MF + r));
      };
      mbar_wait(BAR(B_XS), 0);
      if (unit) {
#pragma unroll 1
        for (int i = 0; i < 3; i++) {
          if (elect_one()) load_a(i, i);
          __nanosleep(PFILL);
        }
      }
      uint32_t key;
#pragma unroll 1
      for (uint32_t it = 0; it < SPIN_MAX; it++) {
        key = ldx1(G.top + ((u >> 1) & 3) * 32 + (lane & 7));
        if (__all_sync(~0u, key)) break;
        __nanosleep(TPNS);
      }
      TLS(480, 66);
      if (lane < 8) sts_u(sb + MISC + M_IDX + lane * 4, key);
      __syncwarp();
      if (lane == 0) mbar_arrive(BAR(B_XS));
      if (unit) {
        int tok[8];
#pragma unroll
        for (int i = 0; i < 8; i++) tok[i] = ~__shfl_sync(~0u, key, i) & 2047;
        int r = 0, p = 0;
#pragma unroll 1
        for (int n = 0; n < 16; n++) {
          if (n >= 3) mbar_wait(BAR(B_ME + r), r == 3 ? p : p ^ 1);
          if (elect_one()) {
            if (n >= 3) load_a(n, r);
#pragma unroll
            for (int i = 0; i < 8; i++) tma2d(sb + m_off(r) + 8192 + i * 128, &tmR, n * 64, tok[i], BAR(B_MF + r));
          }
          if (++r == NR) { r = 0; p ^= 1; }
        }
      }
      if (NUNIT) {
        if (lane == 0) mbar_expect_tx(BAR(B_DF), (MX & 8) ? 0 : 7 * 8192);
#pragma unroll 1
        for (int i = 0; i < 7; i++) {
          if (NR == 4) {
            if (i >= 3) mbar_wait(i < 5 ? BAR(B_ME + 3) : (R5 ? BAR(B_EQ + 1) : BAR(B_STG)), 0);
            else if (unit) mbar_wait(BAR(B_ME + i), 1);
          } else {
            if (i >= 3) mbar_wait(BAR(B_EQ + ((i - 3) >> 1)), 0);
            else if (unit) mbar_wait(BAR(B_ME + (i == 2 ? 0 : i + 1)), i == 2);
          }
          if (!(MX & 8) && elect_one()) tma2d_ef(sb + d_off(i), &tmD, dcol, drow + i * 64, BAR(B_DF));
          if (DNS) __nanosleep(DNS);
        }
      }
    }
    if (warp == 14) {
      if (DPF && NUNIT && !(MX & 8)) {
        mbar_wait(DS ? BAR(B_MS) : (DPF == 1 ? BAR(B_FQ) : BAR(B_T0)), 0);
#pragma unroll 1
        for (int pf = 0; pf < 7; pf++) { pf256(sb + MISC + M_DUM, wd + (size_t)(drow + pf * 64 + rank * 32 + lane) * DM + (dcol & ~127)); __nanosleep(PFNS2); }
      }
      const uint32_t* src = reinterpret_cast<const uint32_t*>(G.part + ((lane >> 3) * 32 + hg) * 544 + 512) + tb * 8 + (lane & 7);
      mbar_wait(BAR(B_EQ + MRW), 0);
      if (MRC) spin_cycles(MRC); else if (MRD) __nanosleep(MRD);
      uint32_t z0, z1, z2, z3;
#pragma unroll 1
      for (uint32_t it = 0; it < SPIN_MAX; it++) {
        z0 = ldx1(src); z1 = ldx1(src + 8 * 2176); z2 = ldx1(src + 16 * 2176); z3 = ldx1(src + 24 * 2176);
        if (!__any_sync(~0u, max(max(z0, z1), max(z2, z3)) == SENT)) break;
      }
      if (MRED == 2 && elect_one()) mbar_arrive(BAR(B_ZOK));
      float zz = (__uint_as_float(z0) + __uint_as_float(z1)) + (__uint_as_float(z2) + __uint_as_float(z3));
      zz += __shfl_xor_sync(~0u, zz, 8);
      zz += __shfl_xor_sync(~0u, zz, 16);
      stx1(reinterpret_cast<uint32_t*>(G.fin + hg * 640) + (tb >> 2) * 640 + 512 + ((tb >> 1) & 1) * 64 + (lane & 1) * 32 + (tb & 1) * 16 + ((lane & 7) >> 1) * 4 + (lane >> 3),
           pack_bf16(zz, zz));
      TLS(448, 12);
    }
    if (!MFIN && (warp == 13 || warp == 14)) {
      mbar_wait(BAR(B_EQ + H2W), 0);
      if (H2C) spin_cycles(H2C); else if (H2D) __nanosleep(H2D);
#pragma unroll 1
      for (uint32_t it = 0; it < SPIN_MAX; it++) {
        if (warp == 14 && elect_one()) {
          mbar_expect_tx(BAR(B_FIN), 10240);
          if (FMC && MC && it == 0) bulk_ld_mc(sb + S_KVB * SLOT + rank * 5120, G.fin + hg * 640 + rank * 320, 5120, BAR(B_FIN));
          else bulk_ld(sb + S_KVB * SLOT, G.fin + hg * 640, 10240, BAR(B_FIN));
        }
        mbar_wait(BAR(B_FIN), it & 1);
        uint32_t m = 0;
#pragma unroll
        for (int i = 0; i < 10; i++) m = max(m, lds_u(sb + S_KVB * SLOT + (i * 64 + ltid - 416) * 16 + (g >> 1) * 4));
        uint32_t bad;
        asm volatile("{\n.reg .pred p, q;\nsetp.eq.u32 p, %1, 0xFFFFFFFF;\nbar.red.or.pred q, 7, 64, p;\nselp.b32 %0, 1, 0, q;\n}" : "=r"(bad) : "r"(m) : "memory");
        if (!__any_sync(~0u, bad)) break;
      }
      if (warp == 14 && elect_one()) mbar_arrive(BAR(B_KVB));
      TLS(448, 14);
    }
    if (PH && (warp == 13 || warp == 14)) {
      bar_sync<3, 192>();
      mbar_wait(BAR(B_STG), 0);
#pragma unroll 1
      for (uint32_t it = 0; NUNIT && it < SPIN_MAX; it++) {
        if (elect_one()) {
          const uint32_t* ph = G.h + (u >> 4) * 7 * 256;
          if (warp == 13) { mbar_expect_tx(BAR(B_HF), 7168); bulk_ld(sb + h_off(3), ph + 768, 2048, BAR(B_HF)); bulk_ld(sb + h_off(5), ph + 1280, 2048, BAR(B_HF)); }
          else { bulk_ld(sb + h_off(0), ph, 1024, BAR(B_HF)); bulk_ld(sb + h_off(1), ph + 256, 1024, BAR(B_HF)); bulk_ld(sb + h_off(2), ph + 512, 1024, BAR(B_HF)); }
        }
        mbar_wait(BAR(B_HF), it & 1);
        uint32_t m = 0;
#pragma unroll
        for (int i = 0; i < 7; i++) m = max(m, lds_u(sb + h_off(i) + (ltid - 416) * 16 + (g >> 1) * 4));
        uint32_t bad;
        asm volatile("{\n.reg .pred p, q;\nsetp.eq.u32 p, %1, 0xFFFFFFFF;\nbar.red.or.pred q, 7, 64, p;\nselp.b32 %0, 1, 0, q;\n}" : "=r"(bad) : "r"(m) : "memory");
        if (!__any_sync(~0u, bad)) break;
        __nanosleep(POLLNS);
      }
      if (warp == 14 && elect_one()) mbar_arrive(BAR(B_KVB));
    }
    __syncwarp();
    if (warp >= 13) {
      const char* og = reinterpret_cast<const char*>(G.o + tb * 16384);
      auto probe = [&](uint32_t m) {
        const char* p = og + m * 8192u + (lane & 15) * 512 + 496;
#pragma unroll 1
        for (uint32_t it = 0; it < SPIN_MAX; it++)
          if (!__any_sync(~0u, ldx1(p) == SENT)) break;
      };
      if (warp == 15) {
        int r = 0, p = 1;
        mbar_wait(BAR(B_EAUX), 0);
#pragma unroll 1
        for (int i = I0; i < 16; i++) {
          const uint32_t dst = sb + ((A_SLOTS >> (4 * r)) & 15u) * SLOT, m0 = slab(2 * i - 4, hg), m1 = slab(2 * i - 3, hg);
          if (i == I0 + 3) mbar_wait(BAR(B_DE), 0);
          mbar_wait(BAR(B_EA + r), p);
          if ((PROBE >> i) & 1) probe(lane < 16 ? m0 : m1);
          if (elect_one()) {
            mbar_expect_tx(BAR(B_AF + r), SLOT);
            bulk_ld(dst, og + m0 * 8192u, 8192, BAR(B_AF + r)); bulk_ld(dst + 8192, og + m1 * 8192u, 8192, BAR(B_AF + r));
          }
          if (++r == NA) { r = 0; p ^= 1; }
        }
      } else {
        const uint32_t lo = lane * 32 + g * 4, hb = sb + (warp - 13) * 8192;
        uint32_t ph = 0;
        int r = 0, p = 0;
#pragma unroll 1
        for (int i = I0; i < 16; i++) {
          const uint32_t mine = hb + ((A_SLOTS >> (4 * r)) & 15u) * SLOT;
          auto bad = [&]() {
            uint32_t v[8];
#pragma unroll
            for (int j = 0; j < 8; j++) v[j] = lds_u(mine + lo + j * 1024);
            return __any_sync(~0u, max(max(max(v[0], v[1]), max(v[2], v[3])), max(max(v[4], v[5]), max(v[6], v[7]))) == SENT);
          };
          mbar_wait(BAR(B_AF + r), p);
          if (!NOVAL && bad()) {
            const uint32_t m = slab(2 * i - 17 + warp, hg);
#pragma unroll 1
            for (uint32_t it = 0; it < 64; it++) {
              probe(m);
              if (elect_one()) { mbar_expect_tx(BAR(B_AR + warp - 13), 8192); bulk_ld(mine, og + m * 8192u, 8192, BAR(B_AR + warp - 13)); }
              mbar_wait(BAR(B_AR + warp - 13), ph);
              ph ^= 1;
              if (!bad()) break;
            }
          }
          if (elect_one()) mbar_arrive(BAR(B_VAL + r));
          if (++r == NA) { r = 0; p ^= 1; }
        }
      }
    }
  } else if (warp >= 8) {
    asm volatile("setmaxnreg.dec.sync.aligned.u32 %0;" ::"n"(MOE_REGS));
    if (MC) asm volatile("barrier.cluster.wait.aligned;" ::: "memory");
    const int aw = warp - 8;
    const uint32_t mbuf = sb + MISC + M_MOE, stg = sb + 12 * SLOT;
    mbar_wait(BAR(B_AST), 0);
    TLS(288, 64);
    {
      float v[16];
#pragma unroll
      for (int r = 0; r < 16; r++) v[r] = 0.f;
      const uint32_t base = stg + aw * 4 * 2048 + lane * 8;
#pragma unroll 1
      for (int c = 0; c < 8; c++) {
        const float2 w2 = lds_f2(mbuf + c * 256 + lane * 8);
        const float w[4] = {bf_lo(__float_as_uint(w2.x)), bf_hi(__float_as_uint(w2.x)), bf_lo(__float_as_uint(w2.y)), bf_hi(__float_as_uint(w2.y))};
        v[12] += (w[0] + w[1]) + (w[2] + w[3]);
#pragma unroll
        for (int r = 0; r < 4; r++) {
          const float2 x2 = lds_f2(base + r * 2048 + c * 256);
#pragma unroll
          for (int e = 0; e < 2; e++) {
            const uint32_t xx = __float_as_uint(e ? x2.y : x2.x);
            const float lo = bf_lo(xx), hi = bf_hi(xx);
            v[r] += lo; v[4 + r] = fmaf(lo, lo, v[4 + r]); v[8 + r] = fmaf(lo, w[2 * e], v[8 + r]);
            v[r] += hi; v[4 + r] = fmaf(hi, hi, v[4 + r]); v[8 + r] = fmaf(hi, w[2 * e + 1], v[8 + r]);
          }
        }
      }
#pragma unroll
      for (int l = 0; l < 4; l++) {
        const int n = 8 >> l;
        const bool up = lane & (2 * n);
#pragma unroll
        for (int r = 0; r < 8; r++) {
          if (r < n) { const float a = v[r], c = v[n + r]; v[r] = (up ? c : a) + __shfl_xor_sync(~0u, up ? a : c, 2 * n); }
        }
      }
      v[0] += __shfl_xor_sync(~0u, v[0], 1);
      const float sx = __shfl_sync(~0u, v[0], 2 * t), sq = __shfl_sync(~0u, v[0], 8 + 2 * t), sw = __shfl_sync(~0u, v[0], 16 + 2 * t), ws = __shfl_sync(~0u, v[0], 24);
      if (lane < 4) {
        const int row = b * 16 + aw * 4 + lane;
        const float mean = sx * (1.f / DM);
        const float var = fmaxf(fmaf(-mean, mean, sq * (1.f / DM)), 0.f);
        float sd;
        asm("sqrt.approx.ftz.f32 %0, %1;" : "=f"(sd) : "f"(bf_round(bf_round(var) + 1e-5f)));
        const float rstd = rcp(bf_round(sd));
        const float mb = bf_round(mean);
        uint32_t rb = pack_bf16(fmaf(-mb, ws, sw) * rstd, 0.f) & 0xFFFFu;
        rb = (rb & 0x8000u) ? (~rb & 0xFFFFu) : (rb | 0x8000u);
        const uint32_t key = (1u << 27) | (rb << 11) | (uint32_t)(2047 - row);
        if (KEY1) sts_u(sb + MISC + M_KEY + (aw * 4 + lane) * 4, key); else stx1(G.key + row, key);
        G.stats[row] = make_float2(mb, SL2 ? rstd * LOG2E : rstd);
      }
    }
    bar_sync<2, 128>();
    if (KEY1 && ltid < 272) stx1(G.key + b * 16 + lane, lds_u(sb + MISC + M_KEY + lane * 4));
    TLS(288, 65);
    sts_u4(sb + A_ONES + (ltid - 256) * 16, make_uint4(0x3F803F80u, 0x3F803F80u, 0x3F803F80u, 0x3F803F80u));
    fence_async_smem();
    asm volatile("bar.arrive 5, 160;" ::: "memory");
    if (ltid == 256) { if (unit && rank == 0) mbar_expect_tx(BAR(B_UP), 2048); mbar_arrive(BAR(B_XS)); }
    bar_sync<2, 128>();
    mbar_wait(BAR(B_XS), 1);
    TLS(288, 70);
    if (NUNIT) {
      if (unit) {
        int r = 0, p = 0;
        uint32_t rel = 0;
        float acc[8];
        uint2 s0, s1;
#pragma unroll
        for (int i = 0; i < 8; i++) acc[i] = 0.f;
        if (MS == 16) mbar_wait(BAR(B_T0), 0); else if (MS) mbar_wait(BAR(B_MS), 0);
#pragma unroll 1
        for (int n = 0; n < 16; n++) {
          if (n == 15) {
            mbar_wait(BAR(B_FAUX), 0);
            s0 = ldx2(G.stats + (~lds_u(sb + MISC + M_IDX + t * 8) & 2047)); s1 = ldx2(G.stats + (~lds_u(sb + MISC + M_IDX + t * 8 + 4) & 2047));
            if (SL2) { s0.y = __float_as_uint(__uint_as_float(s0.y) * LN2); s1.y = __float_as_uint(__uint_as_float(s1.y) * LN2); }
          }
          mbar_wait(BAR(B_MF + r), p);
          if (!(n & 3)) TLS(288, 56 + (n >> 2));
          const uint32_t mo = m_off(r) >> 4, da = (d0 + mo) | (512u << 16), db = (d0 + mo + 512) | (1u << 16);
          const uint32_t hb = 0x40000000u | ((A_ONES >> 4) - 512 - mo);
          wg_fence();
#pragma unroll
          for (int kk = 0; kk < ((MX & 1) ? 1 : 4); kk++) wgmma_ss_n16<1, 0>(acc, mkdesc(da + kk * 128, HI_SW128), mkdesc(db + kk * 2, hb));
          wg_commit();
          wg_wait<1>();
          if (n > 0 && !rel && ltid == 256) mbar_arrive(BAR(B_ME + (r == 0 ? NR - 1 : r - 1)));
          rel = 0;
          const int r0 = r;
          if (++r == NR) { r = 0; p ^= 1; }
        }
        wg_wait<0>();
        reg_fence(acc);
        {
          if (!MW0 && !rel && ltid == 256) mbar_arrive(BAR(B_ME + 15 % NR));
          TLS(288, 71);
          const float v0 = bf_round(fmaf(-__uint_as_float(s0.x), acc[4], acc[0]) * __uint_as_float(s0.y));
          const float v1 = bf_round(fmaf(-__uint_as_float(s1.x), acc[4], acc[1]) * __uint_as_float(s1.y));
          const float v2 = bf_round(fmaf(-__uint_as_float(s0.x), acc[6], acc[2]) * __uint_as_float(s0.y));
          const float v3 = bf_round(fmaf(-__uint_as_float(s1.x), acc[6], acc[3]) * __uint_as_float(s1.y));
          if (rank) {
            asm volatile("{\n.reg .b32 ra, rb;\nmapa.shared::cluster.u32 ra, %0, 0;\nmapa.shared::cluster.u32 rb, %1, 0;\n"
                         "st.async.weak.shared::cluster.mbarrier::complete_tx::bytes.v4.f32 [ra], {%2, %3, %4, %5}, [rb];\n}"
                         ::"r"(mbuf + (ltid - 256) * 16), "r"(BAR(B_UP)), "f"(v0), "f"(v1), "f"(v2), "f"(v3) : "memory");
          } else {
            const float g0 = bf_round(v0 * sigmoid(v0)), g1 = bf_round(v1 * sigmoid(v1)), g2 = bf_round(v2 * sigmoid(v2)), g3 = bf_round(v3 * sigmoid(v3));
            mbar_wait(BAR(B_UP), 0);
            const uint4 uu = lds_u4(mbuf + (ltid - 256) * 16);
            const uint32_t h0 = movmat(pack_bf16(g0 * __uint_as_float(uu.x), g1 * __uint_as_float(uu.y)));
            const uint32_t h1 = movmat(pack_bf16(g2 * __uint_as_float(uu.z), g3 * __uint_as_float(uu.w)));
            uint32_t* ph = G.h + (u >> 1) * 256 + g * 32 + t;
            stx1(ph + ((2 * aw) ^ g) * 4, h0); stx1(ph + ((2 * aw + 1) ^ g) * 4, h1);
          }
          TLS(288, 60);
        }
      }
    }
    if (PH) asm volatile("bar.arrive 3, 192;" ::: "memory");
    {
      const int wd_ = ltid & 63;
      const uint32_t* src = reinterpret_cast<const uint32_t*>(G.part + hg * 544 + (aw >> 1) * 256 + tb * 16) + wd_;
      mbar_wait(MRED == 2 ? BAR(B_ZOK) : BAR(B_EQ + MRW), 0);
      if (MRC) spin_cycles(MRC); else if (MRD) __nanosleep(MRD);
      TLS(256, 48);
      uint32_t v[16];
#pragma unroll 1
      for (uint32_t it = 0; it < SPIN_MAX; it++) {
        uint32_t m = 0;
#pragma unroll
        for (int i = 0; i < 16; i++) v[i] = ldx1(src + i * 8 * 2176);
#pragma unroll
        for (int i = 0; i < 16; i++) m = max(m, v[i]);
        if (!__any_sync(~0u, m == SENT)) break;
      }
      TLS(256, 55);
      float lo[4], hi[4];
#pragma unroll
      for (int i = 0; i < 4; i++) {
        lo[i] = (bf_lo(v[4 * i]) + bf_lo(v[4 * i + 1])) + (bf_lo(v[4 * i + 2]) + bf_lo(v[4 * i + 3]));
        hi[i] = (bf_hi(v[4 * i]) + bf_hi(v[4 * i + 1])) + (bf_hi(v[4 * i + 2]) + bf_hi(v[4 * i + 3]));
      }
      stx1(reinterpret_cast<uint32_t*>(G.fin + hg * 640) + (tb >> 2) * 640 + ((tb >> 1) & 1) * 64 + (tb & 1) * 16 + (aw >> 1) * 32 + ((wd_ >> 2) & 3) * 128 + (wd_ >> 4) * 4 + (wd_ & 3),
           pack_bf16((lo[0] + lo[1]) + (lo[2] + lo[3]), (hi[0] + hi[1]) + (hi[2] + hi[3])));
      TLS(256, 5);
    }
    if (NUNIT) {
      mbar_wait(BAR(B_STG), 0);
      bar_sync<2, 128>();
      if (HW) __nanosleep(HW);
#pragma unroll 1
      for (uint32_t it = 0; it < SPIN_MAX; it++) {
        if (elect_one()) {
          const uint32_t* ph = G.h + (u >> 4) * 7 * 256;
          if (aw == 3) { mbar_expect_tx(BAR(B_HF), 7168); bulk_ld(sb + h_off(3), ph + 768, 2048, BAR(B_HF)); bulk_ld(sb + h_off(5), ph + 1280, 2048, BAR(B_HF)); }
          else bulk_ld(stg + aw * MT + 8192, ph + aw * 256, 1024, BAR(B_HF));
        }
        mbar_wait(BAR(B_HF), it & 1);
        const uint32_t o = (ltid & 63) * 16 + (g >> 1) * 4, o2 = o + (aw >> 1) * 1024;
        const uint32_t m = max(max(lds_u(sb + h_off(0) + (aw >> 1) * MT + o), lds_u(sb + h_off(2) + o)), max(lds_u(sb + h_off(3) + o2), lds_u(sb + h_off(5) + o2)));
        uint32_t bad;
        asm volatile("{\n.reg .pred p, q;\nsetp.eq.u32 p, %1, 0xFFFFFFFF;\nbar.red.or.pred q, 2, 128, p;\nselp.b32 %0, 1, 0, q;\n}" : "=r"(bad) : "r"(m) : "memory");
        if (!__any_sync(~0u, bad)) break;
        __nanosleep(POLLNS);
      }
      TLS(288, 62);
      float acc[4] = {0.f, 0.f, 0.f, 0.f};
      mbar_wait(BAR(B_DF), 0);
      TLS(288, 63);
#pragma unroll 1
      for (int i = 0; i < 7; i++) {
        const uint32_t da = (d0 + (d_off(i) >> 4)) | (512u << 16), db = (d0 + (h_off(i) >> 4)) | (1u << 16);
        wg_fence();
#pragma unroll
        for (int kk = 0; kk < ((MX & 4) ? 1 : 4); kk++) wgmma_ss_n8<1, 0>(acc, mkdesc(da + kk * 128, HI_SW128), mkdesc(db + kk * 2, HI_SW128));
        wg_commit();
      }
      wg_wait<0>();
      reg_fence(acc);
      if (ltid < 258) { if (MC) mbar_arrive_cta(BAR(B_DE), ltid & 1); else mbar_arrive(BAR(B_DE)); }
      {
        uint32_t* py = reinterpret_cast<uint32_t*>(G.y) + u * 512 + t * 128 + aw * 16 + g;
        stx1(py, f2x(acc[0])); stx1(py + 64, f2x(acc[1])); stx1(py + 8, f2x(acc[2])); stx1(py + 72, f2x(acc[3]));
      }
      TLS(288, 69);
      const uint32_t key = lds_u(sb + MISC + M_IDX + (lane & 7) * 4);
      uint32_t rb = (key >> 11) & 0xFFFFu;
      rb = (rb & 0x8000u) ? (rb & 0x7FFFu) : (~rb & 0xFFFFu);
      const float sg = bf_round(sigmoid(__uint_as_float(rb << 16)));
      uint32_t hits = __ballot_sync(~0u, ((~key >> 7) & 15) == tb) & 255u;
      const uint32_t* py = reinterpret_cast<const uint32_t*>(G.y) + (2 * hg + (aw >> 1)) * 512 + (ltid & 63);
      if (hits) {
        sts_u4(mbuf + (ltid - 256) * 16, make_uint4(0, 0, 0, 0));
        bar_sync<2, 128>();
        if (YW >= 0) mbar_wait(BAR(B_EO + YW), 0); else if (YW == -2) mbar_wait(BAR(B_EAUX), 0);
      }
#pragma unroll 1
      while (hits) {
        const int n0 = __ffs(hits) - 1;
        hits &= hits - 1;
        const int n1 = hits ? __ffs(hits) - 1 : n0;
        hits &= hits - 1;
        uint32_t v[16];
#pragma unroll 1
        for (uint32_t it = 0; it < SPIN_MAX; it++) {
          uint32_t m = 0;
#pragma unroll
          for (int i = 0; i < 8; i++) { v[i] = ldx1(py + n0 * 64 + i * 8192); v[8 + i] = ldx1(py + n1 * 64 + i * 8192); }
#pragma unroll
          for (int i = 0; i < 16; i++) m = max(m, v[i]);
          if (!__any_sync(~0u, m == SENT)) break;
          __nanosleep(POLLNS);
        }
#pragma unroll
        for (int e = 0; e < 2; e++) {
          const uint32_t* w8 = v + 8 * e;
          const float y = ((__uint_as_float(w8[0]) + __uint_as_float(w8[1])) + (__uint_as_float(w8[2]) + __uint_as_float(w8[3]))) +
                          ((__uint_as_float(w8[4]) + __uint_as_float(w8[5])) + (__uint_as_float(w8[6]) + __uint_as_float(w8[7])));
          const int n = e ? n1 : n0;
          sts_h(mbuf + (aw >> 1) * 1024 + n * 128 + ((((ltid >> 3) & 7) ^ n) << 4) + (lane & 7) * 2, bf_round(y) * __shfl_sync(~0u, sg, n));
        }
      }
    }
    if (!NUNIT && ltid < 258) mbar_arrive(BAR(B_DE));
    fence_async_smem();
    bar_sync<2, 128>();
    TLS(288, 33);
    if (ltid == 288) mbar_arrive(BAR(B_MOE));
  } else {
    asm volatile("setmaxnreg.inc.sync.aligned.u32 %0;" ::"n"(CON_REGS));
    if (MC) asm volatile("barrier.cluster.wait.aligned;" ::: "memory");
    const int w = warp >> 2, wq = warp & 3, tid = ltid;
    const bool lead = (tid & 127) == 0;
    const uint32_t dA = (d0 + w * 512) | (1u << 16);
    const uint32_t dB = d0 | (512u << 16);
    auto release = [&](int bar) { if (lead) mbar_arrive(BAR(bar)); };
    auto release2 = [&](int bar) {
      if (MC) { if ((tid & 127) < 2) mbar_arrive_cta(BAR(bar), tid & 1); } else release(bar);
    };
    float aq[64], ak[64], av[64];
#pragma unroll
    for (int i = 0; i < 64; i++) aq[i] = ak[i] = av[i] = 0.f;
    auto q_step = [&](uint32_t bar, int p, uint32_t xs, uint32_t qs) {
      mbar_wait_b(bar, p);
      wg_fence();
#pragma unroll
      for (int kk = 0; kk < 4; kk++)
        wgmma_ss_n128<0, 1>(aq, mkdesc(dA + xs * 1024 + kk * 2, HI_SW128), mkdesc(dB + qs * 1024 + kk * 128, HI_SW128));
      wg_commit();
    };
    const uint32_t dT = dB + w * 512, dX = d0 | (1u << 16);
    auto t_step = [&](float (&a)[64], uint32_t ws, uint32_t xs) {
      wg_fence();
#pragma unroll
      for (int kk = 0; kk < 4; kk++)
        wgmma_ss_n128<1, 0>(a, mkdesc(dT + ws * 1024 + kk * 128, HI_SW128), mkdesc(dX + xs * 1024 + kk * 2, HI_SW128));
      wg_commit();
    };
    {
      int s = 0, p = 0, sp = 2;
#pragma unroll 1
      for (int e = 0; e < NF; e++) {
        TLS(0, 16 + e);
        if (((MS && MS < NF) || (DS && DS < NF)) && e == (MS ? MS : DS)) release(B_MS);
        q_step(BAR(B_FXQ + s), p, s, 3 + s);
        wg_wait<1>();
        if (e > 0) release2(B_E + sp);
        mbar_wait(BAR(B_FKV + s), p);
        t_step(ak, 6 + 2 * s, s);
        if (R5) mbar_wait(BAR(B_FV + s), p);
        t_step(av, 7 + 2 * s, s);
        if (R5 && e == NF - 1) { wg_wait<1>(); release2(B_EK + s); }
        sp = s;
        if (++s == 3) { s = 0; p ^= 1; }
      }
#pragma unroll 1
      for (int e = NF; e < 16; e++) {
        TLS(0, 16 + e);
        if (((MS >= NF && MS < 16) || DS >= NF) && e == (MS ? MS : DS)) release(B_MS);
        if (ST && e == 16 - ST && w == 1) mbar_wait(BAR(B_GT), 0);
        mbar_wait(BAR(B_FXQ + s), p);
        mbar_wait(BAR(B_FKV + s), p);
        t_step(ak, R5 ? (K_SLOTS >> (4 * (e - 10))) & 15u : 6 + 2 * s, x_slot(e, s));
        wg_wait<1>();
        release2(B_E + sp);
        if (R5) mbar_wait(BAR(B_FV + s), p);
        t_step(av, R5 ? (V_SLOTS >> (4 * (e - 10))) & 15u : 7 + 2 * s, x_slot(e, s));
        if (ST && e == 15 && tid == 0) mbar_arrive(BAR(B_GT));
        if (R5) { wg_wait<1>(); release2(B_EK + s); }
        sp = s;
        if (++s == 3) { s = 0; p ^= 1; }
      }
    }
    const uint32_t aux = sb;
    mbar_wait(BAR(B_FAUX), 0);
    const int row0 = w * 64 + wq * 16 + g;
    const float ck0 = lds_f(aux + A_CS + 512 + row0 * 4), ck1 = lds_f(aux + A_CS + 512 + (row0 + 8) * 4);
    const float cv0 = lds_f(aux + A_CS + 1024 + row0 * 4), cv1 = lds_f(aux + A_CS + 1024 + (row0 + 8) * 4);
    const uint32_t moff = (uint32_t)(w * 64 + wq * 16 + (lane & 15)) * 128 + (((lane >> 4) ^ (lane & 7)) << 4);
    const uint32_t sta = aux + A_ST + t * 16;
    float kvp[36], ao[64];
    uint32_t xr[32];
    float nm0, nm1, rs0, rs1, rl0, rl1;
    auto row_stats = [&]() {
      const float2 st0 = lds_f2(aux + A_ST + row0 * 8), st1 = lds_f2(aux + A_ST + (row0 + 8) * 8);
      nm0 = -st0.x; nm1 = -st1.x;
      if (SL2) { rl0 = st0.y; rl1 = st1.y; rs0 = rl0 * LN2; rs1 = rl1 * LN2; }
      else { rs0 = st0.y; rs1 = st1.y; rl0 = rs0 * LOG2E; rl1 = rs1 * LOG2E; }
    };
    auto ld_x = [&]() {
#pragma unroll
      for (int j = 0; j < 16; j += 2) ldsm4(sb + (j < 8 ? SX14 : SX15) * SLOT + (moff ^ ((j & 7) << 4)), xr[2 * j], xr[2 * j + 1], xr[2 * j + 2], xr[2 * j + 3]);
    };
    auto resid = [&]() {
      const float c0 = 1.f + rs0, c1 = 1.f + rs1, e0 = nm0 * rs0, e1 = nm1 * rs1;
#pragma unroll
      for (int j = 0; j < 16; j++) {
        ao[4 * j + 0] = fmaf(bf_lo(xr[2 * j]), c0, e0); ao[4 * j + 1] = fmaf(bf_hi(xr[2 * j]), c0, e0);
        ao[4 * j + 2] = fmaf(bf_lo(xr[2 * j + 1]), c1, e1); ao[4 * j + 3] = fmaf(bf_hi(xr[2 * j + 1]), c1, e1);
      }
    };
    {
      uint32_t pa[32];
      float4 st[16];
      auto ld = [&](int j) { st[j] = lds_f4(sta + j * 64); };
      auto k_blk = [&](int c) {
#pragma unroll
        for (int i = 0; i < 2; i++) {
          const float4 u = st[2 * c + i];
          const float l0 = u.y * LOG2E, l1 = u.w * LOG2E;
          const float* a = ak + 8 * c + 4 * i;
          pa[4 * c + 2 * i] = SL2 ? phi2l(fmaf(-u.x, ck0, a[0]), u.y, fmaf(-u.z, ck0, a[1]), u.w) : phi2<(VOL & 1) != 0>(fmaf(-u.x, ck0, a[0]), u.y, l0, fmaf(-u.z, ck0, a[1]), u.w, l1);
          pa[4 * c + 2 * i + 1] = SL2 ? phi2l(fmaf(-u.x, ck1, a[2]), u.y, fmaf(-u.z, ck1, a[3]), u.w) : phi2<(VOL & 1) != 0>(fmaf(-u.x, ck1, a[2]), u.y, l0, fmaf(-u.z, ck1, a[3]), u.w, l1);
        }
      };
      const uint32_t voff = sb + w * 8192 + (uint32_t)(8 * (lane >> 4) + (lane & 7)) * 128 + (((2 * wq + ((lane >> 3) & 1)) ^ (lane & 7)) << 4);
      auto v_blk = [&](int c) {
        uint32_t r[4];
#pragma unroll
        for (int i = 0; i < 2; i++) {
          const float4 u = st[2 * c + i];
          const float* a = av + 8 * c + 4 * i;
          r[2 * i] = pack_bf16(fmaf(-u.x, cv0, a[0]) * u.y, fmaf(-u.z, cv0, a[1]) * u.w);
          r[2 * i + 1] = pack_bf16(fmaf(-u.x, cv1, a[2]) * u.y, fmaf(-u.z, cv1, a[3]) * u.w);
        }
        stsm4t(voff + (c < 4 ? S_V0 : S_V1) * SLOT + (c & 3) * 2048, r[0], r[1], r[2], r[3]);
      };
      auto kv_mma = [&](int c) {
        const uint32_t bo = (c < 4 ? S_V0 : S_V1) * 1024 + w * 512 + (c & 3) * 128;
        const uint64_t bb = mkdesc((d0 + bo) | (((A_ONES >> 4) - bo) << 16), HI_SW128);
        if (c == 0) wgmma_rz_n72<1>(kvp, pa[4 * c], pa[4 * c + 1], pa[4 * c + 2], pa[4 * c + 3], bb);
        else wgmma_rs_n72<1>(kvp, pa[4 * c], pa[4 * c + 1], pa[4 * c + 2], pa[4 * c + 3], bb);
      };
      ld(0); ld(1);
      wg_wait<0>();
      reg_fence(ak); reg_fence(av);
      TLS(0, 2);
      if (!R5) release2(B_E);
      release(B_T0);
      if (LQ) { v_blk(0); ld(2); ld(3); } else { ld(2); ld(3); v_blk(0); }
      ld(4); ld(5); v_blk(1); k_blk(0);
      ld(6); ld(7); v_blk(2); ld(8); ld(9); v_blk(3); k_blk(1);
      ld(10); ld(11); v_blk(4); ld(12); ld(13); v_blk(5); k_blk(2);
      ld(14); ld(15); v_blk(6); v_blk(7); k_blk(3);
      if (RL) { ld(8); ld(9); }
#pragma unroll
      for (int c = 4; c < KS; c++) k_blk(c);
      TLS(0, 3);
      fence_async_smem();
      asm volatile("bar.sync %0, 128;" ::"r"(3 + w) : "memory");
      if (XP == 0) ld_x();
      wg_fence();
#pragma unroll
      for (int c = 0; c < KS; c++) kv_mma(c);
      wg_commit();
#pragma unroll
      for (int c = KS; c < 8; c++) {
        if (RL && c < 7) { ld(2 * c + 2); ld(2 * c + 3); }
        k_blk(c);
        wg_fence();
        kv_mma(c);
        wg_commit();
      }
      if (XP == 3 && (RK == 0 || RK == 9)) ld_x();
      if (QE) { q_step(BAR(B_FQ), 0, SXQ0, QW_SLOTS & 15u); wg_wait<1>(); } else wg_wait<0>();
      reg_fence(kvp);
      auto hand_back = [&]() { release2(B_STG); __syncwarp(); };
      if (!SF) hand_back();
      TLS(0, 4);
      uint4* pp = G.part + b * 544;
      uint32_t pk[8];
#pragma unroll
      for (int j = 0; j < 8; j++) pk[j] = wq >= 2 ? pack_bf16(kvp[16 + 2 * j], kvp[17 + 2 * j]) : pack_bf16(kvp[2 * j], kvp[2 * j + 1]);
      stx4(pp + tid, pk[0], pk[2], pk[4], pk[6]);
      stx4(pp + 256 + tid, pk[1], pk[3], pk[5], pk[7]);
      if (t == 0) stx2(reinterpret_cast<uint2*>(pp + 512) + (tid >> 2), f2x(kvp[32]), f2x(kvp[34]));
      if (SF == 1) hand_back();
      if (XP == 1) ld_x();
      if (!QE) q_step(BAR(B_FQ), 0, SXQ0, QW_SLOTS & 15u);
      if (XP == 2) ld_x();
      if (SF == 2) hand_back();
      if (RK == 0 || RK == 9) {
        uint32_t chk = 0;
#pragma unroll
        for (int j = 0; j < 8; j++) chk ^= xr[4 * j];
        asm volatile("{\n.reg .pred p;\nsetp.eq.u32 p, %0, 0x7FC17FC3;\n@p st.shared.u32 [%1], %0;\n}" ::"r"(chk), "r"(sb + MISC + M_DUM) : "memory");
      }
      const int wd_ = wq * 16 + (lane & 15);
      const uint32_t* src = reinterpret_cast<const uint32_t*>(G.part + ((lane >> 4) * 64 + hg) * 544 + w * 256 + tb * 16) + wd_;
      uint32_t* fin = reinterpret_cast<uint32_t*>(G.fin + hg * 640) + (tb >> 2) * 640 + ((tb >> 1) & 1) * 64 + (tb & 1) * 16 + w * 32 + ((wd_ >> 2) & 3) * 128 + wq * 4 + (wd_ & 3);
      uint32_t v[8];
      auto part_load = [&]() {
#pragma unroll
        for (int i = 0; i < 8; i++) v[i] = ldx1(src + i * 8 * 2176);
      };
#pragma unroll
      for (int k = 1; k < NQ; k++) {
        if (SQ && k == NQ - SQ && w == 1) mbar_wait(BAR(B_GQ), 0);
        q_step(BAR(B_FQ + k), 0, (QX_SLOTS >> (4 * k)) & 15u, (QW_SLOTS >> (4 * k)) & 15u);
        if (SQ && k == NQ - 1 && tid == 0) mbar_arrive(BAR(B_GQ));
        TLS(0, 48 + k);
        if (!MRED && k == PLP) part_load();
        if (!MRED && k == PLC) {
#pragma unroll 1
          for (uint32_t it = 0; it < SPIN_MAX; it++) {
            if (!__any_sync(~0u, max(max(max(v[0], v[1]), max(v[2], v[3])), max(max(v[4], v[5]), max(v[6], v[7]))) == SENT)) break;
            part_load();
          }
          float lo = ((bf_lo(v[0]) + bf_lo(v[1])) + (bf_lo(v[2]) + bf_lo(v[3]))) + ((bf_lo(v[4]) + bf_lo(v[5])) + (bf_lo(v[6]) + bf_lo(v[7])));
          float hi = ((bf_hi(v[0]) + bf_hi(v[1])) + (bf_hi(v[2]) + bf_hi(v[3]))) + ((bf_hi(v[4]) + bf_hi(v[5])) + (bf_hi(v[6]) + bf_hi(v[7])));
          lo += __shfl_xor_sync(~0u, lo, 16); hi += __shfl_xor_sync(~0u, hi, 16);
          if (lane < 16) stx1(fin, pack_bf16(lo, hi));
          TLS(0, 5);
        }
        wg_wait<1>();
        release2(B_EQ + k - 1);
        if (k == RK) { row_stats(); ld_x(); resid(); reg_fence(ao); }
      }
      TLS(0, 13);
      mbar_wait(BAR(B_CQ), 0);
    }
    wg_wait<0>();
    reg_fence(aq);
    TLS(0, 15);
    if (RK == 0 || RK == 9) row_stats();
    uint32_t pq[32];
#pragma unroll
    for (int j = 0; j < 16; j += 2) {
      float4 c4;
      if (CQ4) c4 = lds_f4(aux + A_CS + (j * 8 + 4 * t) * 4);
      else { const float2 ca = lds_f2(aux + A_CS + (j * 8 + 2 * t) * 4), cb = lds_f2(aux + A_CS + (j * 8 + 8 + 2 * t) * 4); c4 = make_float4(ca.x, ca.y, cb.x, cb.y); }
#pragma unroll
      for (int i = 0; i < 2; i++) {
        const float cx = i ? c4.z : c4.x, cy = i ? c4.w : c4.y;
        const float* a = aq + 4 * (j + i);
        pq[2 * (j + i)] = SL2 ? phi2l(fmaf(nm0, cx, a[0]), rl0, fmaf(nm0, cy, a[1]), rl0) : phi2<(VOL & 2) != 0>(fmaf(nm0, cx, a[0]), rs0, rl0, fmaf(nm0, cy, a[1]), rs0, rl0);
        pq[2 * (j + i) + 1] = SL2 ? phi2l(fmaf(nm1, cx, a[2]), rl1, fmaf(nm1, cy, a[3]), rl1) : phi2<(VOL & 2) != 0>(fmaf(nm1, cx, a[2]), rs1, rl1, fmaf(nm1, cy, a[3]), rs1, rl1);
      }
    }
    TLS(0, 6);
    if (RK == 9) { resid(); if (RF) reg_fence(ao); }
    mbar_wait_b(BAR(MFIN ? B_KV4 : B_KVB), 0);
    TLS(0, 7);
    uint32_t of[32];
    uint4* mine = G.o + (tb * 32 + hg) * 512 + warp * 64 + g * 4 + (t ^ (g >> 1));
    const uint32_t dW = d0 | (256u << 16);
    auto o_store = [&](int h) {
#pragma unroll
      for (int c = 0; c < 2; c++) stx4(mine + h * 4096 + c * 32, of[8 * h + c], of[8 * h + 2 + c], of[8 * h + 4 + c], of[8 * h + 6 + c]);
    };
    auto out_step = [&](uint32_t slot, const uint32_t* a) {
      const uint32_t d = dW + slot * 1024;
      wg_fence();
#pragma unroll
      for (int kk = 0; kk < 4; kk++) wgmma_rs_n128<1>(ao, a[4 * kk], a[4 * kk + 1], a[4 * kk + 2], a[4 * kk + 3], mkdesc(d + (kk >> 1) * 512 + (kk & 1) * 128, HI_SW128));
      wg_commit();
    };
    uint4 v[NDIR][4];
    auto ld_o = [&](int k) {
      const uint4* p0 = mine + (slab(2 * k, hg) - hg) * 512;
      const uint4* p1 = mine + (slab(2 * k + 1, hg) - hg) * 512;
      v[k][0] = ldx4(p0); v[k][1] = ldx4(p0 + 32); v[k][2] = ldx4(p1); v[k][3] = ldx4(p1 + 32);
    };
    auto ld_all = [&]() {
#pragma unroll
      for (int k = 0; k < NDIR; k++) ld_o(k);
    };
    {
      float oa[4][20];
      const uint32_t dK = (d0 + S_KVB * 1024) | (8u << 16);
      wg_fence();
#pragma unroll
      for (int h = 0; h < 4; h++) {
        wgmma_rz_n40<1>(oa[h], pq[8 * h], pq[8 * h + 1], pq[8 * h + 2], pq[8 * h + 3], mkdesc(dK + h * 160, HI_NOSW));
        wgmma_rs_n40<1>(oa[h], pq[8 * h + 4], pq[8 * h + 5], pq[8 * h + 6], pq[8 * h + 7], mkdesc(dK + h * 160 + 16, HI_NOSW));
        if (h == 0 || h == 3) wg_commit();
      }
      auto norm = [&](int h) {
        const float r0 = SL2 ? rcp(fmaf(oa[h][16], LOG2E, 1e-6f * LOG2E)) : rcp(oa[h][16] + 1e-6f);
        const float r1 = SL2 ? rcp(fmaf(oa[h][18], LOG2E, 1e-6f * LOG2E)) : rcp(oa[h][18] + 1e-6f);
#pragma unroll
        for (int j = 0; j < 4; j++) {
          of[8 * h + 2 * j] = pack_bf16(oa[h][4 * j] * r0, oa[h][4 * j + 1] * r0);
          of[8 * h + 2 * j + 1] = pack_bf16(oa[h][4 * j + 2] * r1, oa[h][4 * j + 3] * r1);
        }
      };
      wg_wait<1>();
      reg_fence(oa[0]);
      norm(0);
      if (LE == 4) ld_all();
      o_store(0);
      if (LE == 3) ld_all();
      TLS(0, 8);
      wg_wait<0>();
      reg_fence(oa[1]); reg_fence(oa[2]); reg_fence(oa[3]);
      TLP_(0);
      release(B_EAUX);
      norm(1);
      if (OS1 == 3) o_store(1);
      if (E7 && NP == 0 && SL7 && hg == 7) o_store(1);
      if (NP == 0) { norm(2); norm(3); }
      if (E7 && NP == 0 && SL7 && hg == 7) { o_store(2); o_store(3); }
      TLP_(1);
      mbar_wait_b(BAR(B_FWO), 0);
      TLP_(2);
      if (RK == 0) resid();
      if (LE == 2) ld_all();
      TLP_(3);
      out_step(WO_SLOTS & 15u, of);
      TLP_(4);
      if (NP == 1) { norm(2); norm(3); }
      if (LE == 1) ld_all();
      if (LE == 5) ld_o(0);
    }
    if (OS1 == 0) o_store(1);
    mbar_wait(BAR(B_FWO + 1), 0);
    TLP_(5);
    out_step((WO_SLOTS >> 4) & 15u, of + 16);
    TLP_(6);
    const bool early = SL7 && hg == 7;
    if (OS1 == 1 && !(E7 && early)) o_store(1);
    TLP_(7);
    if (early && !E7) { o_store(2); o_store(3); }
    {
      if (DW) __nanosleep(DW);
      if (LE == 0) ld_all();
      if (LE == 5 && NDIR > 1) ld_o(NDIR - 1);
      if (OS1 == 2 && !(E7 && early)) o_store(1);
#pragma unroll
      for (int k = 0; k < NDIR; k++) {
#pragma unroll 1
        for (uint32_t it = 0; it < SPIN_MAX; it++) {
          if (!__any_sync(~0u, max(max(v[k][0].x, v[k][1].x), max(v[k][2].x, v[k][3].x)) == SENT)) break;
#pragma unroll
          for (int j = k; j < (LE == 5 ? k + 1 : NDIR); j++) ld_o(j);
        }
        TLP_(8);
        const uint32_t a[16] = {v[k][0].x, v[k][1].x, v[k][0].y, v[k][1].y, v[k][0].z, v[k][1].z, v[k][0].w, v[k][1].w,
                                v[k][2].x, v[k][3].x, v[k][2].y, v[k][3].y, v[k][2].z, v[k][3].z, v[k][2].w, v[k][3].w};
        mbar_wait(BAR(B_FWO + 2 + k), 0);
        TLS(0, 34 + k);
        out_step((WO_SLOTS >> (8 + 4 * k)) & 15u, a);
        TLP_(9);
        if (k) { wg_wait<1>(); release2(B_EO); }
      }
      if (!early) o_store(2);
    }
    auto routed = [&]() {
      mbar_wait(BAR(B_MOE), 0);
      const float2 kk = lds_f2(sb + MISC + M_IDX + t * 8);
      const int k0 = (int)(~__float_as_uint(kk.x) & 2047u) - tb * 128, k1 = (int)(~__float_as_uint(kk.y) & 2047u) - tb * 128;
      if (NUNIT && __any_sync(~0u, (k0 >> 6) == w || (k1 >> 6) == w)) {
        const uint32_t a0 = (k0 == row0 ? 0x3F80u : 0u) | (k1 == row0 ? 0x3F800000u : 0u);
        const uint32_t a1 = (k0 == row0 + 8 ? 0x3F80u : 0u) | (k1 == row0 + 8 ? 0x3F800000u : 0u);
        wg_fence();
        wgmma_rs_n128<1>(ao, a0, a1, 0u, 0u, mkdesc((d0 + ((MISC + M_MOE) >> 4)) | (64u << 16), 0x40000000u));
        wg_commit();
      }
    };
    auto out_half = [&](int h, const float* v) {
      const uint32_t ost = sb + (w ? S_D1 : S_D0) * SLOT + wq * 4096 + h * 2048;
#pragma unroll
      for (int j = 0; j < 8; j += 2)
        stsm4(ost + ((moff & 2047) ^ (j << 4)), pack_bf16(v[4 * j], v[4 * j + 1]), pack_bf16(v[4 * j + 2], v[4 * j + 3]),
              pack_bf16(v[4 * j + 4], v[4 * j + 5]), pack_bf16(v[4 * j + 6], v[4 * j + 7]));
      if (OUTV == 3 || (OUTV == 4 && h == 0)) {
        __syncwarp();
        __nv_bfloat16* dst = outp + (size_t)(tb * 128 + warp * 16 + (lane >> 3)) * DM + hg * 128 + h * 64 + (lane & 7) * 8;
#pragma unroll
        for (int i = 0; i < 4; i++) {
          const int r = 4 * i + (lane >> 3);
          const uint4 u4 = lds_u4(ost + r * 128 + (((lane & 7) ^ (r & 7)) << 4));
          asm volatile("st.global.v4.u32 [%0], {%1,%2,%3,%4};" ::"l"(dst + (size_t)i * 4 * DM), "r"(u4.x), "r"(u4.y), "r"(u4.z), "r"(u4.w) : "memory");
        }
        return;
      }
      fence_async_smem();
      __syncwarp();
      if (elect_one()) {
        if (OEF) asm volatile("cp.async.bulk.tensor.2d.global.shared::cta.bulk_group.L2::cache_hint [%0, {%2, %3}], [%1], %4;" ::"l"(&tmOut), "r"(ost), "r"(hg * 128 + h * 64), "r"(tb * 128 + warp * 16), "l"(POL_FIRST) : "memory");
        else asm volatile("cp.async.bulk.tensor.2d.global.shared::cta.bulk_group [%0, {%2, %3}], [%1];" ::"l"(&tmOut), "r"(ost), "r"(hg * 128 + h * 64), "r"(tb * 128 + warp * 16) : "memory");
        if (h) asm volatile("cp.async.bulk.commit_group;\ncp.async.bulk.wait_group.read 0;" ::: "memory");
      }
      __syncwarp();
    };
    bool done = false;
    {
      const uint32_t dO = (d0 + w * 256) | (1u << 16);
      auto step = [&](int i, int r, int p, uint32_t as, uint32_t ws) {
        mbar_wait(BAR(B_FWO + i), 0);
        mbar_wait(BAR(B_VAL + r), p);
        TLS(0, 32 + i);
        const uint32_t da = dO + as * 1024, db = dW + ws * 1024;
        wg_fence();
#pragma unroll
        for (int kk = 0; kk < 4; kk++)
          wgmma_ss_n128<0, 1>(ao, mkdesc(da + (kk >> 1) * 512 + (kk & 1) * 2, HI_SW64), mkdesc(db + (kk >> 1) * 512 + (kk & 1) * 128, HI_SW128));
        wg_commit();
      };
      uint64_t tbl = WO_SLOTS >> (4 * I0);
      int r = 0, p = 0, rp = 0;
#pragma unroll 1
      for (int i = I0; i < 12; i++) {
        step(i, r, p, (A_SLOTS >> (4 * r)) & 15u, (uint32_t)tbl & 15u);
        tbl >>= 4;
#pragma unroll
        for (int c = 0; c < 2; c++)
          if (i == OS3 + c && !early) stx4(mine + 3 * 4096 + c * 32, of[24 + c], of[26 + c], of[28 + c], of[30 + c]);
        wg_wait<1>();
        if (i > I0) release(B_EA + rp);
        rp = r;
        if (++r == NA) { r = 0; p ^= 1; }
        if (i >= 3 && i <= 9) release2(B_EO + i - 3);
      }
      if (SPL && w == 1) {
        float bl[32], bh[32];
        mbar_wait(BAR(B_GO), 0);
        routed();
#pragma unroll
        for (int h = 0; h < 2; h++) {
#pragma unroll
          for (int i = 12; i < 16; i++) {
            const int r_ = (i - I0) % NA;
            if (h == 0) { mbar_wait(BAR(B_FWO + i), 0); mbar_wait(BAR(B_VAL + r_), ((i - I0) / NA) & 1); }
            const uint32_t da = dO + ((A_SLOTS >> (4 * r_)) & 15u) * 1024, db = dW + ((uint32_t)(WO_SLOTS >> (4 * i)) & 15u) * 1024 + h * 256;
            if (h == 0 || i == 12) wg_fence();
#pragma unroll
            for (int kk = 0; kk < 4; kk++) {
              const uint64_t a = mkdesc(da + (kk >> 1) * 512 + (kk & 1) * 2, HI_SW64), bb = mkdesc(db + (kk >> 1) * 512 + (kk & 1) * 128, HI_SW128);
              if (i == 12 && kk == 0) wgmma_sz_n64<0, 1>(h ? bh : bl, a, bb); else wgmma_ss_n64<0, 1>(h ? bh : bl, a, bb);
            }
          }
          wg_commit();
        }
        wg_wait<1>();
        reg_fence(ao); reg_fence(bl);
#pragma unroll
        for (int j = 0; j < 32; j++) bl[j] += ao[j];
        out_half(0, bl);
        wg_wait<0>();
        reg_fence(bh);
#pragma unroll
        for (int j = 0; j < 32; j++) bh[j] += ao[32 + j];
        out_half(1, bh);
        done = true;
      } else
#pragma unroll
      for (int i = 12; i < 16; i++) {
        if (i == 16 - STAG && w == 1) mbar_wait(BAR(B_GO), 0);
        step(i, (i - I0) % NA, ((i - I0) / NA) & 1, (A_SLOTS >> (4 * ((i - I0) % NA))) & 15u, (uint32_t)(WO_SLOTS >> (4 * i)) & 15u);
        if (STAG && i == 15 - GOE && tid == 0) mbar_arrive(BAR(B_GO));
      }
    }
    if (!done) {
      routed();
      wg_wait<0>();
      reg_fence(ao);
      TLS(0, 10);
      out_half(0, ao);
      out_half(1, ao + 32);
    }
    TLS(0, 11);
    TLS(128, 9);
  }
}

typedef CUresult (*EncFn)(CUtensorMap*, CUtensorMapDataType, cuuint32_t, void*, const cuuint64_t*, const cuuint64_t*, const cuuint32_t*,
                          const cuuint32_t*, CUtensorMapInterleave, CUtensorMapSwizzle, CUtensorMapL2promotion, CUtensorMapFloatOOBfill);

void make_map2(EncFn enc, CUtensorMap* m, void* p, uint64_t rows, uint64_t cols, uint32_t brows, CUtensorMapL2promotion promo) {
  cuuint64_t gd[2] = {cols, rows}, gs[1] = {cols * 2};
  cuuint32_t bd[2] = {64, brows}, es[2] = {1, 1};
  enc(m, CU_TENSOR_MAP_DATA_TYPE_BFLOAT16, 2, p, gd, gs, bd, es, CU_TENSOR_MAP_INTERLEAVE_NONE, CU_TENSOR_MAP_SWIZZLE_128B, promo,
      CU_TENSOR_MAP_FLOAT_OOB_FILL_NONE);
}
void make_map3(EncFn enc, CUtensorMap* m, void* p, uint64_t rows, uint64_t cols, uint32_t brows) {
  cuuint64_t gd[3] = {64, rows, cols / 64}, gs[2] = {cols * 2, 128};
  cuuint32_t bd[3] = {64, brows, 2}, es[3] = {1, 1, 1};
  enc(m, CU_TENSOR_MAP_DATA_TYPE_BFLOAT16, 3, p, gd, gs, bd, es, CU_TENSOR_MAP_INTERLEAVE_NONE, CU_TENSOR_MAP_SWIZZLE_128B,
      CU_TENSOR_MAP_L2_PROMOTION_L2_256B, CU_TENSOR_MAP_FLOAT_OOB_FILL_NONE);
}

}

extern "C" void kernel_launch(void* const* d_in, const int* in_sizes, int n_in, void* d_out, int out_size) {
  static EncFn enc = nullptr;
  static int by_sm = 0;
  if (!enc) {
    void* fn = nullptr;
    cudaDriverEntryPointQueryResult qr;
    cudaGetDriverEntryPoint("cuTensorMapEncodeTiled", &fn, cudaEnableDefault, &qr);
    enc = (EncFn)fn;
    int dev = 0, sms = 0;
    cudaGetDevice(&dev);
    cudaDeviceGetAttribute(&sms, cudaDevAttrMultiProcessorCount, dev);
    by_sm = MAP == 2 && sms == NCTA + NSVC;
    cudaFuncSetAttribute(fused_kernel, cudaFuncAttributeMaxDynamicSharedMemorySize, SMEM_BYTES);
  }
  CUtensorMap tmX, tmW, tmWo, tmOut, tmG, tmU, tmD, tmR, tmWp;
  {
    cuuint64_t gd[5] = {64, 2, 128, 4, 16}, gs[4] = {2048, 16384, 4096, 128};
    cuuint32_t bd[5] = {64, 2, 4, 4, 2}, es[5] = {1, 1, 1, 1, 1};
    enc(&tmWp, CU_TENSOR_MAP_DATA_TYPE_BFLOAT16, 5, d_in[2], gd, gs, bd, es, CU_TENSOR_MAP_INTERLEAVE_NONE, CU_TENSOR_MAP_SWIZZLE_128B,
        CU_TENSOR_MAP_L2_PROMOTION_L2_256B, CU_TENSOR_MAP_FLOAT_OOB_FILL_NONE);
  }
  make_map2(enc, &tmR, d_in[0], SEQ, DM, 1, CU_TENSOR_MAP_L2_PROMOTION_L2_128B);
  make_map2(enc, &tmX, d_in[0], SEQ, DM, 128, XPROMO);
  make_map3(enc, &tmW, d_in[1], DM, 3 * DM, 64);
  make_map3(enc, &tmWo, d_in[2], DM, DM, 32);
  if (OUTV) make_map2(enc, &tmOut, d_out, SEQ, DM, 16, CU_TENSOR_MAP_L2_PROMOTION_L2_128B); else make_map3(enc, &tmOut, d_out, SEQ, DM, 64);
  make_map2(enc, &tmG, d_in[5], DM, FF, 64, MPROMO);
  make_map2(enc, &tmU, d_in[6], DM, FF, 64, MPROMO);
  make_map2(enc, &tmD, d_in[7], FF, DM, 64, MPROMO);
  typedef const __nv_bfloat16* P;
  cudaLaunchConfig_t cfg = {};
  cfg.gridDim = dim3(NCTA + NSVC); cfg.blockDim = dim3(512); cfg.dynamicSmemBytes = SMEM_BYTES; cfg.stream = cudaStreamPerThread;
  cudaLaunchAttribute at[1];
  at[0].id = cudaLaunchAttributeClusterDimension;
  at[0].val.clusterDim.x = 2; at[0].val.clusterDim.y = 1; at[0].val.clusterDim.z = 1;
  cfg.attrs = at; cfg.numAttrs = 1;
  cudaLaunchKernelEx(&cfg, fused_kernel, (P)d_in[0], (P)d_in[1], (P)d_in[2], (P)d_in[4], (P)d_in[7], (__nv_bfloat16*)d_out, by_sm, tmX, tmW, tmWo, tmOut, tmG, tmU, tmD, tmR, tmWp);
}
```

```cpp
#include <cuda_runtime.h>
#include <cuda.h>
#include <cuda_bf16.h>
#include <stdint.h>

#define WK 0
#define NOCQ 0
#define NOFOLD 0
#define FOLD(m, c, a) fmaf(m, c, a)
#define OEF 0
namespace {

template <int TA, int TB> __device__ __forceinline__ void wgmma_ss_n128(float (&d)[64], uint64_t da, uint64_t db) {
  asm volatile("wgmma.mma_async.sync.aligned.m64n128k16.f32.bf16.bf16 "
  "{%0,%1,%2,%3,%4,%5,%6,%7,%8,%9,%10,%11,%12,%13,%14,%15,%16,%17,%18,%19,%20,%21,%22,%23,%24,%25,%26,%27,%28,%29,%30,%31,%32,%33,%34,%35,%36,%37,%38,%39,%40,%41,%42,%43,%44,%45,%46,%47,%48,%49,%50,%51,%52,%53,%54,%55,%56,%57,%58,%59,%60,%61,%62,%63}, "
  "%64, %65, 1, 1, 1, %66, %67;"
  : "+f"(d[0]),"+f"(d[1]),"+f"(d[2]),"+f"(d[3]),"+f"(d[4]),"+f"(d[5]),"+f"(d[6]),"+f"(d[7]),"+f"(d[8]),"+f"(d[9]),"+f"(d[10]),"+f"(d[11]),"+f"(d[12]),"+f"(d[13]),"+f"(d[14]),"+f"(d[15]),"+f"(d[16]),"+f"(d[17]),"+f"(d[18]),"+f"(d[19]),"+f"(d[20]),"+f"(d[21]),"+f"(d[22]),"+f"(d[23]),"+f"(d[24]),"+f"(d[25]),"+f"(d[26]),"+f"(d[27]),"+f"(d[28]),"+f"(d[29]),"+f"(d[30]),"+f"(d[31]),"+f"(d[32]),"+f"(d[33]),"+f"(d[34]),"+f"(d[35]),"+f"(d[36]),"+f"(d[37]),"+f"(d[38]),"+f"(d[39]),"+f"(d[40]),"+f"(d[41]),"+f"(d[42]),"+f"(d[43]),"+f"(d[44]),"+f"(d[45]),"+f"(d[46]),"+f"(d[47]),"+f"(d[48]),"+f"(d[49]),"+f"(d[50]),"+f"(d[51]),"+f"(d[52]),"+f"(d[53]),"+f"(d[54]),"+f"(d[55]),"+f"(d[56]),"+f"(d[57]),"+f"(d[58]),"+f"(d[59]),"+f"(d[60]),"+f"(d[61]),"+f"(d[62]),"+f"(d[63])
  : "l"(da), "l"(db), "n"(TA), "n"(TB));
}
template <int TA, int TB> __device__ __forceinline__ void wgmma_ss_n64(float (&d)[32], uint64_t da, uint64_t db) {
  asm volatile("wgmma.mma_async.sync.aligned.m64n64k16.f32.bf16.bf16 "
  "{%0,%1,%2,%3,%4,%5,%6,%7,%8,%9,%10,%11,%12,%13,%14,%15,%16,%17,%18,%19,%20,%21,%22,%23,%24,%25,%26,%27,%28,%29,%30,%31}, "
  "%32, %33, 1, 1, 1, %34, %35;"
  : "+f"(d[0]),"+f"(d[1]),"+f"(d[2]),"+f"(d[3]),"+f"(d[4]),"+f"(d[5]),"+f"(d[6]),"+f"(d[7]),"+f"(d[8]),"+f"(d[9]),"+f"(d[10]),"+f"(d[11]),"+f"(d[12]),"+f"(d[13]),"+f"(d[14]),"+f"(d[15]),"+f"(d[16]),"+f"(d[17]),"+f"(d[18]),"+f"(d[19]),"+f"(d[20]),"+f"(d[21]),"+f"(d[22]),"+f"(d[23]),"+f"(d[24]),"+f"(d[25]),"+f"(d[26]),"+f"(d[27]),"+f"(d[28]),"+f"(d[29]),"+f"(d[30]),"+f"(d[31])
  : "l"(da), "l"(db), "n"(TA), "n"(TB));
}
template <int TA, int TB> __device__ __forceinline__ void wgmma_sz_n64(float (&d)[32], uint64_t da, uint64_t db) {
  asm volatile("wgmma.mma_async.sync.aligned.m64n64k16.f32.bf16.bf16 "
  "{%0,%1,%2,%3,%4,%5,%6,%7,%8,%9,%10,%11,%12,%13,%14,%15,%16,%17,%18,%19,%20,%21,%22,%23,%24,%25,%26,%27,%28,%29,%30,%31}, "
  "%32, %33, 0, 1, 1, %34, %35;"
  : "=f"(d[0]),"=f"(d[1]),"=f"(d[2]),"=f"(d[3]),"=f"(d[4]),"=f"(d[5]),"=f"(d[6]),"=f"(d[7]),"=f"(d[8]),"=f"(d[9]),"=f"(d[10]),"=f"(d[11]),"=f"(d[12]),"=f"(d[13]),"=f"(d[14]),"=f"(d[15]),"=f"(d[16]),"=f"(d[17]),"=f"(d[18]),"=f"(d[19]),"=f"(d[20]),"=f"(d[21]),"=f"(d[22]),"=f"(d[23]),"=f"(d[24]),"=f"(d[25]),"=f"(d[26]),"=f"(d[27]),"=f"(d[28]),"=f"(d[29]),"=f"(d[30]),"=f"(d[31])
  : "l"(da), "l"(db), "n"(TA), "n"(TB));
}
template <int TB> __device__ __forceinline__ void wgmma_rs_n72(float (&d)[36], uint32_t a0, uint32_t a1, uint32_t a2, uint32_t a3, uint64_t db) {
  asm volatile("wgmma.mma_async.sync.aligned.m64n72k16.f32.bf16.bf16 "
  "{%0,%1,%2,%3,%4,%5,%6,%7,%8,%9,%10,%11,%12,%13,%14,%15,%16,%17,%18,%19,%20,%21,%22,%23,%24,%25,%26,%27,%28,%29,%30,%31,%32,%33,%34,%35}, "
  "{%36,%37,%38,%39}, %40, 1, 1, 1, %41;"
  : "+f"(d[0]),"+f"(d[1]),"+f"(d[2]),"+f"(d[3]),"+f"(d[4]),"+f"(d[5]),"+f"(d[6]),"+f"(d[7]),"+f"(d[8]),"+f"(d[9]),"+f"(d[10]),"+f"(d[11]),"+f"(d[12]),"+f"(d[13]),"+f"(d[14]),"+f"(d[15]),"+f"(d[16]),"+f"(d[17]),"+f"(d[18]),"+f"(d[19]),"+f"(d[20]),"+f"(d[21]),"+f"(d[22]),"+f"(d[23]),"+f"(d[24]),"+f"(d[25]),"+f"(d[26]),"+f"(d[27]),"+f"(d[28]),"+f"(d[29]),"+f"(d[30]),"+f"(d[31]),"+f"(d[32]),"+f"(d[33]),"+f"(d[34]),"+f"(d[35])
  : "r"(a0), "r"(a1), "r"(a2), "r"(a3), "l"(db), "n"(TB));
}
template <int TB> __device__ __forceinline__ void wgmma_rz_n72(float (&d)[36], uint32_t a0, uint32_t a1, uint32_t a2, uint32_t a3, uint64_t db) {
  asm volatile("wgmma.mma_async.sync.aligned.m64n72k16.f32.bf16.bf16 "
  "{%0,%1,%2,%3,%4,%5,%6,%7,%8,%9,%10,%11,%12,%13,%14,%15,%16,%17,%18,%19,%20,%21,%22,%23,%24,%25,%26,%27,%28,%29,%30,%31,%32,%33,%34,%35}, "
  "{%36,%37,%38,%39}, %40, 0, 1, 1, %41;"
  : "=f"(d[0]),"=f"(d[1]),"=f"(d[2]),"=f"(d[3]),"=f"(d[4]),"=f"(d[5]),"=f"(d[6]),"=f"(d[7]),"=f"(d[8]),"=f"(d[9]),"=f"(d[10]),"=f"(d[11]),"=f"(d[12]),"=f"(d[13]),"=f"(d[14]),"=f"(d[15]),"=f"(d[16]),"=f"(d[17]),"=f"(d[18]),"=f"(d[19]),"=f"(d[20]),"=f"(d[21]),"=f"(d[22]),"=f"(d[23]),"=f"(d[24]),"=f"(d[25]),"=f"(d[26]),"=f"(d[27]),"=f"(d[28]),"=f"(d[29]),"=f"(d[30]),"=f"(d[31]),"=f"(d[32]),"=f"(d[33]),"=f"(d[34]),"=f"(d[35])
  : "r"(a0), "r"(a1), "r"(a2), "r"(a3), "l"(db), "n"(TB));
}
template <int TB> __device__ __forceinline__ void wgmma_rs_n40(float (&d)[20], uint32_t a0, uint32_t a1, uint32_t a2, uint32_t a3, uint64_t db) {
  asm volatile("wgmma.mma_async.sync.aligned.m64n40k16.f32.bf16.bf16 "
  "{%0,%1,%2,%3,%4,%5,%6,%7,%8,%9,%10,%11,%12,%13,%14,%15,%16,%17,%18,%19}, "
  "{%20,%21,%22,%23}, %24, 1, 1, 1, %25;"
  : "+f"(d[0]),"+f"(d[1]),"+f"(d[2]),"+f"(d[3]),"+f"(d[4]),"+f"(d[5]),"+f"(d[6]),"+f"(d[7]),"+f"(d[8]),"+f"(d[9]),"+f"(d[10]),"+f"(d[11]),"+f"(d[12]),"+f"(d[13]),"+f"(d[14]),"+f"(d[15]),"+f"(d[16]),"+f"(d[17]),"+f"(d[18]),"+f"(d[19])
  : "r"(a0), "r"(a1), "r"(a2), "r"(a3), "l"(db), "n"(TB));
}
template <int TB> __device__ __forceinline__ void wgmma_rz_n40(float (&d)[20], uint32_t a0, uint32_t a1, uint32_t a2, uint32_t a3, uint64_t db) {
  asm volatile("wgmma.mma_async.sync.aligned.m64n40k16.f32.bf16.bf16 "
  "{%0,%1,%2,%3,%4,%5,%6,%7,%8,%9,%10,%11,%12,%13,%14,%15,%16,%17,%18,%19}, "
  "{%20,%21,%22,%23}, %24, 0, 1, 1, %25;"
  : "=f"(d[0]),"=f"(d[1]),"=f"(d[2]),"=f"(d[3]),"=f"(d[4]),"=f"(d[5]),"=f"(d[6]),"=f"(d[7]),"=f"(d[8]),"=f"(d[9]),"=f"(d[10]),"=f"(d[11]),"=f"(d[12]),"=f"(d[13]),"=f"(d[14]),"=f"(d[15]),"=f"(d[16]),"=f"(d[17]),"=f"(d[18]),"=f"(d[19])
  : "r"(a0), "r"(a1), "r"(a2), "r"(a3), "l"(db), "n"(TB));
}
template <int TB> __device__ __forceinline__ void wgmma_rs_n128(float (&d)[64], uint32_t a0, uint32_t a1, uint32_t a2, uint32_t a3, uint64_t db) {
  asm volatile("wgmma.mma_async.sync.aligned.m64n128k16.f32.bf16.bf16 "
  "{%0,%1,%2,%3,%4,%5,%6,%7,%8,%9,%10,%11,%12,%13,%14,%15,%16,%17,%18,%19,%20,%21,%22,%23,%24,%25,%26,%27,%28,%29,%30,%31,%32,%33,%34,%35,%36,%37,%38,%39,%40,%41,%42,%43,%44,%45,%46,%47,%48,%49,%50,%51,%52,%53,%54,%55,%56,%57,%58,%59,%60,%61,%62,%63}, "
  "{%64,%65,%66,%67}, %68, 1, 1, 1, %69;"
  : "+f"(d[0]),"+f"(d[1]),"+f"(d[2]),"+f"(d[3]),"+f"(d[4]),"+f"(d[5]),"+f"(d[6]),"+f"(d[7]),"+f"(d[8]),"+f"(d[9]),"+f"(d[10]),"+f"(d[11]),"+f"(d[12]),"+f"(d[13]),"+f"(d[14]),"+f"(d[15]),"+f"(d[16]),"+f"(d[17]),"+f"(d[18]),"+f"(d[19]),"+f"(d[20]),"+f"(d[21]),"+f"(d[22]),"+f"(d[23]),"+f"(d[24]),"+f"(d[25]),"+f"(d[26]),"+f"(d[27]),"+f"(d[28]),"+f"(d[29]),"+f"(d[30]),"+f"(d[31]),"+f"(d[32]),"+f"(d[33]),"+f"(d[34]),"+f"(d[35]),"+f"(d[36]),"+f"(d[37]),"+f"(d[38]),"+f"(d[39]),"+f"(d[40]),"+f"(d[41]),"+f"(d[42]),"+f"(d[43]),"+f"(d[44]),"+f"(d[45]),"+f"(d[46]),"+f"(d[47]),"+f"(d[48]),"+f"(d[49]),"+f"(d[50]),"+f"(d[51]),"+f"(d[52]),"+f"(d[53]),"+f"(d[54]),"+f"(d[55]),"+f"(d[56]),"+f"(d[57]),"+f"(d[58]),"+f"(d[59]),"+f"(d[60]),"+f"(d[61]),"+f"(d[62]),"+f"(d[63])
  : "r"(a0), "r"(a1), "r"(a2), "r"(a3), "l"(db), "n"(TB));
}
template <int TA, int TB> __device__ __forceinline__ void wgmma_ss_n8(float (&d)[4], uint64_t da, uint64_t db) {
  asm volatile("wgmma.mma_async.sync.aligned.m64n8k16.f32.bf16.bf16 "
  "{%0,%1,%2,%3}, "
  "%4, %5, 1, 1, 1, %6, %7;"
  : "+f"(d[0]),"+f"(d[1]),"+f"(d[2]),"+f"(d[3])
  : "l"(da), "l"(db), "n"(TA), "n"(TB));
}
template <int TA, int TB> __device__ __forceinline__ void wgmma_ss_n16(float (&d)[8], uint64_t da, uint64_t db) {
  asm volatile("wgmma.mma_async.sync.aligned.m64n16k16.f32.bf16.bf16 "
  "{%0,%1,%2,%3,%4,%5,%6,%7}, "
  "%8, %9, 1, 1, 1, %10, %11;"
  : "+f"(d[0]),"+f"(d[1]),"+f"(d[2]),"+f"(d[3]),"+f"(d[4]),"+f"(d[5]),"+f"(d[6]),"+f"(d[7])
  : "l"(da), "l"(db), "n"(TA), "n"(TB));
}

constexpr int SEQ = 2048, DM = 1024, FF = 3584;
constexpr int NCTA = 128, NSVC = 4;
constexpr int NUNIT = 112;
constexpr uint32_t SLOT = 16384;
constexpr uint32_t MISC = 14 * SLOT;
constexpr uint32_t SMEM_BYTES = MISC + 3072;
constexpr uint32_t M_MOE = 0;
constexpr uint32_t M_BAR = 2048;
constexpr uint32_t M_DUM = 2048 + 1020;
constexpr uint32_t M_IDX = 2048 + 768;
constexpr uint32_t M_KEY = 2048 + 960;
#define R5 1
#define NQ (R5 ? 6 : 5)
constexpr int NF = 16 - NQ, NR = (NQ == 5 || R5) ? 4 : 3;
constexpr int B_FXQ = 0, B_FKV = 3, B_AST = 6, B_MOE = 7, B_MF = 8  , B_CQ = 12, B_XS = 13, B_DF = 14, B_ZOK = 15, B_FWO = 21  , B_FQ = B_FWO - NQ,
              B_UP = 37, B_FIN = 38, B_KVB = 39, B_ME = 40  , B_HF = 44, B_AF = 45  , B_AR = 50  , B_GO = 52,
              B_FAUX = 53, B_EAUX = 54, B_T0 = 55, B_DE = 56, B_EA = 57  , B_VAL = 62  ,
              B_E = 67  , B_STG = 70, B_EQ = 71  , B_EO = 76  , NBAR = 83, B_KV4 = 83, B_MS = 84,
              B_FV = 85  , B_EK = 88  , B_GQ = 91, B_GT = 92;
constexpr uint32_t MT = 9216, A_ONES = 12 * SLOT + 3 * MT, A_CS = A_ONES + 2048, A_ST = A_CS + 1536;
constexpr uint32_t A_TL = MISC + 2048 + 808;
constexpr int S_V0 = R5 ? 7 : 11, S_V1 = R5 ? 9 : 7;
constexpr uint32_t K_SLOTS = 0x8697A8u, V_SLOTS = 0x97A869u;
constexpr int C_B = 0, C_DONE = 32, NCNT = 2;
constexpr uint32_t QX_SLOTS = NQ == 5 ? 0x43102u : 0x354021u;
constexpr uint32_t QW_SLOTS = R5 ? 0xA9786Au : 0xB76A98u;
constexpr uint32_t qx(int k) { return (QX_SLOTS >> (4 * k)) & 15u; }
constexpr uint32_t qw(int k) { return (QW_SLOTS >> (4 * k)) & 15u; }
constexpr uint32_t S_KVB = R5 ? 1 : 8, S_D0 = R5 ? 11 : (NQ == 5 ? 5 : 1), S_D1 = R5 ? 2 : (NQ == 5 ? 11 : 2);
constexpr uint32_t S_M3 = R5 ? 11 : 5;
constexpr int WQ0 = NQ == 5 ? 1 : 3;
constexpr uint32_t wo_slot_c(int i) { return i >= 9 ? wo_slot_c(i - 9) : (i == 7 ? S_D0 : (i == 8 ? S_D1 : (((i & 1) || i + WQ0 == 1) ? qx((i + WQ0) >> 1) : qw((i + WQ0) >> 1)))); }
constexpr uint64_t wo_slots() { uint64_t t = 0; for (int i = 0; i < 16; i++) t |= (uint64_t)wo_slot_c(i) << (4 * i); return t; }
constexpr uint64_t WO_SLOTS = wo_slots();
constexpr uint32_t A_SLOTS = 0xDC000u | (S_KVB << 8) | (qw(NQ - 1) << 4) | qx(NQ - 1);
constexpr uint32_t SX14 = qx(NQ - 2), SX15 = qx(NQ - 1), SXQ0 = qx(0);
#define WOD 2
#define PLC 3
#define RS0 0
#define POLLNS 150
#define MPROMO CU_TENSOR_MAP_L2_PROMOTION_L2_128B
#define MW0 0
#define PFILL 0
#define H2W (NQ - 3)
#define SV0 2
#define SV0A 14
#define SV0B 22
#define ASTE 2
#define PFS 1
#define PFTAB 0x0012222220000ull
#define HW 0
#define DPF 1
#define PROBE 0x8
#define OS1 0
#define YW 0
#define NOVAL 0
#define NDIR 1
#define I0 (2 + NDIR)
#define DW 0
#define NA 5
#define STAG 4
#define GOE 0
#define KEY1 0
#define HYB 0
#define FW 0
#define E1E 1
#define GATE 0
#define SVD 0
#define XPROMO CU_TENSOR_MAP_L2_PROMOTION_L2_128B
#define MC0 3
#define MX 0
#define OUTV 1
#define NP 0
#define FINCP 0
#define DNS 0
#define WOK 99
#define WOD1 2
#define MRED 1
#define MRW -1
#define ST 0
#define RW 0
#define SL2 0
#define CQ4 0
#define CQE 0
#define VOL 0
#define FMC 0
#define KO 0
#define WOP 3
#define WSP 0
#define SH2 0
#define KS 7
#define SQ 2
#define H2D 200
#define MRC 0
#define H2C 0
#define MRD 300
#define STP 0
#define TPNS 50
#define MFIN 0
#define MFD 300
#define SF 1
#define PH MFIN
#define RSL 0
#define OS3 4
#define PLP 2
#define PFNS2 200
#define MAP 2
#define RSNS 60
#define SVS 6
#define MC 7
#define QE 0
#define TMP 1
#define TMPW 4
#define DS 15
#define RL 0
#define EV 0
#define LQ 0
#define SPL 0
#define PHI2 1
#define E7 1
#define RF 1
#define RK 0
#define LE 1
#define SL7 0
#define XP 3
#define MS 0
constexpr int CON_REGS = 224, MOE_REGS = 40, PROD_REGS = 24;
constexpr uint32_t SPIN_MAX = 2000000;
constexpr uint32_t SENT = 0xFFFFFFFFu;

struct __align__(128) Scratch {
  uint4 o[NCTA * 2048];
  uint4 part[NCTA * 544];
  uint4 fin[8 * 640];
  float2 stats[SEQ];
  uint32_t key[SEQ];
  uint32_t cs[3 * DM];
  uint4 y[NCTA * 128];
  uint32_t h[56 * 256];
  uint32_t top[128];
  uint32_t cnt[NCNT * 32];
};
__device__ Scratch G;
#define TLS(th, i)
#define TLP_(i)
#define TLG(i)
#define TLDUMP()

__device__ __forceinline__ bool elect_one() {
  uint32_t p;
  asm volatile("{\n.reg .pred P;\nelect.sync _|P, 0xffffffff;\nselp.b32 %0, 1, 0, P;\n}" : "=r"(p));
  return p;
}
__device__ __forceinline__ void mbar_init(uint32_t b, uint32_t c) { asm volatile("mbarrier.init.shared::cta.b64 [%0], %1;" ::"r"(b), "r"(c) : "memory"); }
__device__ __forceinline__ void mbar_expect_tx(uint32_t b, uint32_t bytes) { asm volatile("mbarrier.arrive.expect_tx.shared::cta.b64 _, [%0], %1;" ::"r"(b), "r"(bytes) : "memory"); }
__device__ __forceinline__ void mbar_arrive(uint32_t b) { asm volatile("mbarrier.arrive.shared::cta.b64 _, [%0];" ::"r"(b) : "memory"); }
__device__ __forceinline__ void mbar_wait_b(uint32_t b, uint32_t parity) {
  asm volatile(
      "{\n.reg .pred p;\n.reg .u32 cnt;\nmov.u32 cnt, 0;\n"
      "LW:\nmbarrier.try_wait.parity.shared::cta.b64 p, [%0], %1;\n@p bra LD;\n"
      "add.u32 cnt, cnt, 1;\nsetp.lt.u32 p, cnt, 4000000;\n@p bra LW;\ntrap;\nLD:\n}" ::"r"(b), "r"(parity) : "memory");
}
__device__ __forceinline__ void mbar_wait(uint32_t b, uint32_t parity) {
  asm volatile("{\n.reg .pred p;\nLW:\nmbarrier.try_wait.parity.shared::cta.b64 p, [%0], %1;\n@!p bra LW;\n}" ::"r"(b), "r"(parity) : "memory");
}
__device__ __forceinline__ bool mbar_test(uint32_t b, uint32_t parity) {
  uint32_t r;
  asm volatile("{\n.reg .pred p;\nmbarrier.test_wait.parity.shared::cta.b64 p, [%1], %2;\nselp.b32 %0, 1, 0, p;\n}" : "=r"(r) : "r"(b), "r"(parity) : "memory");
  return r;
}
__device__ __forceinline__ uint32_t ev_arrive(uint32_t a) { uint32_t r; asm volatile("atom.shared.add.u32 %0, [%1], 1;" : "=r"(r) : "r"(a) : "memory"); return r; }
__device__ __forceinline__ void tma2d(uint32_t dst, const CUtensorMap* m, int c0, int c1, uint32_t bar) {
  asm volatile("cp.async.bulk.tensor.2d.shared::cluster.global.mbarrier::complete_tx::bytes [%0], [%1, {%3, %4}], [%2];" ::"r"(dst), "l"(m), "r"(bar), "r"(c0), "r"(c1) : "memory");
}
__device__ __forceinline__ void tma3d(uint32_t dst, const CUtensorMap* m, int c1, int c2, uint32_t bar) {
  asm volatile("cp.async.bulk.tensor.3d.shared::cluster.global.mbarrier::complete_tx::bytes [%0], [%1, {%3, %4, %5}], [%2];" ::"r"(dst), "l"(m), "r"(bar), "r"(0), "r"(c1), "r"(c2) : "memory");
}
__device__ __forceinline__ void tma3d_mc(uint32_t dst, const CUtensorMap* m, int c1, int c2, uint32_t bar) {
  asm volatile("cp.async.bulk.tensor.3d.shared::cluster.global.mbarrier::complete_tx::bytes.multicast::cluster [%0], [%1, {%3, %4, %5}], [%2], %6;" ::"r"(dst), "l"(m), "r"(bar), "r"(0), "r"(c1), "r"(c2), "h"((uint16_t)3) : "memory");
}
__device__ __forceinline__ void tma5d(uint32_t dst, const CUtensorMap* m, int c2, int c4, uint32_t bar, bool mc) {
  if (mc) asm volatile("cp.async.bulk.tensor.5d.shared::cluster.global.mbarrier::complete_tx::bytes.multicast::cluster [%0], [%1, {%3, %3, %4, %3, %5}], [%2], %6;" ::"r"(dst), "l"(m), "r"(bar), "r"(0), "r"(c2), "r"(c4), "h"((uint16_t)3) : "memory");
  else asm volatile("cp.async.bulk.tensor.5d.shared::cluster.global.mbarrier::complete_tx::bytes [%0], [%1, {%3, %3, %4, %3, %5}], [%2];" ::"r"(dst), "l"(m), "r"(bar), "r"(0), "r"(c2), "r"(c4) : "memory");
}
__device__ __forceinline__ void mbar_arrive_cta(uint32_t b, uint32_t cta) {
  asm volatile("{\n.reg .b32 ra;\nmapa.shared::cluster.u32 ra, %0, %1;\nmbarrier.arrive.shared::cluster.b64 _, [ra];\n}" ::"r"(b), "r"(cta) : "memory");
}
constexpr uint64_t POL_FIRST = 0x12F0000000000000ull;
__device__ __forceinline__ void tma2d_ef(uint32_t dst, const CUtensorMap* m, int c0, int c1, uint32_t bar) {
  asm volatile("cp.async.bulk.tensor.2d.shared::cluster.global.mbarrier::complete_tx::bytes.L2::cache_hint [%0], [%1, {%3, %4}], [%2], %5;" ::"r"(dst), "l"(m), "r"(bar), "r"(c0), "r"(c1), "l"(POL_FIRST) : "memory");
}
__device__ __forceinline__ void bulk_ld(uint32_t dst, const void* src, uint32_t bytes, uint32_t bar) {
  asm volatile("cp.async.bulk.shared::cluster.global.mbarrier::complete_tx::bytes [%0], [%1], %2, [%3];" ::"r"(dst), "l"(src), "r"(bytes), "r"(bar) : "memory");
}
__device__ __forceinline__ void bulk_ld_mc(uint32_t dst, const void* src, uint32_t bytes, uint32_t bar) {
  asm volatile("cp.async.bulk.shared::cluster.global.mbarrier::complete_tx::bytes.multicast::cluster [%0], [%1], %2, [%3], %4;" ::"r"(dst), "l"(src), "r"(bytes), "r"(bar), "h"((uint16_t)3) : "memory");
}
__device__ __forceinline__ void bulk_pf(const void* src, uint32_t bytes) { asm volatile("cp.async.bulk.prefetch.L2.global [%0], %1;" ::"l"(src), "r"(bytes) : "memory"); }
__device__ __forceinline__ void tma2d_pf(const CUtensorMap* m, int c0, int c1) {
  asm volatile("cp.async.bulk.prefetch.tensor.2d.L2.global [%0, {%1, %2}];" ::"l"(m), "r"(c0), "r"(c1) : "memory");
}
__device__ __forceinline__ void map_pf(const CUtensorMap* m) { asm volatile("prefetch.tensormap [%0];" ::"l"(m) : "memory"); }
__device__ __forceinline__ void line_pf(const void* p) { asm volatile("prefetch.global.L2 [%0];" ::"l"(p)); }
__device__ __forceinline__ void pf128(uint32_t dummy, const void* src) { asm volatile("cp.async.ca.shared.global.L2::128B [%0], [%1], 4;" ::"r"(dummy), "l"(src) : "memory"); }
__device__ __forceinline__ void pf256(uint32_t dummy, const void* src) { asm volatile("cp.async.ca.shared.global.L2::256B [%0], [%1], 4;" ::"r"(dummy), "l"(src) : "memory"); }
__device__ __forceinline__ void cp16x2(uint32_t dst, const void* src) {
  asm volatile("cp.async.cg.shared.global [%0], [%1], 16;\ncp.async.cg.shared.global [%0+4096], [%1+512], 16;" ::"r"(dst), "l"(src) : "memory");
}
constexpr uint32_t HI_SW128 = 0x40000000u | (1024 >> 4), HI_SW64 = 0x80000000u | (512 >> 4), HI_NOSW = 512 >> 4;
__device__ __forceinline__ uint64_t mkdesc(uint32_t lo, uint32_t hi) { uint64_t d; asm("mov.b64 %0, {%1, %2};" : "=l"(d) : "r"(lo), "r"(hi)); return d; }
__device__ __forceinline__ void wg_fence() { asm volatile("wgmma.fence.sync.aligned;" ::: "memory"); }
__device__ __forceinline__ void wg_commit() { asm volatile("wgmma.commit_group.sync.aligned;" ::: "memory"); }
template <int N> __device__ __forceinline__ void wg_wait() { asm volatile("wgmma.wait_group.sync.aligned %0;" ::"n"(N) : "memory"); }
template <int N> __device__ __forceinline__ void reg_fence(float (&a)[N]) {
#pragma unroll
  for (int i = 0; i < N; i++) asm volatile("" : "+f"(a[i])::"memory");
}
template <int ID, int N> __device__ __forceinline__ void bar_sync() { asm volatile("bar.sync %0, %1;" ::"n"(ID), "n"(N) : "memory"); }
__device__ __forceinline__ void fence_async_smem() { asm volatile("fence.proxy.async.shared::cta;" ::: "memory"); }
__device__ __forceinline__ void fence_async_gmem() { asm volatile("fence.proxy.async.global;" ::: "memory"); }
__device__ __forceinline__ uint32_t pack_bf16(float lo, float hi) { uint32_t r; asm("cvt.rn.bf16x2.f32 %0, %1, %2;" : "=r"(r) : "f"(hi), "f"(lo)); return r; }
__device__ __forceinline__ float bf_lo(uint32_t v) { return __uint_as_float(v << 16); }
__device__ __forceinline__ float bf_hi(uint32_t v) { return __uint_as_float(v & 0xFFFF0000u); }
__device__ __forceinline__ float bf_round(float v) { return bf_lo(pack_bf16(v, v)); }
__device__ __forceinline__ uint32_t bf_sub2(uint32_t a, uint32_t b) { uint32_t r; asm("sub.rn.bf16x2 %0, %1, %2;" : "=r"(r) : "r"(a), "r"(b)); return r; }
__device__ __forceinline__ float rcp(float v) { float r; asm("rcp.approx.ftz.f32 %0, %1;" : "=f"(r) : "f"(v)); return r; }
__device__ __forceinline__ float ex2(float v) { float r; asm("ex2.approx.ftz.f32 %0, %1;" : "=f"(r) : "f"(v)); return r; }
__device__ __forceinline__ float sigmoid(float v) { return rcp(1.f + ex2(v * -1.4426950408889634f)); }
__device__ __forceinline__ void stsm4(uint32_t a, uint32_t r0, uint32_t r1, uint32_t r2, uint32_t r3) {
  asm volatile("stmatrix.sync.aligned.m8n8.x4.shared.b16 [%0], {%1,%2,%3,%4};" ::"r"(a), "r"(r0), "r"(r1), "r"(r2), "r"(r3) : "memory");
}
__device__ __forceinline__ void stsm4t(uint32_t a, uint32_t r0, uint32_t r1, uint32_t r2, uint32_t r3) {
  asm volatile("stmatrix.sync.aligned.m8n8.x4.trans.shared.b16 [%0], {%1,%2,%3,%4};" ::"r"(a), "r"(r0), "r"(r1), "r"(r2), "r"(r3) : "memory");
}
__device__ __forceinline__ void ldsm4(uint32_t a, uint32_t& r0, uint32_t& r1, uint32_t& r2, uint32_t& r3) {
  asm volatile("ldmatrix.sync.aligned.m8n8.x4.shared.b16 {%0,%1,%2,%3}, [%4];" : "=r"(r0), "=r"(r1), "=r"(r2), "=r"(r3) : "r"(a) : "memory");
}
__device__ __forceinline__ uint32_t movmat(uint32_t a) { uint32_t d; asm volatile("movmatrix.sync.aligned.m8n8.trans.b16 %0, %1;" : "=r"(d) : "r"(a)); return d; }
__device__ __forceinline__ void sts_h(uint32_t a, float v) { asm volatile("st.shared.u16 [%0], %1;" ::"r"(a), "h"((uint16_t)pack_bf16(v, v)) : "memory"); }
__device__ __forceinline__ float2 lds_f2(uint32_t a) { float2 v; asm volatile("ld.shared.v2.f32 {%0,%1}, [%2];" : "=f"(v.x), "=f"(v.y) : "r"(a)); return v; }
__device__ __forceinline__ float lds_f(uint32_t a) { float v; asm volatile("ld.shared.f32 %0, [%1];" : "=f"(v) : "r"(a)); return v; }
__device__ __forceinline__ float4 lds_f4(uint32_t a) { float4 v; asm volatile("ld.shared.v4.f32 {%0,%1,%2,%3}, [%4];" : "=f"(v.x), "=f"(v.y), "=f"(v.z), "=f"(v.w) : "r"(a)); return v; }
__device__ __forceinline__ uint32_t lds_u(uint32_t a) { uint32_t v; asm volatile("ld.shared.u32 %0, [%1];" : "=r"(v) : "r"(a) : "memory"); return v; }
__device__ __forceinline__ uint4 lds_u4(uint32_t a) { uint4 v; asm volatile("ld.shared.v4.u32 {%0,%1,%2,%3}, [%4];" : "=r"(v.x), "=r"(v.y), "=r"(v.z), "=r"(v.w) : "r"(a) : "memory"); return v; }
__device__ __forceinline__ void sts_u(uint32_t a, uint32_t v) { asm volatile("st.shared.u32 [%0], %1;" ::"r"(a), "r"(v) : "memory"); }
__device__ __forceinline__ void sts_u4(uint32_t a, uint4 v) { asm volatile("st.shared.v4.u32 [%0], {%1,%2,%3,%4};" ::"r"(a), "r"(v.x), "r"(v.y), "r"(v.z), "r"(v.w) : "memory"); }
__device__ __forceinline__ uint4 ldx4(const void* p) { uint4 v; asm volatile("ld.relaxed.gpu.global.v4.u32 {%0,%1,%2,%3}, [%4];" : "=r"(v.x), "=r"(v.y), "=r"(v.z), "=r"(v.w) : "l"(p) : "memory"); return v; }
__device__ __forceinline__ uint2 ldx2(const void* p) { uint2 v; asm volatile("ld.relaxed.gpu.global.v2.u32 {%0,%1}, [%2];" : "=r"(v.x), "=r"(v.y) : "l"(p) : "memory"); return v; }
__device__ __forceinline__ uint32_t ldx1(const void* p) { uint32_t v; asm volatile("ld.relaxed.gpu.global.u32 %0, [%1];" : "=r"(v) : "l"(p) : "memory"); return v; }
__device__ __forceinline__ void stx4(void* p, uint32_t a, uint32_t b, uint32_t c, uint32_t d) {
  asm volatile("st.relaxed.gpu.global.v4.u32 [%0], {%1,%2,%3,%4};" ::"l"(p), "r"(a), "r"(b), "r"(c), "r"(d) : "memory");
}
__device__ __forceinline__ void stx2(void* p, uint32_t a, uint32_t b) { asm volatile("st.relaxed.gpu.global.v2.u32 [%0], {%1,%2};" ::"l"(p), "r"(a), "r"(b) : "memory"); }
__device__ __forceinline__ void stx1(void* p, uint32_t a) { asm volatile("st.relaxed.gpu.global.u32 [%0], %1;" ::"l"(p), "r"(a) : "memory"); }
__device__ __forceinline__ uint32_t umax4(uint4 v) { return max(max(v.x, v.y), max(v.z, v.w)); }
__device__ __forceinline__ uint32_t f2x(float f) { return min(__float_as_uint(f), 0xFFFFFFFEu); }
__device__ __forceinline__ void red4(float* p, float a, float b, float c, float d) { asm volatile("red.relaxed.gpu.global.add.v4.f32 [%0], {%1,%2,%3,%4};" ::"l"(p), "f"(a), "f"(b), "f"(c), "f"(d) : "memory"); }
__device__ __forceinline__ void cnt_arrive(int c) { asm volatile("red.release.gpu.global.add.u32 [%0], 1;" ::"l"(&G.cnt[c]) : "memory"); }
__device__ __forceinline__ void cnt_wait(int c, uint32_t target) {
#pragma unroll 1
  for (uint32_t it = 0; it < SPIN_MAX; it++) {
    uint32_t v;
    asm volatile("ld.acquire.gpu.global.u32 %0, [%1];" : "=r"(v) : "l"(&G.cnt[c]) : "memory");
    if (v >= target) break;
    __nanosleep(POLLNS);
  }
}
__device__ __forceinline__ void spin_cycles(uint32_t n) {
  uint32_t t0, t1;
  asm volatile("mov.u32 %0, %%clock;" : "=r"(t0));
#pragma unroll 1
  do { __nanosleep(20); asm volatile("mov.u32 %0, %%clock;" : "=r"(t1)); } while (t1 - t0 < n);
}
__device__ __forceinline__ void cnt_done() {
  uint32_t t;
  asm volatile("atom.acq_rel.gpu.global.add.u32 %0, [%1], 1;" : "=r"(t) : "l"(&G.cnt[C_DONE]) : "memory");
  if (t == NCTA + NSVC - 1) {
#pragma unroll 1
    for (int i = 0; i < NCNT; i++) G.cnt[i * 32] = 0;
  }
}
__device__ __forceinline__ float phi(float u, float rs, float rl) {
  float a = fmaf(u, rs, 1.000001f), e = ex2(u * rl), r;
  asm("add.sat.f32 %0, %1, 0f358637BD;" : "=f"(e) : "f"(e));
  asm("max.NaN.f32 %0, %1, %2;" : "=f"(r) : "f"(a), "f"(e));
  return r;
}

constexpr float LOG2E = 1.4426950408889634f, LN2 = 0.6931471805599453f;
__device__ __forceinline__ uint32_t phi2l(float u0, float rl0, float u1, float rl1) {
  const float l0 = u0 * rl0, l1 = u1 * rl1;
  float e0, e1;
  asm("{\n.reg .f32 t;\nabs.f32 t, %1;\nneg.f32 t, t;\nex2.approx.ftz.f32 %0, t;\n}" : "=f"(e0) : "f"(l0));
  asm("{\n.reg .f32 t;\nabs.f32 t, %1;\nneg.f32 t, t;\nex2.approx.ftz.f32 %0, t;\n}" : "=f"(e1) : "f"(l1));
  uint32_t e = pack_bf16(e0, e1), r;
  const uint32_t a = pack_bf16(fmaf(l0, LN2, 1.000001f), fmaf(l1, LN2, 1.000001f));
  asm("add.rn.bf16x2 %0, %0, %1;" : "+r"(e) : "r"(0x35863586u));
  asm("max.NaN.bf16x2 %0, %1, %2;" : "=r"(r) : "r"(a), "r"(e));
  return r;
}
template <bool V = false>
__device__ __forceinline__ uint32_t phi2(float u0, float rs0, float rl0, float u1, float rs1, float rl1) {
  float e0, e1;
  if (V) {
    asm volatile("{\n.reg .f32 t;\nabs.f32 t, %1;\nneg.f32 t, t;\nex2.approx.ftz.f32 %0, t;\n}" : "=f"(e0) : "f"(u0 * rl0));
    asm volatile("{\n.reg .f32 t;\nabs.f32 t, %1;\nneg.f32 t, t;\nex2.approx.ftz.f32 %0, t;\n}" : "=f"(e1) : "f"(u1 * rl1));
  } else {
    asm("{\n.reg .f32 t;\nabs.f32 t, %1;\nneg.f32 t, t;\nex2.approx.ftz.f32 %0, t;\n}" : "=f"(e0) : "f"(u0 * rl0));
    asm("{\n.reg .f32 t;\nabs.f32 t, %1;\nneg.f32 t, t;\nex2.approx.ftz.f32 %0, t;\n}" : "=f"(e1) : "f"(u1 * rl1));
  }
  uint32_t e = pack_bf16(e0, e1), r;
  const uint32_t a = pack_bf16(fmaf(u0, rs0, 1.000001f), fmaf(u1, rs1, 1.000001f));
  asm("add.rn.bf16x2 %0, %0, %1;" : "+r"(e) : "r"(0x35863586u));
  asm("max.NaN.bf16x2 %0, %1, %2;" : "=r"(r) : "r"(a), "r"(e));
  return r;
}

__device__ __forceinline__ int kstep1(int e, int hg) { return e < 14 ? (e < 2 * hg ? e : e + 2) : 2 * hg + e - 14; }
__device__ __forceinline__ int slab(int n, int hg) {
  return n + (((n + 7 - hg) * 37) >> 8);
}
__host__ __device__ constexpr uint32_t d_off(int i) { return i < 3 ? 12 * SLOT + (NR == 4 ? i : (i == 2 ? 0 : i + 1)) * MT : (i < 5 ? S_D0 * SLOT + (i - 3) * 8192 : S_D1 * SLOT + (i - 5) * 8192); }
__host__ __device__ constexpr uint32_t h_off(int i) { return i < 3 ? 12 * SLOT + i * MT + 8192 : (i < 5 ? A_ONES + (i - 3) * 1024 : MISC + M_MOE + (i - 5) * 1024); }
__device__ __forceinline__ uint32_t m_off(int r) { return r < 3 ? 12 * SLOT + r * MT : S_M3 * SLOT; }
__device__ __forceinline__ int x_slot(int e, int s) { return NQ == 5 ? (e < 14 ? s : e - 11) : (e < 13 ? s : 3 + s); }
__device__ __forceinline__ uint32_t wo_slot(int i) { return (uint32_t)(WO_SLOTS >> (4 * i)) & 15u; }

__global__ void __launch_bounds__(512, 1)
fused_kernel(const __nv_bfloat16* __restrict__ x, const __nv_bfloat16* __restrict__ wqkv, const __nv_bfloat16* __restrict__ wo,
             const __nv_bfloat16* __restrict__ wr, const __nv_bfloat16* __restrict__ wd, __nv_bfloat16* __restrict__ outp, const int by_sm,
             const __grid_constant__ CUtensorMap tmX, const __grid_constant__ CUtensorMap tmW,
             const __grid_constant__ CUtensorMap tmWo, const __grid_constant__ CUtensorMap tmOut,
             const __grid_constant__ CUtensorMap tmG, const __grid_constant__ CUtensorMap tmU,
             const __grid_constant__ CUtensorMap tmD, const __grid_constant__ CUtensorMap tmR,
             const __grid_constant__ CUtensorMap tmWp) {
  if (TMP && threadIdx.x == 32 * TMPW) { map_pf(&tmX); map_pf(&tmW); }
  extern __shared__ __align__(1024) uint8_t smem_raw[];
  const uint32_t sb = (uint32_t)__cvta_generic_to_shared(smem_raw);
  const uint32_t bars = sb + MISC + M_BAR;
  uint32_t smid;
  asm("mov.u32 %0, %%smid;" : "=r"(smid));
  const int tpc = smid >> 1;
  int cl = tpc + max(((tpc - 25) * 37) >> 8, 0);
  cl = tpc < 60 ? cl : cl - 1;
  cl = tpc < 62 ? cl : (tpc - 58) * 8;
  const int u = by_sm ? 2 * cl + (blockIdx.x & 1) : blockIdx.x;
  const int hg = (u >> 4) & 7, tb = u & 15;
  const int b = tb * 8 + hg;
  const int lane = threadIdx.x & 31;
  const int warp = __shfl_sync(~0u, threadIdx.x >> 5, 0);
  const int ltid = threadIdx.x;
  const int g = lane >> 2, t = lane & 3;
  const uint32_t d0 = (sb & 0x3FFFF) >> 4;
#define BAR(i) (bars + 8 * (i))
  TLS(0, 0);

  const int rank = u & 1;
  auto load_entry = [&](int e, int s) {
    const int k0 = kstep1(e, hg) * 64;
    mbar_expect_tx(BAR(B_FXQ + s), e < NF ? 2 * SLOT : SLOT);
    mbar_expect_tx(BAR(B_FKV + s), R5 ? SLOT : 2 * SLOT);
    if (R5 && e < 11) mbar_expect_tx(BAR(B_FV + s), SLOT);
    const uint32_t vb = R5 ? BAR(B_FV + s) : BAR(B_FKV + s);
    tma2d(sb + x_slot(e, s) * SLOT, &tmX, k0, tb * 128, BAR(B_FXQ + s));
    if (e < MC0 || !(MC & 1)) {
      if (e < NF) tma3d(sb + (3 + s) * SLOT, &tmW, k0, 2 * hg, BAR(B_FXQ + s));
      tma3d(sb + (6 + 2 * s) * SLOT, &tmW, k0, 16 + 2 * hg, BAR(B_FKV + s));
      tma3d(sb + (7 + 2 * s) * SLOT, &tmW, k0, 32 + 2 * hg, vb);
    } else {
      if (e < NF && (e & 1) == rank) tma3d_mc(sb + (3 + s) * SLOT, &tmW, k0, 2 * hg, BAR(B_FXQ + s));
      if (R5 && e >= 11) { if (rank == 0) tma3d_mc(sb + ((K_SLOTS >> (4 * (e - 10))) & 15u) * SLOT, &tmW, k0, 16 + 2 * hg, BAR(B_FKV + s)); }
      else tma3d_mc(sb + (6 + 2 * s + rank) * SLOT, &tmW, k0, 16 + 16 * rank + 2 * hg, rank ? vb : BAR(B_FKV + s));
    }
  };
  if (warp == FW && u < NCTA) {
    if (elect_one()) {
      mbar_init(BAR(B_FXQ), 1); mbar_init(BAR(B_FKV), 1);
      if (R5) mbar_init(BAR(B_FV), 1);
      load_entry(0, 0);
      asm volatile("fence.mbarrier_init.release.cluster;" ::: "memory");
      TLS(FW * 32, 61);
    }
    __syncwarp();
  }
  if (u >= NCTA) {
    const int j = u - NCTA;
    if (warp == 8 && elect_one()) {
#pragma unroll
      for (int i = 0; i < 13; i++) mbar_init(BAR(i), 1);
    }
    if (ltid < 64) sts_u4(sb + MISC + ltid * 16, make_uint4(0x3F803F80u, 0x3F803F80u, 0x3F803F80u, 0x3F803F80u));
    fence_async_smem();
    __syncthreads();
    if (warp < 4) {
      int s = 0, p = 0;
#pragma unroll 1
      for (int pass = 0; pass < 3; pass++) {
        float acc[4][4];
#pragma unroll
        for (int c = 0; c < 4; c++) acc[c][0] = acc[c][1] = acc[c][2] = acc[c][3] = 0.f;
#pragma unroll 1
        for (int k = 0; k < 16; k++) {
          mbar_wait(BAR(s), p);
          wg_fence();
#pragma unroll
          for (int c = 0; c < 4; c++)
#pragma unroll
            for (int kk = 0; kk < 4; kk++)
              wgmma_ss_n8<1, 0>(acc[c], mkdesc((d0 + s * 2048 + c * 512 + kk * 128) | (512u << 16), HI_SW128), mkdesc((d0 + (MISC >> 4)) | (1u << 16), HI_SW128));
          wg_commit();
          wg_wait<0>();
          if (ltid == 0) mbar_arrive(BAR(6 + s));
          if (++s == SVS) { s = 0; p ^= 1; }
        }
        uint32_t* pc = G.cs + (pass < 2 ? DM + pass * DM : 0) + j * 256 + warp * 16 + g;
#pragma unroll
        for (int c = 0; c < 4; c++) {
          reg_fence(acc[c]);
          const uint32_t v = __float_as_uint((t & 1) ? acc[c][2] : acc[c][0]);
          if (t < 2) stx1(pc + c * 64 + t * 8, v ? v : 0x80000000u);
        }
        TLS(0, 1 + pass);
      }
    } else if (warp >= 8 && j == 0) {
      const int wq = warp - 8;
      const uint32_t top = sb + MISC + 1024;
#pragma unroll 1
      for (uint32_t it = 0; it < SPIN_MAX; it++) {
        const uint4 v0 = ldx4(G.key + wq * 256 + lane * 4), v1 = ldx4(G.key + wq * 256 + 128 + lane * 4);
        uint32_t ok;
        asm volatile("{\n.reg .pred p, q;\nsetp.ne.u32 p, %1, 0;\nbar.red.and.pred q, 2, 256, p;\nselp.b32 %0, 1, 0, q;\n}" : "=r"(ok) : "r"((v0.x & v0.y & v0.z & v0.w & v1.x & v1.y & v1.z & v1.w) >> 27) : "memory");
        ok = __any_sync(~0u, ok);
        if (!ok && it) continue;
        TLS(256, 4);
        uint32_t np = 0u - (1u << 28), mine = 0;
#pragma unroll 1
        for (int r = 0; r < 8; r++) {
          const uint32_t m0 = __viaddmax_u32(v0.x, np, v0.y + np), m1 = __viaddmax_u32(v0.z, np, v0.w + np), m2 = __viaddmax_u32(v1.x, np, v1.y + np), m3 = __viaddmax_u32(v1.z, np, v1.w + np);
          np -= __reduce_max_sync(~0u, max(max(m0, m1), max(m2, m3)));
          if (g == r) mine = 0u - np;
        }
        if (t == 0) sts_u(top + (wq * 8 + g) * 4, mine);
        bar_sync<2, 256>();
        TLS(256, 5);
        int rk = 0;
#pragma unroll
        for (int i = 0; i < 4; i++) {
          const uint4 o = lds_u4(top + t * 64 + i * 16);
          rk += (o.x > mine) + (o.y > mine) + (o.z > mine) + (o.w > mine);
        }
        rk += __shfl_xor_sync(~0u, rk, 1);
        rk += __shfl_xor_sync(~0u, rk, 2);
        if (ok) { if (rk < 8) stx1(G.top + t * 32 + rk, mine); break; }
        __nanosleep(2500);
      }
      TLS(256, 7);
    } else if (warp == 4) {
      int s = 0, p = 1;
      if (SVD) __nanosleep(SVD);
#pragma unroll 1
      for (int i = 0; i < 48; i++) {
        mbar_wait(BAR(6 + s), p);
        if (j == 0 && i >= SV0A && i < SV0B) mbar_wait(BAR(s >= SV0 ? s - SV0 : s - SV0 + SVS), s >= SV0 ? p ^ 1 : p);
        if (elect_one()) {
          mbar_expect_tx(BAR(s), 2 * SLOT);
          const int ch = (i < 32 ? 16 + (i & 16) : 0) + j * 4, k0 = (i & 15) * 64;
          tma3d(sb + s * 2 * SLOT, &tmW, k0, ch, BAR(s));
          tma3d(sb + s * 2 * SLOT + SLOT, &tmW, k0, ch + 2, BAR(s));
        }
        if (++s == SVS) { s = 0; p ^= 1; }
      }
    }
    if (ltid == 0) cnt_wait(C_DONE, NCTA);
    __syncthreads();
    const uint4 zero = make_uint4(0, 0, 0, 0);
    if (ltid < 128) reinterpret_cast<uint4*>(G.key)[j * 128 + ltid] = zero;
    else if (ltid < 320) reinterpret_cast<uint4*>(G.cs)[j * 192 + ltid - 128] = zero;
    else if (ltid < 322) reinterpret_cast<uint4*>(G.top)[j * 8 + ltid - 320] = zero;
    if (ltid == 0) { cnt_done(); TLDUMP(); }
    return;
  }

  if (warp == 12) {
    if (elect_one()) {
#pragma unroll
      for (int i = 1; i < 7; i++) if (i != B_FKV) mbar_init(BAR(i), 1);
      if (R5) { mbar_init(BAR(B_FV + 1), 1); mbar_init(BAR(B_FV + 2), 1); }
      if (E1E) load_entry(1, 1);
      asm volatile("fence.mbarrier_init.release.cluster;" ::: "memory");
    }
  } else if (warp >= 13) {
    if (elect_one()) {
      if (warp == 15) {
#pragma unroll
        for (int i = B_FAUX; i < NBAR; i++) mbar_init(BAR(i), i < B_E || !MC ? 2 : 4);
        mbar_init(BAR(B_KV4), 4); mbar_init(BAR(B_MS), 2); mbar_init(BAR(B_GQ), 1); mbar_init(BAR(B_GT), 1);
        if (R5) { mbar_init(BAR(B_EK), 4); mbar_init(BAR(B_EK + 1), 4); mbar_init(BAR(B_EK + 2), 4); }
      } else {
#pragma unroll
        for (int i = 0; i < 23; i++) mbar_init(BAR((warp == 13 ? 7 : 30) + i), 1);
      }
      asm volatile("fence.mbarrier_init.release.cluster;" ::: "memory");
    }
  }
  __syncthreads();
  if (MC) asm volatile("barrier.cluster.arrive.relaxed.aligned;" ::: "memory");

  const bool unit = u < NUNIT;
  const int dcol = (u & 15) * 64, drow = (u >> 4) * 448;
  if (warp >= 12) {
    asm volatile("setmaxnreg.dec.sync.aligned.u32 %0;" ::"n"(PROD_REGS));
    if (MC && warp != 12) asm volatile("barrier.cluster.wait.aligned;" ::: "memory");
    if (warp == 12) {
      int s = 1 + E1E, p = 1, pn = 3;
#pragma unroll 1
      for (int e = 1 + E1E; e < 16; e++) {
        if (MC && e == MC0) asm volatile("barrier.cluster.wait.aligned;" ::: "memory");
        if (e == GATE) mbar_wait(BAR(B_FXQ), 0);
        mbar_wait(BAR(B_E + s), p);
        if (elect_one()) {
          load_entry(e, s);
          if (NR == 4 && e == 11) mbar_arrive(BAR(B_ME + 3));
          if (e == ASTE) {
            mbar_expect_tx(BAR(B_AST), 2 * SLOT + 2048);
            bulk_ld(sb + 12 * SLOT, x + (size_t)b * 16 * DM, 2 * SLOT, BAR(B_AST));
            bulk_ld(sb + MISC + M_MOE, wr, 2048, BAR(B_AST));
          } else if (e >= 3) {
            if (WSP == 0) { if (e < 6) bulk_pf(wqkv + (size_t)((e - 2) * 256 + 2 * b) * 3 * DM, 2 * 3 * DM * 2); }
            else if (e < 9) bulk_pf(wqkv + (size_t)((e - 1) * 128 + b) * 3 * DM, 3 * DM * 2);
            if (WOP >= 0 && e >= WOP && e < WOP + 4) bulk_pf(wo + (size_t)((e - WOP) * 256 + 2 * b) * DM, 2 * DM * 2);
            if (NUNIT) {
#pragma unroll 1
              for (int i = (PFTAB >> (4 * (e - 3))) & 15; i > 0; i--, pn++) {
                if (pn >= 16) { if (!(MX & 8)) tma2d_pf(&tmD, dcol, drow + (pn - 16) * 64); }
                else if (unit && !(MX & 2)) tma2d_pf(rank ? &tmU : &tmG, (u >> 1) * 64, pn * 64);
              }
            }
          }
        }
        if (R5 && e >= 11) {
          mbar_wait(BAR(B_EK + (s == 2 ? 0 : s + 1)), e >= 14);
          if (elect_one()) {
            mbar_expect_tx(BAR(B_FV + s), SLOT);
            if (rank) tma3d_mc(sb + ((V_SLOTS >> (4 * (e - 10))) & 15u) * SLOT, &tmW, kstep1(e, hg) * 64, 32 + 2 * hg, BAR(B_FV + s));
          }
        }
        if (++s == 3) { s = 0; p ^= 1; }
      }
#pragma unroll 1
      for (int k = 0; k < NQ; k++) {
        if (k == 0) mbar_wait(BAR(B_E + 1), 0);
        if (k == 1) mbar_wait(BAR(B_EK + 2), 1);
        if (k == 2) mbar_wait(BAR(B_EK + 0), 0);
        if (k == 3) mbar_wait(BAR(B_STG), 0);
        if (k == 5) mbar_wait(BAR(B_EQ), 0);
        if (elect_one()) {
          const int k0 = kstep1(NF + k, hg) * 64;
          mbar_expect_tx(BAR(B_FQ + k), SLOT);
          if (!(MC & 2)) tma3d(sb + ((QW_SLOTS >> (4 * k)) & 15u) * SLOT, &tmW, k0, 2 * hg, BAR(B_FQ + k));
          else if ((k & 1) == rank) tma3d_mc(sb + ((QW_SLOTS >> (4 * k)) & 15u) * SLOT, &tmW, k0, 2 * hg, BAR(B_FQ + k));
        }
      }
#pragma unroll 1
      for (int i = 0; i < 16; i++) {
        mbar_wait(i < 7 ? BAR(B_EQ + ((i + WQ0) >> 1)) : (i < 9 ? BAR(B_DE) : BAR(B_EO + i - 9)), 0);
        if (i == WOK) mbar_wait(BAR(B_KVB), 0);
        mbar_wait(BAR(B_FWO + i - (i < WOK ? WOD1 : WOD)), 0);
        if (elect_one()) {
          mbar_expect_tx(BAR(B_FWO + i), SLOT);
#pragma unroll
          for (int hf = 0; hf < ((MC & 4) ? 1 : 2); hf++) {
            const int n = 2 * i + ((MC & 4) ? rank : hf), m = slab(n - 4, hg), hd = n < 4 ? 4 * hg + n : 4 * (m & 7) + (m >> 3);
            if (i < 2 + NDIR) tma5d(sb + wo_slot(i) * SLOT + (n & 1) * 8192, &tmWp, hd * 4, 2 * hg, BAR(B_FWO + i), MC & 4);
            else if (MC & 4) tma3d_mc(sb + wo_slot(i) * SLOT + rank * 8192, &tmWo, hd * 32, 2 * hg, BAR(B_FWO + i));
            else tma3d(sb + wo_slot(i) * SLOT + hf * 8192, &tmWo, hd * 32, 2 * hg, BAR(B_FWO + i));
          }
        }
      }
    } else if (warp == 13) {
      if (elect_one()) {
        map_pf(rank ? &tmU : &tmG); map_pf(&tmR); map_pf(&tmD); map_pf(&tmWo); map_pf(&tmWp); map_pf(&tmOut);
      }
      bar_sync<6, 64>();
      if (elect_one()) {
        cnt_wait(C_B, NCTA);
        fence_async_gmem();
        mbar_expect_tx(BAR(B_FAUX), 1024);
        bulk_ld(sb + A_ST, G.stats + tb * 128, 1024, BAR(B_FAUX));
      }
      __syncwarp();
      TLS(416, 68);
#pragma unroll 1
      for (int m = 1; m < 4; m++) {
        const int part = m == 3 ? 0 : m;
        uint4 c;
#pragma unroll 1
        for (uint32_t it = 0; it < SPIN_MAX; it++) {
          c = ldx4(G.cs + part * DM + hg * 128 + lane * 4);
          if (__all_sync(~0u, min(min(c.x, c.y), min(c.z, c.w)))) break;
          __nanosleep(POLLNS);
        }
        if (CQ4 && part == 0) {
          const uint32_t o = sb + A_CS + (lane >> 2) * 64 + (lane & 1) * 32 + ((lane >> 1) & 1) * 8;
          asm volatile("st.shared.v2.u32 [%0], {%1,%2};\nst.shared.v2.u32 [%0+16], {%3,%4};" ::"r"(o), "r"(c.x), "r"(c.y), "r"(c.z), "r"(c.w) : "memory");
        } else sts_u4(sb + A_CS + part * 512 + lane * 16, c);
        __syncwarp();
        if (m > 1 && lane == 0) mbar_arrive(BAR(m == 2 ? B_FAUX : B_CQ));
        TLS(416, 71 + m);
      }
      mbar_wait(BAR(B_XS), 1);
      if (elect_one()) asm volatile("red.relaxed.gpu.global.add.u32 [%0], 1;" ::"l"(&G.cnt[C_DONE]) : "memory");
    } else if (warp == 14) {
      const uint4 sent = make_uint4(SENT, SENT, SENT, SENT);
      uint4* ro = G.o + (tb * 32 + hg) * 512 + lane;
      uint4* rp = G.part + b * 544 + lane;
      if (RSL) bar_sync<5, 160>(); else mbar_wait(BAR(B_AST), 0);
#pragma unroll 1
      for (int i = RS0; i < 40; i++) {
        uint4* q = i < 32 ? ro + (i >> 3) * 4096 + (i & 7) * 64 : rp + (i - 32) * 64;
        q[0] = sent; q[32] = sent;
        __nanosleep(RSNS);
      }
      rp[512] = sent;
#pragma unroll
      for (int i = 0; i < 4; i++) G.y[u * 128 + i * 32 + lane] = sent;
      if (unit) reinterpret_cast<uint4*>(G.h)[u * 32 + lane] = sent;
      G.fin[hg * 640 + tb * 40 + lane] = sent;
      if (lane < 8) G.fin[hg * 640 + tb * 40 + 32 + lane] = sent;
      if (!RSL) bar_sync<5, 160>();
      __syncwarp();
      TLS(448, 67);
      if (lane == 0) cnt_arrive(C_B);
      __syncwarp();
      TLS(448, 32);
      asm volatile("bar.arrive 6, 64;" ::: "memory");
    } else {
      const uint32_t stg = sb + 12 * SLOT;
      auto load_a = [&](int n, int r) {
        mbar_expect_tx(BAR(B_MF + r), (MX & 2) ? 1024 : MT);
        if (!(MX & 2)) tma2d_ef(sb + m_off(r), rank ? &tmU : &tmG, (u >> 1) * 64, n * 64, BAR(B_MF + r));
      };
      mbar_wait(BAR(B_XS), 0);
      if (unit) {
#pragma unroll 1
        for (int i = 0; i < 3; i++) {
          if (elect_one()) load_a(i, i);
          __nanosleep(PFILL);
        }
      }
      uint32_t key;
#pragma unroll 1
      for (uint32_t it = 0; it < SPIN_MAX; it++) {
        key = ldx1(G.top + ((u >> 1) & 3) * 32 + (lane & 7));
        if (__all_sync(~0u, key)) break;
        __nanosleep(TPNS);
      }
      TLS(480, 66);
      if (lane < 8) sts_u(sb + MISC + M_IDX + lane * 4, key);
      __syncwarp();
      if (lane == 0) mbar_arrive(BAR(B_XS));
      if (unit) {
        int tok[8];
#pragma unroll
        for (int i = 0; i < 8; i++) tok[i] = ~__shfl_sync(~0u, key, i) & 2047;
        int r = 0, p = 0;
#pragma unroll 1
        for (int n = 0; n < 16; n++) {
          if (n >= 3) mbar_wait(BAR(B_ME + r), r == 3 ? p : p ^ 1);
          if (elect_one()) {
            if (n >= 3) load_a(n, r);
#pragma unroll
            for (int i = 0; i < 8; i++) tma2d(sb + m_off(r) + 8192 + i * 128, &tmR, n * 64, tok[i], BAR(B_MF + r));
          }
          if (++r == NR) { r = 0; p ^= 1; }
        }
      }
      if (NUNIT) {
        if (lane == 0) mbar_expect_tx(BAR(B_DF), (MX & 8) ? 0 : 7 * 8192);
#pragma unroll 1
        for (int i = 0; i < 7; i++) {
          if (NR == 4) {
            if (i >= 3) mbar_wait(i < 5 ? BAR(B_ME + 3) : (R5 ? BAR(B_EQ + 1) : BAR(B_STG)), 0);
            else if (unit) mbar_wait(BAR(B_ME + i), 1);
          } else {
            if (i >= 3) mbar_wait(BAR(B_EQ + ((i - 3) >> 1)), 0);
            else if (unit) mbar_wait(BAR(B_ME + (i == 2 ? 0 : i + 1)), i == 2);
          }
          if (!(MX & 8) && elect_one()) tma2d_ef(sb + d_off(i), &tmD, dcol, drow + i * 64, BAR(B_DF));
          if (DNS) __nanosleep(DNS);
        }
      }
    }
    if (warp == 14) {
      if (DPF && NUNIT && !(MX & 8)) {
        mbar_wait(DS ? BAR(B_MS) : (DPF == 1 ? BAR(B_FQ) : BAR(B_T0)), 0);
#pragma unroll 1
        for (int pf = 0; pf < 7; pf++) { pf256(sb + MISC + M_DUM, wd + (size_t)(drow + pf * 64 + rank * 32 + lane) * DM + (dcol & ~127)); __nanosleep(PFNS2); }
      }
      const uint32_t* src = reinterpret_cast<const uint32_t*>(G.part + ((lane >> 3) * 32 + hg) * 544 + 512) + tb * 8 + (lane & 7);
      mbar_wait(BAR(B_EQ + MRW), 0);
      if (MRC) spin_cycles(MRC); else if (MRD) __nanosleep(MRD);
      uint32_t z0, z1, z2, z3;
#pragma unroll 1
      for (uint32_t it = 0; it < SPIN_MAX; it++) {
        z0 = ldx1(src); z1 = ldx1(src + 8 * 2176); z2 = ldx1(src + 16 * 2176); z3 = ldx1(src + 24 * 2176);
        if (!__any_sync(~0u, max(max(z0, z1), max(z2, z3)) == SENT)) break;
      }
      if (MRED == 2 && elect_one()) mbar_arrive(BAR(B_ZOK));
      float zz = (__uint_as_float(z0) + __uint_as_float(z1)) + (__uint_as_float(z2) + __uint_as_float(z3));
      zz += __shfl_xor_sync(~0u, zz, 8);
      zz += __shfl_xor_sync(~0u, zz, 16);
      stx1(reinterpret_cast<uint32_t*>(G.fin + hg * 640) + (tb >> 2) * 640 + 512 + ((tb >> 1) & 1) * 64 + (lane & 1) * 32 + (tb & 1) * 16 + ((lane & 7) >> 1) * 4 + (lane >> 3),
           pack_bf16(zz, zz));
      TLS(448, 12);
    }
    if (!MFIN && (warp == 13 || warp == 14)) {
      mbar_wait(BAR(B_EQ + H2W), 0);
      if (H2C) spin_cycles(H2C); else if (H2D) __nanosleep(H2D);
#pragma unroll 1
      for (uint32_t it = 0; it < SPIN_MAX; it++) {
        if (warp == 14 && elect_one()) {
          mbar_expect_tx(BAR(B_FIN), 10240);
          if (FMC && MC && it == 0) bulk_ld_mc(sb + S_KVB * SLOT + rank * 5120, G.fin + hg * 640 + rank * 320, 5120, BAR(B_FIN));
          else bulk_ld(sb + S_KVB * SLOT, G.fin + hg * 640, 10240, BAR(B_FIN));
        }
        mbar_wait(BAR(B_FIN), it & 1);
        uint32_t m = 0;
#pragma unroll
        for (int i = 0; i < 10; i++) m = max(m, lds_u(sb + S_KVB * SLOT + (i * 64 + ltid - 416) * 16 + (g >> 1) * 4));
        uint32_t bad;
        asm volatile("{\n.reg .pred p, q;\nsetp.eq.u32 p, %1, 0xFFFFFFFF;\nbar.red.or.pred q, 7, 64, p;\nselp.b32 %0, 1, 0, q;\n}" : "=r"(bad) : "r"(m) : "memory");
        if (!__any_sync(~0u, bad)) break;
      }
      if (warp == 14 && elect_one()) mbar_arrive(BAR(B_KVB));
      TLS(448, 14);
    }
    if (PH && (warp == 13 || warp == 14)) {
      bar_sync<3, 192>();
      mbar_wait(BAR(B_STG), 0);
#pragma unroll 1
      for (uint32_t it = 0; NUNIT && it < SPIN_MAX; it++) {
        if (elect_one()) {
          const uint32_t* ph = G.h + (u >> 4) * 7 * 256;
          if (warp == 13) { mbar_expect_tx(BAR(B_HF), 7168); bulk_ld(sb + h_off(3), ph + 768, 2048, BAR(B_HF)); bulk_ld(sb + h_off(5), ph + 1280, 2048, BAR(B_HF)); }
          else { bulk_ld(sb + h_off(0), ph, 1024, BAR(B_HF)); bulk_ld(sb + h_off(1), ph + 256, 1024, BAR(B_HF)); bulk_ld(sb + h_off(2), ph + 512, 1024, BAR(B_HF)); }
        }
        mbar_wait(BAR(B_HF), it & 1);
        uint32_t m = 0;
#pragma unroll
        for (int i = 0; i < 7; i++) m = max(m, lds_u(sb + h_off(i) + (ltid - 416) * 16 + (g >> 1) * 4));
        uint32_t bad;
        asm volatile("{\n.reg .pred p, q;\nsetp.eq.u32 p, %1, 0xFFFFFFFF;\nbar.red.or.pred q, 7, 64, p;\nselp.b32 %0, 1, 0, q;\n}" : "=r"(bad) : "r"(m) : "memory");
        if (!__any_sync(~0u, bad)) break;
        __nanosleep(POLLNS);
      }
      if (warp == 14 && elect_one()) mbar_arrive(BAR(B_KVB));
    }
    __syncwarp();
    if (warp >= 13) {
      const char* og = reinterpret_cast<const char*>(G.o + tb * 16384);
      auto probe = [&](uint32_t m) {
        const char* p = og + m * 8192u + (lane & 15) * 512 + 496;
#pragma unroll 1
        for (uint32_t it = 0; it < SPIN_MAX; it++)
          if (!__any_sync(~0u, ldx1(p) == SENT)) break;
      };
      if (warp == 15) {
        int r = 0, p = 1;
        mbar_wait(BAR(B_EAUX), 0);
#pragma unroll 1
        for (int i = I0; i < 16; i++) {
          const uint32_t dst = sb + ((A_SLOTS >> (4 * r)) & 15u) * SLOT, m0 = slab(2 * i - 4, hg), m1 = slab(2 * i - 3, hg);
          if (i == I0 + 3) mbar_wait(BAR(B_DE), 0);
          mbar_wait(BAR(B_EA + r), p);
          if ((PROBE >> i) & 1) probe(lane < 16 ? m0 : m1);
          if (elect_one()) {
            mbar_expect_tx(BAR(B_AF + r), SLOT);
            bulk_ld(dst, og + m0 * 8192u, 8192, BAR(B_AF + r)); bulk_ld(dst + 8192, og + m1 * 8192u, 8192, BAR(B_AF + r));
          }
          if (++r == NA) { r = 0; p ^= 1; }
        }
      } else {
        const uint32_t lo = lane * 32 + g * 4, hb = sb + (warp - 13) * 8192;
        uint32_t ph = 0;
        int r = 0, p = 0;
#pragma unroll 1
        for (int i = I0; i < 16; i++) {
          const uint32_t mine = hb + ((A_SLOTS >> (4 * r)) & 15u) * SLOT;
          auto bad = [&]() {
            uint32_t v[8];
#pragma unroll
            for (int j = 0; j < 8; j++) v[j] = lds_u(mine + lo + j * 1024);
            return __any_sync(~0u, max(max(max(v[0], v[1]), max(v[2], v[3])), max(max(v[4], v[5]), max(v[6], v[7]))) == SENT);
          };
          mbar_wait(BAR(B_AF + r), p);
          if (!NOVAL && bad()) {
            const uint32_t m = slab(2 * i - 17 + warp, hg);
#pragma unroll 1
            for (uint32_t it = 0; it < 64; it++) {
              probe(m);
              if (elect_one()) { mbar_expect_tx(BAR(B_AR + warp - 13), 8192); bulk_ld(mine, og + m * 8192u, 8192, BAR(B_AR + warp - 13)); }
              mbar_wait(BAR(B_AR + warp - 13), ph);
              ph ^= 1;
              if (!bad()) break;
            }
          }
          if (elect_one()) mbar_arrive(BAR(B_VAL + r));
          if (++r == NA) { r = 0; p ^= 1; }
        }
      }
    }
  } else if (warp >= 8) {
    asm volatile("setmaxnreg.dec.sync.aligned.u32 %0;" ::"n"(MOE_REGS));
    if (MC) asm volatile("barrier.cluster.wait.aligned;" ::: "memory");
    const int aw = warp - 8;
    const uint32_t mbuf = sb + MISC + M_MOE, stg = sb + 12 * SLOT;
    mbar_wait(BAR(B_AST), 0);
    TLS(288, 64);
    {
      float v[16];
#pragma unroll
      for (int r = 0; r < 16; r++) v[r] = 0.f;
      const uint32_t base = stg + aw * 4 * 2048 + lane * 8;
#pragma unroll 1
      for (int c = 0; c < 8; c++) {
        const float2 w2 = lds_f2(mbuf + c * 256 + lane * 8);
        const float w[4] = {bf_lo(__float_as_uint(w2.x)), bf_hi(__float_as_uint(w2.x)), bf_lo(__float_as_uint(w2.y)), bf_hi(__float_as_uint(w2.y))};
        v[12] += (w[0] + w[1]) + (w[2] + w[3]);
#pragma unroll
        for (int r = 0; r < 4; r++) {
          const float2 x2 = lds_f2(base + r * 2048 + c * 256);
#pragma unroll
          for (int e = 0; e < 2; e++) {
            const uint32_t xx = __float_as_uint(e ? x2.y : x2.x);
            const float lo = bf_lo(xx), hi = bf_hi(xx);
            v[r] += lo; v[4 + r] = fmaf(lo, lo, v[4 + r]); v[8 + r] = fmaf(lo, w[2 * e], v[8 + r]);
            v[r] += hi; v[4 + r] = fmaf(hi, hi, v[4 + r]); v[8 + r] = fmaf(hi, w[2 * e + 1], v[8 + r]);
          }
        }
      }
#pragma unroll
      for (int l = 0; l < 4; l++) {
        const int n = 8 >> l;
        const bool up = lane & (2 * n);
#pragma unroll
        for (int r = 0; r < 8; r++) {
          if (r < n) { const float a = v[r], c = v[n + r]; v[r] = (up ? c : a) + __shfl_xor_sync(~0u, up ? a : c, 2 * n); }
        }
      }
      v[0] += __shfl_xor_sync(~0u, v[0], 1);
      const float sx = __shfl_sync(~0u, v[0], 2 * t), sq = __shfl_sync(~0u, v[0], 8 + 2 * t), sw = __shfl_sync(~0u, v[0], 16 + 2 * t), ws = __shfl_sync(~0u, v[0], 24);
      if (lane < 4) {
        const int row = b * 16 + aw * 4 + lane;
        const float mean = sx * (1.f / DM);
        const float var = fmaxf(fmaf(-mean, mean, sq * (1.f / DM)), 0.f);
        float sd;
        asm("sqrt.approx.ftz.f32 %0, %1;" : "=f"(sd) : "f"(bf_round(bf_round(var) + 1e-5f)));
        const float rstd = rcp(bf_round(sd));
        const float mb = bf_round(mean);
        uint32_t rb = pack_bf16(fmaf(-mb, ws, sw) * rstd, 0.f) & 0xFFFFu;
        rb = (rb & 0x8000u) ? (~rb & 0xFFFFu) : (rb | 0x8000u);
        const uint32_t key = (1u << 27) | (rb << 11) | (uint32_t)(2047 - row);
        if (KEY1) sts_u(sb + MISC + M_KEY + (aw * 4 + lane) * 4, key); else stx1(G.key + row, key);
        G.stats[row] = make_float2(mb, SL2 ? rstd * LOG2E : rstd);
      }
    }
    bar_sync<2, 128>();
    if (KEY1 && ltid < 272) stx1(G.key + b * 16 + lane, lds_u(sb + MISC + M_KEY + lane * 4));
    TLS(288, 65);
    sts_u4(sb + A_ONES + (ltid - 256) * 16, make_uint4(0x3F803F80u, 0x3F803F80u, 0x3F803F80u, 0x3F803F80u));
    fence_async_smem();
    asm volatile("bar.arrive 5, 160;" ::: "memory");
    if (ltid == 256) { if (unit && rank == 0) mbar_expect_tx(BAR(B_UP), 2048); mbar_arrive(BAR(B_XS)); }
    bar_sync<2, 128>();
    mbar_wait(BAR(B_XS), 1);
    TLS(288, 70);
    if (NUNIT) {
      if (unit) {
        int r = 0, p = 0;
        uint32_t rel = 0;
        float acc[8];
        uint2 s0, s1;
#pragma unroll
        for (int i = 0; i < 8; i++) acc[i] = 0.f;
        if (MS == 16) mbar_wait(BAR(B_T0), 0); else if (MS) mbar_wait(BAR(B_MS), 0);
#pragma unroll 1
        for (int n = 0; n < 16; n++) {
          if (n == 15) {
            mbar_wait(BAR(B_FAUX), 0);
            s0 = ldx2(G.stats + (~lds_u(sb + MISC + M_IDX + t * 8) & 2047)); s1 = ldx2(G.stats + (~lds_u(sb + MISC + M_IDX + t * 8 + 4) & 2047));
            if (SL2) { s0.y = __float_as_uint(__uint_as_float(s0.y) * LN2); s1.y = __float_as_uint(__uint_as_float(s1.y) * LN2); }
          }
          mbar_wait(BAR(B_MF + r), p);
          if (!(n & 3)) TLS(288, 56 + (n >> 2));
          const uint32_t mo = m_off(r) >> 4, da = (d0 + mo) | (512u << 16), db = (d0 + mo + 512) | (1u << 16);
          const uint32_t hb = 0x40000000u | ((A_ONES >> 4) - 512 - mo);
          wg_fence();
#pragma unroll
          for (int kk = 0; kk < ((MX & 1) ? 1 : 4); kk++) wgmma_ss_n16<1, 0>(acc, mkdesc(da + kk * 128, HI_SW128), mkdesc(db + kk * 2, hb));
          wg_commit();
          wg_wait<1>();
          if (n > 0 && !rel && ltid == 256) mbar_arrive(BAR(B_ME + (r == 0 ? NR - 1 : r - 1)));
          rel = 0;
          const int r0 = r;
          if (++r == NR) { r = 0; p ^= 1; }
        }
        wg_wait<0>();
        reg_fence(acc);
        {
          if (!MW0 && !rel && ltid == 256) mbar_arrive(BAR(B_ME + 15 % NR));
          TLS(288, 71);
          const float v0 = bf_round(fmaf(-__uint_as_float(s0.x), acc[4], acc[0]) * __uint_as_float(s0.y));
          const float v1 = bf_round(fmaf(-__uint_as_float(s1.x), acc[4], acc[1]) * __uint_as_float(s1.y));
          const float v2 = bf_round(fmaf(-__uint_as_float(s0.x), acc[6], acc[2]) * __uint_as_float(s0.y));
          const float v3 = bf_round(fmaf(-__uint_as_float(s1.x), acc[6], acc[3]) * __uint_as_float(s1.y));
          if (rank) {
            asm volatile("{\n.reg .b32 ra, rb;\nmapa.shared::cluster.u32 ra, %0, 0;\nmapa.shared::cluster.u32 rb, %1, 0;\n"
                         "st.async.weak.shared::cluster.mbarrier::complete_tx::bytes.v4.f32 [ra], {%2, %3, %4, %5}, [rb];\n}"
                         ::"r"(mbuf + (ltid - 256) * 16), "r"(BAR(B_UP)), "f"(v0), "f"(v1), "f"(v2), "f"(v3) : "memory");
          } else {
            const float g0 = bf_round(v0 * sigmoid(v0)), g1 = bf_round(v1 * sigmoid(v1)), g2 = bf_round(v2 * sigmoid(v2)), g3 = bf_round(v3 * sigmoid(v3));
            mbar_wait(BAR(B_UP), 0);
            const uint4 uu = lds_u4(mbuf + (ltid - 256) * 16);
            const uint32_t h0 = movmat(pack_bf16(g0 * __uint_as_float(uu.x), g1 * __uint_as_float(uu.y)));
            const uint32_t h1 = movmat(pack_bf16(g2 * __uint_as_float(uu.z), g3 * __uint_as_float(uu.w)));
            uint32_t* ph = G.h + (u >> 1) * 256 + g * 32 + t;
            stx1(ph + ((2 * aw) ^ g) * 4, h0); stx1(ph + ((2 * aw + 1) ^ g) * 4, h1);
          }
          TLS(288, 60);
        }
      }
    }
    if (PH) asm volatile("bar.arrive 3, 192;" ::: "memory");
    {
      const int wd_ = ltid & 63;
      const uint32_t* src = reinterpret_cast<const uint32_t*>(G.part + hg * 544 + (aw >> 1) * 256 + tb * 16) + wd_;
      mbar_wait(MRED == 2 ? BAR(B_ZOK) : BAR(B_EQ + MRW), 0);
      if (MRC) spin_cycles(MRC); else if (MRD) __nanosleep(MRD);
      TLS(256, 48);
      uint32_t v[16];
#pragma unroll 1
      for (uint32_t it = 0; it < SPIN_MAX; it++) {
        uint32_t m = 0;
#pragma unroll
        for (int i = 0; i < 16; i++) v[i] = ldx1(src + i * 8 * 2176);
#pragma unroll
        for (int i = 0; i < 16; i++) m = max(m, v[i]);
        if (!__any_sync(~0u, m == SENT)) break;
      }
      TLS(256, 55);
      float lo[4], hi[4];
#pragma unroll
      for (int i = 0; i < 4; i++) {
        lo[i] = (bf_lo(v[4 * i]) + bf_lo(v[4 * i + 1])) + (bf_lo(v[4 * i + 2]) + bf_lo(v[4 * i + 3]));
        hi[i] = (bf_hi(v[4 * i]) + bf_hi(v[4 * i + 1])) + (bf_hi(v[4 * i + 2]) + bf_hi(v[4 * i + 3]));
      }
      stx1(reinterpret_cast<uint32_t*>(G.fin + hg * 640) + (tb >> 2) * 640 + ((tb >> 1) & 1) * 64 + (tb & 1) * 16 + (aw >> 1) * 32 + ((wd_ >> 2) & 3) * 128 + (wd_ >> 4) * 4 + (wd_ & 3),
           pack_bf16((lo[0] + lo[1]) + (lo[2] + lo[3]), (hi[0] + hi[1]) + (hi[2] + hi[3])));
      TLS(256, 5);
    }
    if (NUNIT) {
      mbar_wait(BAR(B_STG), 0);
      bar_sync<2, 128>();
      if (HW) __nanosleep(HW);
#pragma unroll 1
      for (uint32_t it = 0; it < SPIN_MAX; it++) {
        if (elect_one()) {
          const uint32_t* ph = G.h + (u >> 4) * 7 * 256;
          if (aw == 3) { mbar_expect_tx(BAR(B_HF), 7168); bulk_ld(sb + h_off(3), ph + 768, 2048, BAR(B_HF)); bulk_ld(sb + h_off(5), ph + 1280, 2048, BAR(B_HF)); }
          else bulk_ld(stg + aw * MT + 8192, ph + aw * 256, 1024, BAR(B_HF));
        }
        mbar_wait(BAR(B_HF), it & 1);
        const uint32_t o = (ltid & 63) * 16 + (g >> 1) * 4, o2 = o + (aw >> 1) * 1024;
        const uint32_t m = max(max(lds_u(sb + h_off(0) + (aw >> 1) * MT + o), lds_u(sb + h_off(2) + o)), max(lds_u(sb + h_off(3) + o2), lds_u(sb + h_off(5) + o2)));
        uint32_t bad;
        asm volatile("{\n.reg .pred p, q;\nsetp.eq.u32 p, %1, 0xFFFFFFFF;\nbar.red.or.pred q, 2, 128, p;\nselp.b32 %0, 1, 0, q;\n}" : "=r"(bad) : "r"(m) : "memory");
        if (!__any_sync(~0u, bad)) break;
        __nanosleep(POLLNS);
      }
      TLS(288, 62);
      float acc[4] = {0.f, 0.f, 0.f, 0.f};
      mbar_wait(BAR(B_DF), 0);
      TLS(288, 63);
#pragma unroll 1
      for (int i = 0; i < 7; i++) {
        const uint32_t da = (d0 + (d_off(i) >> 4)) | (512u << 16), db = (d0 + (h_off(i) >> 4)) | (1u << 16);
        wg_fence();
#pragma unroll
        for (int kk = 0; kk < ((MX & 4) ? 1 : 4); kk++) wgmma_ss_n8<1, 0>(acc, mkdesc(da + kk * 128, HI_SW128), mkdesc(db + kk * 2, HI_SW128));
        wg_commit();
      }
      wg_wait<0>();
      reg_fence(acc);
      if (ltid < 258) { if (MC) mbar_arrive_cta(BAR(B_DE), ltid & 1); else mbar_arrive(BAR(B_DE)); }
      {
        uint32_t* py = reinterpret_cast<uint32_t*>(G.y) + u * 512 + t * 128 + aw * 16 + g;
        stx1(py, f2x(acc[0])); stx1(py + 64, f2x(acc[1])); stx1(py + 8, f2x(acc[2])); stx1(py + 72, f2x(acc[3]));
      }
      TLS(288, 69);
      const uint32_t key = lds_u(sb + MISC + M_IDX + (lane & 7) * 4);
      uint32_t rb = (key >> 11) & 0xFFFFu;
      rb = (rb & 0x8000u) ? (rb & 0x7FFFu) : (~rb & 0xFFFFu);
      const float sg = bf_round(sigmoid(__uint_as_float(rb << 16)));
      uint32_t hits = __ballot_sync(~0u, ((~key >> 7) & 15) == tb) & 255u;
      const uint32_t* py = reinterpret_cast<const uint32_t*>(G.y) + (2 * hg + (aw >> 1)) * 512 + (ltid & 63);
      if (hits) {
        sts_u4(mbuf + (ltid - 256) * 16, make_uint4(0, 0, 0, 0));
        bar_sync<2, 128>();
        if (YW >= 0) mbar_wait(BAR(B_EO + YW), 0); else if (YW == -2) mbar_wait(BAR(B_EAUX), 0);
      }
#pragma unroll 1
      while (hits) {
        const int n0 = __ffs(hits) - 1;
        hits &= hits - 1;
        const int n1 = hits ? __ffs(hits) - 1 : n0;
        hits &= hits - 1;
        uint32_t v[16];
#pragma unroll 1
        for (uint32_t it = 0; it < SPIN_MAX; it++) {
          uint32_t m = 0;
#pragma unroll
          for (int i = 0; i < 8; i++) { v[i] = ldx1(py + n0 * 64 + i * 8192); v[8 + i] = ldx1(py + n1 * 64 + i * 8192); }
#pragma unroll
          for (int i = 0; i < 16; i++) m = max(m, v[i]);
          if (!__any_sync(~0u, m == SENT)) break;
          __nanosleep(POLLNS);
        }
#pragma unroll
        for (int e = 0; e < 2; e++) {
          const uint32_t* w8 = v + 8 * e;
          const float y = ((__uint_as_float(w8[0]) + __uint_as_float(w8[1])) + (__uint_as_float(w8[2]) + __uint_as_float(w8[3]))) +
                          ((__uint_as_float(w8[4]) + __uint_as_float(w8[5])) + (__uint_as_float(w8[6]) + __uint_as_float(w8[7])));
          const int n = e ? n1 : n0;
          sts_h(mbuf + (aw >> 1) * 1024 + n * 128 + ((((ltid >> 3) & 7) ^ n) << 4) + (lane & 7) * 2, bf_round(y) * __shfl_sync(~0u, sg, n));
        }
      }
    }
    if (!NUNIT && ltid < 258) mbar_arrive(BAR(B_DE));
    fence_async_smem();
    bar_sync<2, 128>();
    TLS(288, 33);
    if (ltid == 288) mbar_arrive(BAR(B_MOE));
  } else {
    asm volatile("setmaxnreg.inc.sync.aligned.u32 %0;" ::"n"(CON_REGS));
    if (MC) asm volatile("barrier.cluster.wait.aligned;" ::: "memory");
    const int w = warp >> 2, wq = warp & 3, tid = ltid;
    const bool lead = (tid & 127) == 0;
    const uint32_t dA = (d0 + w * 512) | (1u << 16);
    const uint32_t dB = d0 | (512u << 16);
    auto release = [&](int bar) { if (lead) mbar_arrive(BAR(bar)); };
    auto release2 = [&](int bar) {
      if (MC) { if ((tid & 127) < 2) mbar_arrive_cta(BAR(bar), tid & 1); } else release(bar);
    };
    float aq[64], ak[64], av[64];
#pragma unroll
    for (int i = 0; i < 64; i++) aq[i] = ak[i] = av[i] = 0.f;
    auto q_step = [&](uint32_t bar, int p, uint32_t xs, uint32_t qs) {
      mbar_wait_b(bar, p);
      wg_fence();
#pragma unroll
      for (int kk = 0; kk < 4; kk++)
        wgmma_ss_n128<0, 1>(aq, mkdesc(dA + xs * 1024 + kk * 2, HI_SW128), mkdesc(dB + qs * 1024 + kk * 128, HI_SW128));
      wg_commit();
    };
    const uint32_t dT = dB + w * 512, dX = d0 | (1u << 16);
    auto t_step = [&](float (&a)[64], uint32_t ws, uint32_t xs) {
      wg_fence();
#pragma unroll
      for (int kk = 0; kk < 4; kk++)
        wgmma_ss_n128<1, 0>(a, mkdesc(dT + ws * 1024 + kk * 128, HI_SW128), mkdesc(dX + xs * 1024 + kk * 2, HI_SW128));
      wg_commit();
    };
    {
      int s = 0, p = 0, sp = 2;
#pragma unroll 1
      for (int e = 0; e < NF; e++) {
        TLS(0, 16 + e);
        if (((MS && MS < NF) || (DS && DS < NF)) && e == (MS ? MS : DS)) release(B_MS);
        q_step(BAR(B_FXQ + s), p, s, 3 + s);
        wg_wait<1>();
        if (e > 0) release2(B_E + sp);
        mbar_wait(BAR(B_FKV + s), p);
        t_step(ak, 6 + 2 * s, s);
        if (R5) mbar_wait(BAR(B_FV + s), p);
        t_step(av, 7 + 2 * s, s);
        if (R5 && e == NF - 1) { wg_wait<1>(); release2(B_EK + s); }
        sp = s;
        if (++s == 3) { s = 0; p ^= 1; }
      }
#pragma unroll 1
      for (int e = NF; e < 16; e++) {
        TLS(0, 16 + e);
        if (((MS >= NF && MS < 16) || DS >= NF) && e == (MS ? MS : DS)) release(B_MS);
        if (ST && e == 16 - ST && w == 1) mbar_wait(BAR(B_GT), 0);
        mbar_wait(BAR(B_FXQ + s), p);
        mbar_wait(BAR(B_FKV + s), p);
        t_step(ak, R5 ? (K_SLOTS >> (4 * (e - 10))) & 15u : 6 + 2 * s, x_slot(e, s));
        wg_wait<1>();
        release2(B_E + sp);
        if (R5) mbar_wait(BAR(B_FV + s), p);
        t_step(av, R5 ? (V_SLOTS >> (4 * (e - 10))) & 15u : 7 + 2 * s, x_slot(e, s));
        if (ST && e == 15 && tid == 0) mbar_arrive(BAR(B_GT));
        if (R5) { wg_wait<1>(); release2(B_EK + s); }
        sp = s;
        if (++s == 3) { s = 0; p ^= 1; }
      }
    }
    const uint32_t aux = sb;
    mbar_wait(BAR(B_FAUX), 0);
    const int row0 = w * 64 + wq * 16 + g;
    const float ck0 = lds_f(aux + A_CS + 512 + row0 * 4), ck1 = lds_f(aux + A_CS + 512 + (row0 + 8) * 4);
    const float cv0 = lds_f(aux + A_CS + 1024 + row0 * 4), cv1 = lds_f(aux + A_CS + 1024 + (row0 + 8) * 4);
    const uint32_t moff = (uint32_t)(w * 64 + wq * 16 + (lane & 15)) * 128 + (((lane >> 4) ^ (lane & 7)) << 4);
    const uint32_t sta = aux + A_ST + t * 16;
    float kvp[36], ao[64];
    uint32_t xr[32];
    float nm0, nm1, rs0, rs1, rl0, rl1;
    auto row_stats = [&]() {
      const float2 st0 = lds_f2(aux + A_ST + row0 * 8), st1 = lds_f2(aux + A_ST + (row0 + 8) * 8);
      nm0 = -st0.x; nm1 = -st1.x;
      if (SL2) { rl0 = st0.y; rl1 = st1.y; rs0 = rl0 * LN2; rs1 = rl1 * LN2; }
      else { rs0 = st0.y; rs1 = st1.y; rl0 = rs0 * LOG2E; rl1 = rs1 * LOG2E; }
    };
    auto ld_x = [&]() {
#pragma unroll
      for (int j = 0; j < 16; j += 2) ldsm4(sb + (j < 8 ? SX14 : SX15) * SLOT + (moff ^ ((j & 7) << 4)), xr[2 * j], xr[2 * j + 1], xr[2 * j + 2], xr[2 * j + 3]);
    };
    auto resid = [&]() {
      const float c0 = 1.f + rs0, c1 = 1.f + rs1, e0 = nm0 * rs0, e1 = nm1 * rs1;
#pragma unroll
      for (int j = 0; j < 16; j++) {
        ao[4 * j + 0] = fmaf(bf_lo(xr[2 * j]), c0, e0); ao[4 * j + 1] = fmaf(bf_hi(xr[2 * j]), c0, e0);
        ao[4 * j + 2] = fmaf(bf_lo(xr[2 * j + 1]), c1, e1); ao[4 * j + 3] = fmaf(bf_hi(xr[2 * j + 1]), c1, e1);
      }
    };
    {
      uint32_t pa[32];
      float4 st[16];
      auto ld = [&](int j) { st[j] = lds_f4(sta + j * 64); };
      auto k_blk = [&](int c) {
#pragma unroll
        for (int i = 0; i < 2; i++) {
          const float4 u = st[2 * c + i];
          const float l0 = u.y * LOG2E, l1 = u.w * LOG2E;
          const float* a = ak + 8 * c + 4 * i;
          pa[4 * c + 2 * i] = SL2 ? phi2l(FOLD(-u.x, ck0, a[0]), u.y, FOLD(-u.z, ck0, a[1]), u.w) : phi2<(VOL & 1) != 0>(FOLD(-u.x, ck0, a[0]), u.y, l0, FOLD(-u.z, ck0, a[1]), u.w, l1);
          pa[4 * c + 2 * i + 1] = SL2 ? phi2l(FOLD(-u.x, ck1, a[2]), u.y, FOLD(-u.z, ck1, a[3]), u.w) : phi2<(VOL & 1) != 0>(FOLD(-u.x, ck1, a[2]), u.y, l0, FOLD(-u.z, ck1, a[3]), u.w, l1);
        }
      };
      const uint32_t voff = sb + w * 8192 + (uint32_t)(8 * (lane >> 4) + (lane & 7)) * 128 + (((2 * wq + ((lane >> 3) & 1)) ^ (lane & 7)) << 4);
      auto v_blk = [&](int c) {
        uint32_t r[4];
#pragma unroll
        for (int i = 0; i < 2; i++) {
          const float4 u = st[2 * c + i];
          const float* a = av + 8 * c + 4 * i;
          r[2 * i] = pack_bf16(FOLD(-u.x, cv0, a[0]) * u.y, FOLD(-u.z, cv0, a[1]) * u.w);
          r[2 * i + 1] = pack_bf16(FOLD(-u.x, cv1, a[2]) * u.y, FOLD(-u.z, cv1, a[3]) * u.w);
        }
        stsm4t(voff + (c < 4 ? S_V0 : S_V1) * SLOT + (c & 3) * 2048, r[0], r[1], r[2], r[3]);
      };
      auto kv_mma = [&](int c) {
        const uint32_t bo = (c < 4 ? S_V0 : S_V1) * 1024 + w * 512 + (c & 3) * 128;
        const uint64_t bb = mkdesc((d0 + bo) | (((A_ONES >> 4) - bo) << 16), HI_SW128);
        if (c == 0) wgmma_rz_n72<1>(kvp, pa[4 * c], pa[4 * c + 1], pa[4 * c + 2], pa[4 * c + 3], bb);
        else wgmma_rs_n72<1>(kvp, pa[4 * c], pa[4 * c + 1], pa[4 * c + 2], pa[4 * c + 3], bb);
      };
      if (NOFOLD == 2) {
        wg_fence();
        wgmma_rs_n128<0>(ak, __float_as_uint(ck0), __float_as_uint(ck1), 0u, 0u, mkdesc(dX + SX14 * 1024, HI_SW128));
        wgmma_rs_n128<0>(av, __float_as_uint(cv0), __float_as_uint(cv1), 0u, 0u, mkdesc(dX + SX14 * 1024, HI_SW128));
        wg_commit();
      }
      if (SH2 && R5) {
        reg_fence(ak);
        ld(6); ld(7); k_blk(3);
        asm volatile("" : "+r"(pa[12]), "+r"(pa[13]), "+r"(pa[14]), "+r"(pa[15]));
      }
      ld(0); ld(1);
      wg_wait<0>();
      if (!(SH2 && R5)) reg_fence(ak);
      reg_fence(av);
      TLS(0, 2);
      if (!R5) release2(B_E);
      release(B_T0);
      if (LQ) { v_blk(0); ld(2); ld(3); } else { ld(2); ld(3); v_blk(0); }
      ld(4); ld(5); v_blk(1); k_blk(0);
      ld(6); ld(7); v_blk(2); ld(8); ld(9); v_blk(3); k_blk(1);
      ld(10); ld(11); v_blk(4); ld(12); ld(13); v_blk(5); k_blk(2);
      ld(14); ld(15); v_blk(6); v_blk(7); if (!(SH2 && R5)) k_blk(3);
      if (RL) { ld(8); ld(9); }
#pragma unroll
      for (int c = 4; c < KS; c++) k_blk(c);
      TLS(0, 3);
      fence_async_smem();
      asm volatile("bar.sync %0, 128;" ::"r"(3 + w) : "memory");
      if (XP == 0) ld_x();
      wg_fence();
#pragma unroll
      for (int c = 0; c < KS; c++) kv_mma(c);
      wg_commit();
#pragma unroll
      for (int c = KS; c < 8; c++) {
        if (RL && c < 7) { ld(2 * c + 2); ld(2 * c + 3); }
        k_blk(c);
        wg_fence();
        kv_mma(c);
        wg_commit();
      }
      if (XP == 3 && (RK == 0 || RK == 9)) ld_x();
      if (QE) { q_step(BAR(B_FQ), 0, SXQ0, QW_SLOTS & 15u); wg_wait<1>(); } else wg_wait<0>();
      reg_fence(kvp);
      auto hand_back = [&]() { release2(B_STG); __syncwarp(); };
      if (!SF) hand_back();
      TLS(0, 4);
      uint4* pp = G.part + b * 544;
      uint32_t pk[8];
#pragma unroll
      for (int j = 0; j < 8; j++) pk[j] = wq >= 2 ? pack_bf16(kvp[16 + 2 * j], kvp[17 + 2 * j]) : pack_bf16(kvp[2 * j], kvp[2 * j + 1]);
      stx4(pp + tid, pk[0], pk[2], pk[4], pk[6]);
      stx4(pp + 256 + tid, pk[1], pk[3], pk[5], pk[7]);
      if (t == 0) stx2(reinterpret_cast<uint2*>(pp + 512) + (tid >> 2), f2x(kvp[32]), f2x(kvp[34]));
      if (SF == 1) hand_back();
      if (XP == 1) ld_x();
      if (!QE) q_step(BAR(B_FQ), 0, SXQ0, QW_SLOTS & 15u);
      if (XP == 2) ld_x();
      if (SF == 2) hand_back();
      if (RK == 0 || RK == 9) {
        uint32_t chk = 0;
#pragma unroll
        for (int j = 0; j < 8; j++) chk ^= xr[4 * j];
        asm volatile("{\n.reg .pred p;\nsetp.eq.u32 p, %0, 0x7FC17FC3;\n@p st.shared.u32 [%1], %0;\n}" ::"r"(chk), "r"(sb + MISC + M_DUM) : "memory");
      }
      const int wd_ = wq * 16 + (lane & 15);
      const uint32_t* src = reinterpret_cast<const uint32_t*>(G.part + ((lane >> 4) * 64 + hg) * 544 + w * 256 + tb * 16) + wd_;
      uint32_t* fin = reinterpret_cast<uint32_t*>(G.fin + hg * 640) + (tb >> 2) * 640 + ((tb >> 1) & 1) * 64 + (tb & 1) * 16 + w * 32 + ((wd_ >> 2) & 3) * 128 + wq * 4 + (wd_ & 3);
      uint32_t v[8];
      auto part_load = [&]() {
#pragma unroll
        for (int i = 0; i < 8; i++) v[i] = ldx1(src + i * 8 * 2176);
      };
#pragma unroll
      for (int k = 1; k < NQ; k++) {
        if (SQ && k == NQ - SQ && w == 1) mbar_wait(BAR(B_GQ), 0);
        q_step(BAR(B_FQ + k), 0, (QX_SLOTS >> (4 * k)) & 15u, (QW_SLOTS >> (4 * k)) & 15u);
        if (SQ && k == NQ - 1 && tid == 0) mbar_arrive(BAR(B_GQ));
        TLS(0, 48 + k);
        if (!MRED && k == PLP) part_load();
        if (!MRED && k == PLC) {
#pragma unroll 1
          for (uint32_t it = 0; it < SPIN_MAX; it++) {
            if (!__any_sync(~0u, max(max(max(v[0], v[1]), max(v[2], v[3])), max(max(v[4], v[5]), max(v[6], v[7]))) == SENT)) break;
            part_load();
          }
          float lo = ((bf_lo(v[0]) + bf_lo(v[1])) + (bf_lo(v[2]) + bf_lo(v[3]))) + ((bf_lo(v[4]) + bf_lo(v[5])) + (bf_lo(v[6]) + bf_lo(v[7])));
          float hi = ((bf_hi(v[0]) + bf_hi(v[1])) + (bf_hi(v[2]) + bf_hi(v[3]))) + ((bf_hi(v[4]) + bf_hi(v[5])) + (bf_hi(v[6]) + bf_hi(v[7])));
          lo += __shfl_xor_sync(~0u, lo, 16); hi += __shfl_xor_sync(~0u, hi, 16);
          if (lane < 16) stx1(fin, pack_bf16(lo, hi));
          TLS(0, 5);
        }
        wg_wait<1>();
        release2(B_EQ + k - 1);
        if (k == RK) { row_stats(); ld_x(); resid(); reg_fence(ao); }
      }
      TLS(0, 13);
      if (!NOCQ) mbar_wait(BAR(B_CQ), 0);
    }
    float4 cq4[8];
    auto ld_cq = [&](int j) {
      if (CQ4) cq4[j >> 1] = lds_f4(aux + A_CS + (j * 8 + 4 * t) * 4);
      else { const float2 ca = lds_f2(aux + A_CS + (j * 8 + 2 * t) * 4), cb = lds_f2(aux + A_CS + (j * 8 + 8 + 2 * t) * 4); cq4[j >> 1] = make_float4(ca.x, ca.y, cb.x, cb.y); }
    };
    if (CQE) {
      if (RK == 0 || RK == 9) row_stats();
#pragma unroll
      for (int j = 0; j < 16; j += 2) ld_cq(j);
    }
    wg_wait<0>();
    reg_fence(aq);
    TLS(0, 15);
    if (!CQE && (RK == 0 || RK == 9)) row_stats();
    uint32_t pq[32];
#pragma unroll
    for (int j = 0; j < 16; j += 2) {
      if (!CQE) ld_cq(j);
      const float4 c4 = cq4[j >> 1];
#pragma unroll
      for (int i = 0; i < 2; i++) {
        const float cx = i ? c4.z : c4.x, cy = i ? c4.w : c4.y;
        const float* a = aq + 4 * (j + i);
        pq[2 * (j + i)] = SL2 ? phi2l(fmaf(nm0, cx, a[0]), rl0, fmaf(nm0, cy, a[1]), rl0) : phi2<(VOL & 2) != 0>(fmaf(nm0, cx, a[0]), rs0, rl0, fmaf(nm0, cy, a[1]), rs0, rl0);
        pq[2 * (j + i) + 1] = SL2 ? phi2l(fmaf(nm1, cx, a[2]), rl1, fmaf(nm1, cy, a[3]), rl1) : phi2<(VOL & 2) != 0>(fmaf(nm1, cx, a[2]), rs1, rl1, fmaf(nm1, cy, a[3]), rs1, rl1);
      }
    }
    TLS(0, 6);
    if (RK == 9) { resid(); if (RF) reg_fence(ao); }
    mbar_wait_b(BAR(MFIN ? B_KV4 : B_KVB), 0);
    TLS(0, 7);
    uint32_t of[32];
    uint4* mine = G.o + (tb * 32 + hg) * 512 + warp * 64 + g * 4 + (t ^ (g >> 1));
    const uint32_t dW = d0 | (256u << 16);
    auto o_store = [&](int h) {
#pragma unroll
      for (int c = 0; c < 2; c++) stx4(mine + h * 4096 + c * 32, of[8 * h + c], of[8 * h + 2 + c], of[8 * h + 4 + c], of[8 * h + 6 + c]);
    };
    auto out_step = [&](uint32_t slot, const uint32_t* a) {
      const uint32_t d = dW + slot * 1024;
      wg_fence();
#pragma unroll
      for (int kk = 0; kk < 4; kk++) wgmma_rs_n128<1>(ao, a[4 * kk], a[4 * kk + 1], a[4 * kk + 2], a[4 * kk + 3], mkdesc(d + (kk >> 1) * 512 + (kk & 1) * 128, HI_SW128));
      wg_commit();
    };
    uint4 v[NDIR][4];
    auto ld_o = [&](int k) {
      const uint4* p0 = mine + (slab(2 * k, hg) - hg) * 512;
      const uint4* p1 = mine + (slab(2 * k + 1, hg) - hg) * 512;
      v[k][0] = ldx4(p0); v[k][1] = ldx4(p0 + 32); v[k][2] = ldx4(p1); v[k][3] = ldx4(p1 + 32);
    };
    auto ld_all = [&]() {
#pragma unroll
      for (int k = 0; k < NDIR; k++) ld_o(k);
    };
    {
      float oa[4][20];
      const uint32_t dK = (d0 + S_KVB * 1024) | (8u << 16);
      wg_fence();
#pragma unroll
      for (int h = 0; h < 4; h++) {
        wgmma_rz_n40<1>(oa[h], pq[8 * h], pq[8 * h + 1], pq[8 * h + 2], pq[8 * h + 3], mkdesc(dK + h * 160, HI_NOSW));
        wgmma_rs_n40<1>(oa[h], pq[8 * h + 4], pq[8 * h + 5], pq[8 * h + 6], pq[8 * h + 7], mkdesc(dK + h * 160 + 16, HI_NOSW));
        if (h == 0 || h == 3) wg_commit();
      }
      auto norm = [&](int h) {
        const float r0 = SL2 ? rcp(fmaf(oa[h][16], LOG2E, 1e-6f * LOG2E)) : rcp(oa[h][16] + 1e-6f);
        const float r1 = SL2 ? rcp(fmaf(oa[h][18], LOG2E, 1e-6f * LOG2E)) : rcp(oa[h][18] + 1e-6f);
#pragma unroll
        for (int j = 0; j < 4; j++) {
          of[8 * h + 2 * j] = pack_bf16(oa[h][4 * j] * r0, oa[h][4 * j + 1] * r0);
          of[8 * h + 2 * j + 1] = pack_bf16(oa[h][4 * j + 2] * r1, oa[h][4 * j + 3] * r1);
        }
      };
      wg_wait<1>();
      reg_fence(oa[0]);
      norm(0);
      if (LE == 4) ld_all();
      o_store(0);
      if (LE == 3) ld_all();
      TLS(0, 8);
      wg_wait<0>();
      reg_fence(oa[1]); reg_fence(oa[2]); reg_fence(oa[3]);
      TLP_(0);
      release(B_EAUX);
      norm(1);
      if (OS1 == 3) o_store(1);
      if (E7 && NP == 0 && SL7 && hg == 7) o_store(1);
      if (NP == 0) { norm(2); norm(3); }
      if (E7 && NP == 0 && SL7 && hg == 7) { o_store(2); o_store(3); }
      TLP_(1);
      mbar_wait_b(BAR(B_FWO), 0);
      TLP_(2);
      if (RK == 0) resid();
      if (LE == 2) ld_all();
      TLP_(3);
      out_step(WO_SLOTS & 15u, of);
      TLP_(4);
      if (NP == 1) { norm(2); norm(3); }
      if (LE == 1) ld_all();
      if (LE == 5) ld_o(0);
    }
    if (OS1 == 0) o_store(1);
    mbar_wait(BAR(B_FWO + 1), 0);
    TLP_(5);
    out_step((WO_SLOTS >> 4) & 15u, of + 16);
    TLP_(6);
    const bool early = SL7 && hg == 7;
    if (OS1 == 1 && !(E7 && early)) o_store(1);
    TLP_(7);
    if (early && !E7) { o_store(2); o_store(3); }
    {
      if (DW) __nanosleep(DW);
      if (LE == 0) ld_all();
      if (LE == 5 && NDIR > 1) ld_o(NDIR - 1);
      if (OS1 == 2 && !(E7 && early)) o_store(1);
#pragma unroll
      for (int k = 0; k < NDIR; k++) {
#pragma unroll 1
        for (uint32_t it = 0; it < SPIN_MAX; it++) {
          if (!__any_sync(~0u, max(max(v[k][0].x, v[k][1].x), max(v[k][2].x, v[k][3].x)) == SENT)) break;
#pragma unroll
          for (int j = k; j < (LE == 5 ? k + 1 : NDIR); j++) ld_o(j);
        }
        TLP_(8);
        const uint32_t a[16] = {v[k][0].x, v[k][1].x, v[k][0].y, v[k][1].y, v[k][0].z, v[k][1].z, v[k][0].w, v[k][1].w,
                                v[k][2].x, v[k][3].x, v[k][2].y, v[k][3].y, v[k][2].z, v[k][3].z, v[k][2].w, v[k][3].w};
        mbar_wait(BAR(B_FWO + 2 + k), 0);
        TLS(0, 34 + k);
        out_step((WO_SLOTS >> (8 + 4 * k)) & 15u, a);
        TLP_(9);
        if (k) { wg_wait<1>(); release2(B_EO); }
      }
      if (!early) o_store(2);
    }
    auto routed = [&]() {
      mbar_wait(BAR(B_MOE), 0);
      const float2 kk = lds_f2(sb + MISC + M_IDX + t * 8);
      const int k0 = (int)(~__float_as_uint(kk.x) & 2047u) - tb * 128, k1 = (int)(~__float_as_uint(kk.y) & 2047u) - tb * 128;
      if (NUNIT && __any_sync(~0u, (k0 >> 6) == w || (k1 >> 6) == w)) {
        const uint32_t a0 = (k0 == row0 ? 0x3F80u : 0u) | (k1 == row0 ? 0x3F800000u : 0u);
        const uint32_t a1 = (k0 == row0 + 8 ? 0x3F80u : 0u) | (k1 == row0 + 8 ? 0x3F800000u : 0u);
        wg_fence();
        wgmma_rs_n128<1>(ao, a0, a1, 0u, 0u, mkdesc((d0 + ((MISC + M_MOE) >> 4)) | (64u << 16), 0x40000000u));
        wg_commit();
      }
    };
    auto out_half = [&](int h, const float* v) {
      const uint32_t ost = sb + (w ? S_D1 : S_D0) * SLOT + wq * 4096 + h * 2048;
#pragma unroll
      for (int j = 0; j < 8; j += 2)
        stsm4(ost + ((moff & 2047) ^ (j << 4)), pack_bf16(v[4 * j], v[4 * j + 1]), pack_bf16(v[4 * j + 2], v[4 * j + 3]),
              pack_bf16(v[4 * j + 4], v[4 * j + 5]), pack_bf16(v[4 * j + 6], v[4 * j + 7]));
      if (OUTV == 3 || (OUTV == 4 && h == 0)) {
        __syncwarp();
        __nv_bfloat16* dst = outp + (size_t)(tb * 128 + warp * 16 + (lane >> 3)) * DM + hg * 128 + h * 64 + (lane & 7) * 8;
#pragma unroll
        for (int i = 0; i < 4; i++) {
          const int r = 4 * i + (lane >> 3);
          const uint4 u4 = lds_u4(ost + r * 128 + (((lane & 7) ^ (r & 7)) << 4));
          asm volatile("st.global.v4.u32 [%0], {%1,%2,%3,%4};" ::"l"(dst + (size_t)i * 4 * DM), "r"(u4.x), "r"(u4.y), "r"(u4.z), "r"(u4.w) : "memory");
        }
        return;
      }
      fence_async_smem();
      __syncwarp();
      if (elect_one()) {
        if (OEF) asm volatile("cp.async.bulk.tensor.2d.global.shared::cta.bulk_group.L2::cache_hint [%0, {%2, %3}], [%1], %4;" ::"l"(&tmOut), "r"(ost), "r"(hg * 128 + h * 64), "r"(tb * 128 + warp * 16), "l"(POL_FIRST) : "memory");
        else asm volatile("cp.async.bulk.tensor.2d.global.shared::cta.bulk_group [%0, {%2, %3}], [%1];" ::"l"(&tmOut), "r"(ost), "r"(hg * 128 + h * 64), "r"(tb * 128 + warp * 16) : "memory");
        if (h) asm volatile("cp.async.bulk.commit_group;\ncp.async.bulk.wait_group.read 0;" ::: "memory");
      }
      __syncwarp();
    };
    bool done = false;
    {
      const uint32_t dO = (d0 + w * 256) | (1u << 16);
      auto step = [&](int i, int r, int p, uint32_t as, uint32_t ws) {
        mbar_wait(BAR(B_FWO + i), 0);
        mbar_wait(BAR(B_VAL + r), p);
        TLS(0, 32 + i);
        const uint32_t da = dO + as * 1024, db = dW + ws * 1024;
        wg_fence();
#pragma unroll
        for (int kk = 0; kk < 4; kk++)
          wgmma_ss_n128<0, 1>(ao, mkdesc(da + (kk >> 1) * 512 + (kk & 1) * 2, HI_SW64), mkdesc(db + (kk >> 1) * 512 + (kk & 1) * 128, HI_SW128));
        wg_commit();
      };
      uint64_t tbl = WO_SLOTS >> (4 * I0);
      int r = 0, p = 0, rp = 0;
#pragma unroll 1
      for (int i = I0; i < 12; i++) {
        step(i, r, p, (A_SLOTS >> (4 * r)) & 15u, (uint32_t)tbl & 15u);
        tbl >>= 4;
#pragma unroll
        for (int c = 0; c < 2; c++)
          if (i == OS3 + c && !early) stx4(mine + 3 * 4096 + c * 32, of[24 + c], of[26 + c], of[28 + c], of[30 + c]);
        wg_wait<1>();
        if (i > I0) release(B_EA + rp);
        rp = r;
        if (++r == NA) { r = 0; p ^= 1; }
        if (i >= 3 && i <= 9) release2(B_EO + i - 3);
      }
      if (SPL && w == 1) {
        float bl[32], bh[32];
        mbar_wait(BAR(B_GO), 0);
        routed();
#pragma unroll
        for (int h = 0; h < 2; h++) {
#pragma unroll
          for (int i = 12; i < 16; i++) {
            const int r_ = (i - I0) % NA;
            if (h == 0) { mbar_wait(BAR(B_FWO + i), 0); mbar_wait(BAR(B_VAL + r_), ((i - I0) / NA) & 1); }
            const uint32_t da = dO + ((A_SLOTS >> (4 * r_)) & 15u) * 1024, db = dW + ((uint32_t)(WO_SLOTS >> (4 * i)) & 15u) * 1024 + h * 256;
            if (h == 0 || i == 12) wg_fence();
#pragma unroll
            for (int kk = 0; kk < 4; kk++) {
              const uint64_t a = mkdesc(da + (kk >> 1) * 512 + (kk & 1) * 2, HI_SW64), bb = mkdesc(db + (kk >> 1) * 512 + (kk & 1) * 128, HI_SW128);
              if (i == 12 && kk == 0) wgmma_sz_n64<0, 1>(h ? bh : bl, a, bb); else wgmma_ss_n64<0, 1>(h ? bh : bl, a, bb);
            }
          }
          wg_commit();
        }
        wg_wait<1>();
        reg_fence(ao); reg_fence(bl);
#pragma unroll
        for (int j = 0; j < 32; j++) bl[j] += ao[j];
        out_half(0, bl);
        wg_wait<0>();
        reg_fence(bh);
#pragma unroll
        for (int j = 0; j < 32; j++) bh[j] += ao[32 + j];
        out_half(1, bh);
        done = true;
      } else
#pragma unroll
      for (int i = 12; i < 16; i++) {
        if (i == 16 - STAG && w == 1) mbar_wait(BAR(B_GO), 0);
        step(i, (i - I0) % NA, ((i - I0) / NA) & 1, (A_SLOTS >> (4 * ((i - I0) % NA))) & 15u, (uint32_t)(WO_SLOTS >> (4 * i)) & 15u);
        if (STAG && i == 15 - GOE && tid == 0) mbar_arrive(BAR(B_GO));
      }
    }
    if (!done) {
      routed();
      wg_wait<0>();
      reg_fence(ao);
      TLS(0, 10);
      out_half(0, ao);
      out_half(1, ao + 32);
    }
    TLS(0, 11);
    TLS(128, 9);
  }
}

typedef CUresult (*EncFn)(CUtensorMap*, CUtensorMapDataType, cuuint32_t, void*, const cuuint64_t*, const cuuint64_t*, const cuuint32_t*,
                          const cuuint32_t*, CUtensorMapInterleave, CUtensorMapSwizzle, CUtensorMapL2promotion, CUtensorMapFloatOOBfill);

void make_map2(EncFn enc, CUtensorMap* m, void* p, uint64_t rows, uint64_t cols, uint32_t brows, CUtensorMapL2promotion promo) {
  cuuint64_t gd[2] = {cols, rows}, gs[1] = {cols * 2};
  cuuint32_t bd[2] = {64, brows}, es[2] = {1, 1};
  enc(m, CU_TENSOR_MAP_DATA_TYPE_BFLOAT16, 2, p, gd, gs, bd, es, CU_TENSOR_MAP_INTERLEAVE_NONE, CU_TENSOR_MAP_SWIZZLE_128B, promo,
      CU_TENSOR_MAP_FLOAT_OOB_FILL_NONE);
}
void make_map3(EncFn enc, CUtensorMap* m, void* p, uint64_t rows, uint64_t cols, uint32_t brows) {
  cuuint64_t gd[3] = {64, rows, cols / 64}, gs[2] = {cols * 2, 128};
  cuuint32_t bd[3] = {64, brows, 2}, es[3] = {1, 1, 1};
  enc(m, CU_TENSOR_MAP_DATA_TYPE_BFLOAT16, 3, p, gd, gs, bd, es, CU_TENSOR_MAP_INTERLEAVE_NONE, CU_TENSOR_MAP_SWIZZLE_128B,
      CU_TENSOR_MAP_L2_PROMOTION_L2_256B, CU_TENSOR_MAP_FLOAT_OOB_FILL_NONE);
}

}

extern "C" void kernel_launch(void* const* d_in, const int* in_sizes, int n_in, void* d_out, int out_size) {
  static EncFn enc = nullptr;
  static int by_sm = 0;
  if (!enc) {
    void* fn = nullptr;
    cudaDriverEntryPointQueryResult qr;
    cudaGetDriverEntryPoint("cuTensorMapEncodeTiled", &fn, cudaEnableDefault, &qr);
    enc = (EncFn)fn;
    int dev = 0, sms = 0;
    cudaGetDevice(&dev);
    cudaDeviceGetAttribute(&sms, cudaDevAttrMultiProcessorCount, dev);
    by_sm = MAP == 2 && sms == NCTA + NSVC;
    cudaFuncSetAttribute(fused_kernel, cudaFuncAttributeMaxDynamicSharedMemorySize, SMEM_BYTES);
  }
  CUtensorMap tmX, tmW, tmWo, tmOut, tmG, tmU, tmD, tmR, tmWp;
  {
    cuuint64_t gd[5] = {64, 2, 128, 4, 16}, gs[4] = {2048, 16384, 4096, 128};
    cuuint32_t bd[5] = {64, 2, 4, 4, 2}, es[5] = {1, 1, 1, 1, 1};
    enc(&tmWp, CU_TENSOR_MAP_DATA_TYPE_BFLOAT16, 5, d_in[2], gd, gs, bd, es, CU_TENSOR_MAP_INTERLEAVE_NONE, CU_TENSOR_MAP_SWIZZLE_128B,
        CU_TENSOR_MAP_L2_PROMOTION_L2_256B, CU_TENSOR_MAP_FLOAT_OOB_FILL_NONE);
  }
  make_map2(enc, &tmR, d_in[0], SEQ, DM, 1, CU_TENSOR_MAP_L2_PROMOTION_L2_128B);
  make_map2(enc, &tmX, d_in[0], SEQ, DM, 128, XPROMO);
  make_map3(enc, &tmW, d_in[1], DM, 3 * DM, 64);
  make_map3(enc, &tmWo, d_in[2], DM, DM, 32);
  if (OUTV) make_map2(enc, &tmOut, d_out, SEQ, DM, 16, CU_TENSOR_MAP_L2_PROMOTION_L2_128B); else make_map3(enc, &tmOut, d_out, SEQ, DM, 64);
  make_map2(enc, &tmG, d_in[5], DM, FF, 64, MPROMO);
  make_map2(enc, &tmU, d_in[6], DM, FF, 64, MPROMO);
  make_map2(enc, &tmD, d_in[7], FF, DM, 64, MPROMO);
  typedef const __nv_bfloat16* P;
  cudaLaunchConfig_t cfg = {};
  cfg.gridDim = dim3(NCTA + NSVC); cfg.blockDim = dim3(512); cfg.dynamicSmemBytes = SMEM_BYTES; cfg.stream = cudaStreamPerThread;
  cudaLaunchAttribute at[1];
  at[0].id = cudaLaunchAttributeClusterDimension;
  at[0].val.clusterDim.x = 2; at[0].val.clusterDim.y = 1; at[0].val.clusterDim.z = 1;
  cfg.attrs = at; cfg.numAttrs = 1;
  cudaLaunchKernelEx(&cfg, fused_kernel, (P)d_in[0], (P)d_in[1], (P)d_in[2], (P)d_in[4], (P)d_in[7], (__nv_bfloat16*)d_out, by_sm, tmX, tmW, tmWo, tmOut, tmG, tmU, tmD, tmR, tmWp);
}
```

```cpp
#include <cuda_runtime.h>
#include <cuda.h>
#include <cuda_bf16.h>
#include <stdint.h>

#define WK 0
#define NOCQ 0
#define NOFOLD 0
#define FOLD(m, c, a) fmaf(m, c, a)
#define OEF 0
namespace {

template <int TA, int TB> __device__ __forceinline__ void wgmma_ss_n128(float (&d)[64], uint64_t da, uint64_t db) {
  asm volatile("wgmma.mma_async.sync.aligned.m64n128k16.f32.bf16.bf16 "
  "{%0,%1,%2,%3,%4,%5,%6,%7,%8,%9,%10,%11,%12,%13,%14,%15,%16,%17,%18,%19,%20,%21,%22,%23,%24,%25,%26,%27,%28,%29,%30,%31,%32,%33,%34,%35,%36,%37,%38,%39,%40,%41,%42,%43,%44,%45,%46,%47,%48,%49,%50,%51,%52,%53,%54,%55,%56,%57,%58,%59,%60,%61,%62,%63}, "
  "%64, %65, 1, 1, 1, %66, %67;"
  : "+f"(d[0]),"+f"(d[1]),"+f"(d[2]),"+f"(d[3]),"+f"(d[4]),"+f"(d[5]),"+f"(d[6]),"+f"(d[7]),"+f"(d[8]),"+f"(d[9]),"+f"(d[10]),"+f"(d[11]),"+f"(d[12]),"+f"(d[13]),"+f"(d[14]),"+f"(d[15]),"+f"(d[16]),"+f"(d[17]),"+f"(d[18]),"+f"(d[19]),"+f"(d[20]),"+f"(d[21]),"+f"(d[22]),"+f"(d[23]),"+f"(d[24]),"+f"(d[25]),"+f"(d[26]),"+f"(d[27]),"+f"(d[28]),"+f"(d[29]),"+f"(d[30]),"+f"(d[31]),"+f"(d[32]),"+f"(d[33]),"+f"(d[34]),"+f"(d[35]),"+f"(d[36]),"+f"(d[37]),"+f"(d[38]),"+f"(d[39]),"+f"(d[40]),"+f"(d[41]),"+f"(d[42]),"+f"(d[43]),"+f"(d[44]),"+f"(d[45]),"+f"(d[46]),"+f"(d[47]),"+f"(d[48]),"+f"(d[49]),"+f"(d[50]),"+f"(d[51]),"+f"(d[52]),"+f"(d[53]),"+f"(d[54]),"+f"(d[55]),"+f"(d[56]),"+f"(d[57]),"+f"(d[58]),"+f"(d[59]),"+f"(d[60]),"+f"(d[61]),"+f"(d[62]),"+f"(d[63])
  : "l"(da), "l"(db), "n"(TA), "n"(TB));
}
template <int TA, int TB> __device__ __forceinline__ void wgmma_ss_n64(float (&d)[32], uint64_t da, uint64_t db) {
  asm volatile("wgmma.mma_async.sync.aligned.m64n64k16.f32.bf16.bf16 "
  "{%0,%1,%2,%3,%4,%5,%6,%7,%8,%9,%10,%11,%12,%13,%14,%15,%16,%17,%18,%19,%20,%21,%22,%23,%24,%25,%26,%27,%28,%29,%30,%31}, "
  "%32, %33, 1, 1, 1, %34, %35;"
  : "+f"(d[0]),"+f"(d[1]),"+f"(d[2]),"+f"(d[3]),"+f"(d[4]),"+f"(d[5]),"+f"(d[6]),"+f"(d[7]),"+f"(d[8]),"+f"(d[9]),"+f"(d[10]),"+f"(d[11]),"+f"(d[12]),"+f"(d[13]),"+f"(d[14]),"+f"(d[15]),"+f"(d[16]),"+f"(d[17]),"+f"(d[18]),"+f"(d[19]),"+f"(d[20]),"+f"(d[21]),"+f"(d[22]),"+f"(d[23]),"+f"(d[24]),"+f"(d[25]),"+f"(d[26]),"+f"(d[27]),"+f"(d[28]),"+f"(d[29]),"+f"(d[30]),"+f"(d[31])
  : "l"(da), "l"(db), "n"(TA), "n"(TB));
}
template <int TA, int TB> __device__ __forceinline__ void wgmma_sz_n64(float (&d)[32], uint64_t da, uint64_t db) {
  asm volatile("wgmma.mma_async.sync.aligned.m64n64k16.f32.bf16.bf16 "
  "{%0,%1,%2,%3,%4,%5,%6,%7,%8,%9,%10,%11,%12,%13,%14,%15,%16,%17,%18,%19,%20,%21,%22,%23,%24,%25,%26,%27,%28,%29,%30,%31}, "
  "%32, %33, 0, 1, 1, %34, %35;"
  : "=f"(d[0]),"=f"(d[1]),"=f"(d[2]),"=f"(d[3]),"=f"(d[4]),"=f"(d[5]),"=f"(d[6]),"=f"(d[7]),"=f"(d[8]),"=f"(d[9]),"=f"(d[10]),"=f"(d[11]),"=f"(d[12]),"=f"(d[13]),"=f"(d[14]),"=f"(d[15]),"=f"(d[16]),"=f"(d[17]),"=f"(d[18]),"=f"(d[19]),"=f"(d[20]),"=f"(d[21]),"=f"(d[22]),"=f"(d[23]),"=f"(d[24]),"=f"(d[25]),"=f"(d[26]),"=f"(d[27]),"=f"(d[28]),"=f"(d[29]),"=f"(d[30]),"=f"(d[31])
  : "l"(da), "l"(db), "n"(TA), "n"(TB));
}
template <int TB> __device__ __forceinline__ void wgmma_rs_n72(float (&d)[36], uint32_t a0, uint32_t a1, uint32_t a2, uint32_t a3, uint64_t db) {
  asm volatile("wgmma.mma_async.sync.aligned.m64n72k16.f32.bf16.bf16 "
  "{%0,%1,%2,%3,%4,%5,%6,%7,%8,%9,%10,%11,%12,%13,%14,%15,%16,%17,%18,%19,%20,%21,%22,%23,%24,%25,%26,%27,%28,%29,%30,%31,%32,%33,%34,%35}, "
  "{%36,%37,%38,%39}, %40, 1, 1, 1, %41;"
  : "+f"(d[0]),"+f"(d[1]),"+f"(d[2]),"+f"(d[3]),"+f"(d[4]),"+f"(d[5]),"+f"(d[6]),"+f"(d[7]),"+f"(d[8]),"+f"(d[9]),"+f"(d[10]),"+f"(d[11]),"+f"(d[12]),"+f"(d[13]),"+f"(d[14]),"+f"(d[15]),"+f"(d[16]),"+f"(d[17]),"+f"(d[18]),"+f"(d[19]),"+f"(d[20]),"+f"(d[21]),"+f"(d[22]),"+f"(d[23]),"+f"(d[24]),"+f"(d[25]),"+f"(d[26]),"+f"(d[27]),"+f"(d[28]),"+f"(d[29]),"+f"(d[30]),"+f"(d[31]),"+f"(d[32]),"+f"(d[33]),"+f"(d[34]),"+f"(d[35])
  : "r"(a0), "r"(a1), "r"(a2), "r"(a3), "l"(db), "n"(TB));
}
template <int TB> __device__ __forceinline__ void wgmma_rz_n72(float (&d)[36], uint32_t a0, uint32_t a1, uint32_t a2, uint32_t a3, uint64_t db) {
  asm volatile("wgmma.mma_async.sync.aligned.m64n72k16.f32.bf16.bf16 "
  "{%0,%1,%2,%3,%4,%5,%6,%7,%8,%9,%10,%11,%12,%13,%14,%15,%16,%17,%18,%19,%20,%21,%22,%23,%24,%25,%26,%27,%28,%29,%30,%31,%32,%33,%34,%35}, "
  "{%36,%37,%38,%39}, %40, 0, 1, 1, %41;"
  : "=f"(d[0]),"=f"(d[1]),"=f"(d[2]),"=f"(d[3]),"=f"(d[4]),"=f"(d[5]),"=f"(d[6]),"=f"(d[7]),"=f"(d[8]),"=f"(d[9]),"=f"(d[10]),"=f"(d[11]),"=f"(d[12]),"=f"(d[13]),"=f"(d[14]),"=f"(d[15]),"=f"(d[16]),"=f"(d[17]),"=f"(d[18]),"=f"(d[19]),"=f"(d[20]),"=f"(d[21]),"=f"(d[22]),"=f"(d[23]),"=f"(d[24]),"=f"(d[25]),"=f"(d[26]),"=f"(d[27]),"=f"(d[28]),"=f"(d[29]),"=f"(d[30]),"=f"(d[31]),"=f"(d[32]),"=f"(d[33]),"=f"(d[34]),"=f"(d[35])
  : "r"(a0), "r"(a1), "r"(a2), "r"(a3), "l"(db), "n"(TB));
}
template <int TB> __device__ __forceinline__ void wgmma_rs_n40(float (&d)[20], uint32_t a0, uint32_t a1, uint32_t a2, uint32_t a3, uint64_t db) {
  asm volatile("wgmma.mma_async.sync.aligned.m64n40k16.f32.bf16.bf16 "
  "{%0,%1,%2,%3,%4,%5,%6,%7,%8,%9,%10,%11,%12,%13,%14,%15,%16,%17,%18,%19}, "
  "{%20,%21,%22,%23}, %24, 1, 1, 1, %25;"
  : "+f"(d[0]),"+f"(d[1]),"+f"(d[2]),"+f"(d[3]),"+f"(d[4]),"+f"(d[5]),"+f"(d[6]),"+f"(d[7]),"+f"(d[8]),"+f"(d[9]),"+f"(d[10]),"+f"(d[11]),"+f"(d[12]),"+f"(d[13]),"+f"(d[14]),"+f"(d[15]),"+f"(d[16]),"+f"(d[17]),"+f"(d[18]),"+f"(d[19])
  : "r"(a0), "r"(a1), "r"(a2), "r"(a3), "l"(db), "n"(TB));
}
template <int TB> __device__ __forceinline__ void wgmma_rz_n40(float (&d)[20], uint32_t a0, uint32_t a1, uint32_t a2, uint32_t a3, uint64_t db) {
  asm volatile("wgmma.mma_async.sync.aligned.m64n40k16.f32.bf16.bf16 "
  "{%0,%1,%2,%3,%4,%5,%6,%7,%8,%9,%10,%11,%12,%13,%14,%15,%16,%17,%18,%19}, "
  "{%20,%21,%22,%23}, %24, 0, 1, 1, %25;"
  : "=f"(d[0]),"=f"(d[1]),"=f"(d[2]),"=f"(d[3]),"=f"(d[4]),"=f"(d[5]),"=f"(d[6]),"=f"(d[7]),"=f"(d[8]),"=f"(d[9]),"=f"(d[10]),"=f"(d[11]),"=f"(d[12]),"=f"(d[13]),"=f"(d[14]),"=f"(d[15]),"=f"(d[16]),"=f"(d[17]),"=f"(d[18]),"=f"(d[19])
  : "r"(a0), "r"(a1), "r"(a2), "r"(a3), "l"(db), "n"(TB));
}
template <int TB> __device__ __forceinline__ void wgmma_rs_n128(float (&d)[64], uint32_t a0, uint32_t a1, uint32_t a2, uint32_t a3, uint64_t db) {
  asm volatile("wgmma.mma_async.sync.aligned.m64n128k16.f32.bf16.bf16 "
  "{%0,%1,%2,%3,%4,%5,%6,%7,%8,%9,%10,%11,%12,%13,%14,%15,%16,%17,%18,%19,%20,%21,%22,%23,%24,%25,%26,%27,%28,%29,%30,%31,%32,%33,%34,%35,%36,%37,%38,%39,%40,%41,%42,%43,%44,%45,%46,%47,%48,%49,%50,%51,%52,%53,%54,%55,%56,%57,%58,%59,%60,%61,%62,%63}, "
  "{%64,%65,%66,%67}, %68, 1, 1, 1, %69;"
  : "+f"(d[0]),"+f"(d[1]),"+f"(d[2]),"+f"(d[3]),"+f"(d[4]),"+f"(d[5]),"+f"(d[6]),"+f"(d[7]),"+f"(d[8]),"+f"(d[9]),"+f"(d[10]),"+f"(d[11]),"+f"(d[12]),"+f"(d[13]),"+f"(d[14]),"+f"(d[15]),"+f"(d[16]),"+f"(d[17]),"+f"(d[18]),"+f"(d[19]),"+f"(d[20]),"+f"(d[21]),"+f"(d[22]),"+f"(d[23]),"+f"(d[24]),"+f"(d[25]),"+f"(d[26]),"+f"(d[27]),"+f"(d[28]),"+f"(d[29]),"+f"(d[30]),"+f"(d[31]),"+f"(d[32]),"+f"(d[33]),"+f"(d[34]),"+f"(d[35]),"+f"(d[36]),"+f"(d[37]),"+f"(d[38]),"+f"(d[39]),"+f"(d[40]),"+f"(d[41]),"+f"(d[42]),"+f"(d[43]),"+f"(d[44]),"+f"(d[45]),"+f"(d[46]),"+f"(d[47]),"+f"(d[48]),"+f"(d[49]),"+f"(d[50]),"+f"(d[51]),"+f"(d[52]),"+f"(d[53]),"+f"(d[54]),"+f"(d[55]),"+f"(d[56]),"+f"(d[57]),"+f"(d[58]),"+f"(d[59]),"+f"(d[60]),"+f"(d[61]),"+f"(d[62]),"+f"(d[63])
  : "r"(a0), "r"(a1), "r"(a2), "r"(a3), "l"(db), "n"(TB));
}
template <int TA, int TB> __device__ __forceinline__ void wgmma_ss_n8(float (&d)[4], uint64_t da, uint64_t db) {
  asm volatile("wgmma.mma_async.sync.aligned.m64n8k16.f32.bf16.bf16 "
  "{%0,%1,%2,%3}, "
  "%4, %5, 1, 1, 1, %6, %7;"
  : "+f"(d[0]),"+f"(d[1]),"+f"(d[2]),"+f"(d[3])
  : "l"(da), "l"(db), "n"(TA), "n"(TB));
}
template <int TA, int TB> __device__ __forceinline__ void wgmma_ss_n16(float (&d)[8], uint64_t da, uint64_t db) {
  asm volatile("wgmma.mma_async.sync.aligned.m64n16k16.f32.bf16.bf16 "
  "{%0,%1,%2,%3,%4,%5,%6,%7}, "
  "%8, %9, 1, 1, 1, %10, %11;"
  : "+f"(d[0]),"+f"(d[1]),"+f"(d[2]),"+f"(d[3]),"+f"(d[4]),"+f"(d[5]),"+f"(d[6]),"+f"(d[7])
  : "l"(da), "l"(db), "n"(TA), "n"(TB));
}

constexpr int SEQ = 2048, DM = 1024, FF = 3584;
constexpr int NCTA = 128, NSVC = 4;
constexpr int NUNIT = 112;
constexpr uint32_t SLOT = 16384;
constexpr uint32_t MISC = 14 * SLOT;
constexpr uint32_t SMEM_BYTES = MISC + 3072;
constexpr uint32_t M_MOE = 0;
constexpr uint32_t M_BAR = 2048;
constexpr uint32_t M_DUM = 2048 + 1020;
constexpr uint32_t M_IDX = 2048 + 768;
constexpr uint32_t M_KEY = 2048 + 960;
#define R5 1
#define NQ (R5 ? 6 : 5)
constexpr int NF = 16 - NQ, NR = (NQ == 5 || R5) ? 4 : 3;
constexpr int B_FXQ = 0, B_FKV = 3, B_AST = 6, B_MOE = 7, B_MF = 8  , B_CQ = 12, B_XS = 13, B_DF = 14, B_ZOK = 15, B_FWO = 21  , B_FQ = B_FWO - NQ,
              B_UP = 37, B_FIN = 38, B_KVB = 39, B_ME = 40  , B_HF = 44, B_AF = 45  , B_AR = 50  , B_GO = 52,
              B_FAUX = 53, B_EAUX = 54, B_T0 = 55, B_DE = 56, B_EA = 57  , B_VAL = 62  ,
              B_E = 67  , B_STG = 70, B_EQ = 71  , B_EO = 76  , NBAR = 83, B_KV4 = 83, B_MS = 84,
              B_FV = 85  , B_EK = 88  , B_GQ = 91, B_GT = 92;
constexpr uint32_t MT = 9216, A_ONES = 12 * SLOT + 3 * MT, A_CS = A_ONES + 2048, A_ST = A_CS + 1536;
constexpr uint32_t A_TL = MISC + 2048 + 808;
constexpr int S_V0 = R5 ? 7 : 11, S_V1 = R5 ? 9 : 7;
constexpr uint32_t K_SLOTS = 0x8697A8u, V_SLOTS = 0x97A869u;
constexpr int C_B = 0, C_DONE = 32, NCNT = 2;
constexpr uint32_t QX_SLOTS = NQ == 5 ? 0x43102u : 0x354021u;
constexpr uint32_t QW_SLOTS = R5 ? 0xA9786Au : 0xB76A98u;
constexpr uint32_t qx(int k) { return (QX_SLOTS >> (4 * k)) & 15u; }
constexpr uint32_t qw(int k) { return (QW_SLOTS >> (4 * k)) & 15u; }
constexpr uint32_t S_KVB = R5 ? 1 : 8, S_D0 = R5 ? 11 : (NQ == 5 ? 5 : 1), S_D1 = R5 ? 2 : (NQ == 5 ? 11 : 2);
constexpr uint32_t S_M3 = R5 ? 11 : 5;
constexpr int WQ0 = NQ == 5 ? 1 : 3;
constexpr uint32_t wo_slot_c(int i) { return i >= 9 ? wo_slot_c(i - 9) : (i == 7 ? S_D0 : (i == 8 ? S_D1 : (((i & 1) || i + WQ0 == 1) ? qx((i + WQ0) >> 1) : qw((i + WQ0) >> 1)))); }
constexpr uint64_t wo_slots() { uint64_t t = 0; for (int i = 0; i < 16; i++) t |= (uint64_t)wo_slot_c(i) << (4 * i); return t; }
constexpr uint64_t WO_SLOTS = wo_slots();
constexpr uint32_t A_SLOTS = 0xDC000u | (S_KVB << 8) | (qw(NQ - 1) << 4) | qx(NQ - 1);
constexpr uint32_t SX14 = qx(NQ - 2), SX15 = qx(NQ - 1), SXQ0 = qx(0);
#define WOD 2
#define PLC 3
#define RS0 0
#define POLLNS 150
#define MPROMO CU_TENSOR_MAP_L2_PROMOTION_L2_128B
#define MW0 0
#define PFILL 0
#define H2W (NQ - 3)
#define SV0 2
#define SV0A 14
#define SV0B 22
#define ASTE 2
#define PFS 1
#define PFTAB 0x0012222220000ull
#define HW 0
#define DPF 1
#define PROBE 0x8
#define OS1 0
#define YW 0
#define NOVAL 0
#define NDIR 1
#define I0 (2 + NDIR)
#define DW 0
#define NA 5
#define STAG 4
#define GOE 0
#define KEY1 0
#define HYB 0
#define FW 0
#define E1E 1
#define GATE 0
#define SVD 0
#define XPROMO CU_TENSOR_MAP_L2_PROMOTION_L2_128B
#define MC0 3
#define MX 0
#define OUTV 1
#define NP 0
#define FINCP 0
#define DNS 0
#define WOK 99
#define WOD1 2
#define MRED 1
#define MRW -1
#define ST 0
#define RW 0
#define SL2 0
#define CQ4 0
#define CQE 0
#define VOL 0
#define FMC 0
#define KO 0
#define OH 0
#define R4E 0
#define WOP 3
#define WSP 0
#define SH2 0
#define KS 7
#define SQ 2
#define H2D 200
#define MRC 0
#define H2C 0
#define MRD 300
#define STP 0
#define TPNS 50
#define MFIN 0
#define MFD 300
#define SF 1
#define PH MFIN
#define RSL 0
#define OS3 4
#define PLP 2
#define PFNS2 200
#define MAP 2
#define RSNS 60
#define SVS 6
#define MC 7
#define QE 0
#define TMP 1
#define TMPW 4
#define DS 15
#define RL 0
#define EV 0
#define LQ 0
#define SPL 0
#define PHI2 1
#define E7 1
#define RF 1
#define RK 0
#define LE 1
#define SL7 0
#define XP 3
#define MS 0
constexpr int CON_REGS = 224, MOE_REGS = 40, PROD_REGS = 24;
constexpr uint32_t SPIN_MAX = 2000000;
constexpr uint32_t SENT = 0xFFFFFFFFu;

struct __align__(128) Scratch {
  uint4 o[NCTA * 2048];
  uint4 part[NCTA * 544];
  uint4 fin[8 * 640];
  float2 stats[SEQ];
  uint32_t key[SEQ];
  uint32_t cs[3 * DM];
  uint4 y[NCTA * 128];
  uint32_t h[56 * 256];
  uint32_t top[128];
  uint32_t cnt[NCNT * 32];
};
__device__ Scratch G;
#define TLS(th, i)
#define TLP_(i)
#define TLG(i)
#define TLDUMP()

__device__ __forceinline__ bool elect_one() {
  uint32_t p;
  asm volatile("{\n.reg .pred P;\nelect.sync _|P, 0xffffffff;\nselp.b32 %0, 1, 0, P;\n}" : "=r"(p));
  return p;
}
__device__ __forceinline__ void mbar_init(uint32_t b, uint32_t c) { asm volatile("mbarrier.init.shared::cta.b64 [%0], %1;" ::"r"(b), "r"(c) : "memory"); }
__device__ __forceinline__ void mbar_expect_tx(uint32_t b, uint32_t bytes) { asm volatile("mbarrier.arrive.expect_tx.shared::cta.b64 _, [%0], %1;" ::"r"(b), "r"(bytes) : "memory"); }
__device__ __forceinline__ void mbar_arrive(uint32_t b) { asm volatile("mbarrier.arrive.shared::cta.b64 _, [%0];" ::"r"(b) : "memory"); }
__device__ __forceinline__ void mbar_wait_b(uint32_t b, uint32_t parity) {
  asm volatile(
      "{\n.reg .pred p;\n.reg .u32 cnt;\nmov.u32 cnt, 0;\n"
      "LW:\nmbarrier.try_wait.parity.shared::cta.b64 p, [%0], %1;\n@p bra LD;\n"
      "add.u32 cnt, cnt, 1;\nsetp.lt.u32 p, cnt, 4000000;\n@p bra LW;\ntrap;\nLD:\n}" ::"r"(b), "r"(parity) : "memory");
}
__device__ __forceinline__ void mbar_wait(uint32_t b, uint32_t parity) {
  asm volatile("{\n.reg .pred p;\nLW:\nmbarrier.try_wait.parity.shared::cta.b64 p, [%0], %1;\n@!p bra LW;\n}" ::"r"(b), "r"(parity) : "memory");
}
__device__ __forceinline__ bool mbar_test(uint32_t b, uint32_t parity) {
  uint32_t r;
  asm volatile("{\n.reg .pred p;\nmbarrier.test_wait.parity.shared::cta.b64 p, [%1], %2;\nselp.b32 %0, 1, 0, p;\n}" : "=r"(r) : "r"(b), "r"(parity) : "memory");
  return r;
}
__device__ __forceinline__ uint32_t ev_arrive(uint32_t a) { uint32_t r; asm volatile("atom.shared.add.u32 %0, [%1], 1;" : "=r"(r) : "r"(a) : "memory"); return r; }
__device__ __forceinline__ void tma2d(uint32_t dst, const CUtensorMap* m, int c0, int c1, uint32_t bar) {
  asm volatile("cp.async.bulk.tensor.2d.shared::cluster.global.mbarrier::complete_tx::bytes [%0], [%1, {%3, %4}], [%2];" ::"r"(dst), "l"(m), "r"(bar), "r"(c0), "r"(c1) : "memory");
}
__device__ __forceinline__ void tma3d(uint32_t dst, const CUtensorMap* m, int c1, int c2, uint32_t bar) {
  asm volatile("cp.async.bulk.tensor.3d.shared::cluster.global.mbarrier::complete_tx::bytes [%0], [%1, {%3, %4, %5}], [%2];" ::"r"(dst), "l"(m), "r"(bar), "r"(0), "r"(c1), "r"(c2) : "memory");
}
__device__ __forceinline__ void tma3d_mc(uint32_t dst, const CUtensorMap* m, int c1, int c2, uint32_t bar) {
  asm volatile("cp.async.bulk.tensor.3d.shared::cluster.global.mbarrier::complete_tx::bytes.multicast::cluster [%0], [%1, {%3, %4, %5}], [%2], %6;" ::"r"(dst), "l"(m), "r"(bar), "r"(0), "r"(c1), "r"(c2), "h"((uint16_t)3) : "memory");
}
__device__ __forceinline__ void tma5d(uint32_t dst, const CUtensorMap* m, int c2, int c4, uint32_t bar, bool mc) {
  if (mc) asm volatile("cp.async.bulk.tensor.5d.shared::cluster.global.mbarrier::complete_tx::bytes.multicast::cluster [%0], [%1, {%3, %3, %4, %3, %5}], [%2], %6;" ::"r"(dst), "l"(m), "r"(bar), "r"(0), "r"(c2), "r"(c4), "h"((uint16_t)3) : "memory");
  else asm volatile("cp.async.bulk.tensor.5d.shared::cluster.global.mbarrier::complete_tx::bytes [%0], [%1, {%3, %3, %4, %3, %5}], [%2];" ::"r"(dst), "l"(m), "r"(bar), "r"(0), "r"(c2), "r"(c4) : "memory");
}
__device__ __forceinline__ void mbar_arrive_cta(uint32_t b, uint32_t cta) {
  asm volatile("{\n.reg .b32 ra;\nmapa.shared::cluster.u32 ra, %0, %1;\nmbarrier.arrive.shared::cluster.b64 _, [ra];\n}" ::"r"(b), "r"(cta) : "memory");
}
constexpr uint64_t POL_FIRST = 0x12F0000000000000ull;
__device__ __forceinline__ void tma2d_ef(uint32_t dst, const CUtensorMap* m, int c0, int c1, uint32_t bar) {
  asm volatile("cp.async.bulk.tensor.2d.shared::cluster.global.mbarrier::complete_tx::bytes.L2::cache_hint [%0], [%1, {%3, %4}], [%2], %5;" ::"r"(dst), "l"(m), "r"(bar), "r"(c0), "r"(c1), "l"(POL_FIRST) : "memory");
}
__device__ __forceinline__ void bulk_ld(uint32_t dst, const void* src, uint32_t bytes, uint32_t bar) {
  asm volatile("cp.async.bulk.shared::cluster.global.mbarrier::complete_tx::bytes [%0], [%1], %2, [%3];" ::"r"(dst), "l"(src), "r"(bytes), "r"(bar) : "memory");
}
__device__ __forceinline__ void bulk_ld_mc(uint32_t dst, const void* src, uint32_t bytes, uint32_t bar) {
  asm volatile("cp.async.bulk.shared::cluster.global.mbarrier::complete_tx::bytes.multicast::cluster [%0], [%1], %2, [%3], %4;" ::"r"(dst), "l"(src), "r"(bytes), "r"(bar), "h"((uint16_t)3) : "memory");
}
__device__ __forceinline__ void bulk_pf(const void* src, uint32_t bytes) { asm volatile("cp.async.bulk.prefetch.L2.global [%0], %1;" ::"l"(src), "r"(bytes) : "memory"); }
__device__ __forceinline__ void tma2d_pf(const CUtensorMap* m, int c0, int c1) {
  asm volatile("cp.async.bulk.prefetch.tensor.2d.L2.global [%0, {%1, %2}];" ::"l"(m), "r"(c0), "r"(c1) : "memory");
}
__device__ __forceinline__ void map_pf(const CUtensorMap* m) { asm volatile("prefetch.tensormap [%0];" ::"l"(m) : "memory"); }
__device__ __forceinline__ void line_pf(const void* p) { asm volatile("prefetch.global.L2 [%0];" ::"l"(p)); }
__device__ __forceinline__ void pf128(uint32_t dummy, const void* src) { asm volatile("cp.async.ca.shared.global.L2::128B [%0], [%1], 4;" ::"r"(dummy), "l"(src) : "memory"); }
__device__ __forceinline__ void pf256(uint32_t dummy, const void* src) { asm volatile("cp.async.ca.shared.global.L2::256B [%0], [%1], 4;" ::"r"(dummy), "l"(src) : "memory"); }
__device__ __forceinline__ void cp16x2(uint32_t dst, const void* src) {
  asm volatile("cp.async.cg.shared.global [%0], [%1], 16;\ncp.async.cg.shared.global [%0+4096], [%1+512], 16;" ::"r"(dst), "l"(src) : "memory");
}
constexpr uint32_t HI_SW128 = 0x40000000u | (1024 >> 4), HI_SW64 = 0x80000000u | (512 >> 4), HI_NOSW = 512 >> 4;
__device__ __forceinline__ uint64_t mkdesc(uint32_t lo, uint32_t hi) { uint64_t d; asm("mov.b64 %0, {%1, %2};" : "=l"(d) : "r"(lo), "r"(hi)); return d; }
__device__ __forceinline__ void wg_fence() { asm volatile("wgmma.fence.sync.aligned;" ::: "memory"); }
__device__ __forceinline__ void wg_commit() { asm volatile("wgmma.commit_group.sync.aligned;" ::: "memory"); }
template <int N> __device__ __forceinline__ void wg_wait() { asm volatile("wgmma.wait_group.sync.aligned %0;" ::"n"(N) : "memory"); }
template <int N> __device__ __forceinline__ void reg_fence(float (&a)[N]) {
#pragma unroll
  for (int i = 0; i < N; i++) asm volatile("" : "+f"(a[i])::"memory");
}
template <int ID, int N> __device__ __forceinline__ void bar_sync() { asm volatile("bar.sync %0, %1;" ::"n"(ID), "n"(N) : "memory"); }
__device__ __forceinline__ void fence_async_smem() { asm volatile("fence.proxy.async.shared::cta;" ::: "memory"); }
__device__ __forceinline__ void fence_async_gmem() { asm volatile("fence.proxy.async.global;" ::: "memory"); }
__device__ __forceinline__ uint32_t pack_bf16(float lo, float hi) { uint32_t r; asm("cvt.rn.bf16x2.f32 %0, %1, %2;" : "=r"(r) : "f"(hi), "f"(lo)); return r; }
__device__ __forceinline__ float bf_lo(uint32_t v) { return __uint_as_float(v << 16); }
__device__ __forceinline__ float bf_hi(uint32_t v) { return __uint_as_float(v & 0xFFFF0000u); }
__device__ __forceinline__ float bf_round(float v) { return bf_lo(pack_bf16(v, v)); }
__device__ __forceinline__ uint32_t bf_sub2(uint32_t a, uint32_t b) { uint32_t r; asm("sub.rn.bf16x2 %0, %1, %2;" : "=r"(r) : "r"(a), "r"(b)); return r; }
__device__ __forceinline__ float rcp(float v) { float r; asm("rcp.approx.ftz.f32 %0, %1;" : "=f"(r) : "f"(v)); return r; }
__device__ __forceinline__ float ex2(float v) { float r; asm("ex2.approx.ftz.f32 %0, %1;" : "=f"(r) : "f"(v)); return r; }
__device__ __forceinline__ float sigmoid(float v) { return rcp(1.f + ex2(v * -1.4426950408889634f)); }
__device__ __forceinline__ void stsm4(uint32_t a, uint32_t r0, uint32_t r1, uint32_t r2, uint32_t r3) {
  asm volatile("stmatrix.sync.aligned.m8n8.x4.shared.b16 [%0], {%1,%2,%3,%4};" ::"r"(a), "r"(r0), "r"(r1), "r"(r2), "r"(r3) : "memory");
}
__device__ __forceinline__ void stsm4t(uint32_t a, uint32_t r0, uint32_t r1, uint32_t r2, uint32_t r3) {
  asm volatile("stmatrix.sync.aligned.m8n8.x4.trans.shared.b16 [%0], {%1,%2,%3,%4};" ::"r"(a), "r"(r0), "r"(r1), "r"(r2), "r"(r3) : "memory");
}
__device__ __forceinline__ void ldsm4(uint32_t a, uint32_t& r0, uint32_t& r1, uint32_t& r2, uint32_t& r3) {
  asm volatile("ldmatrix.sync.aligned.m8n8.x4.shared.b16 {%0,%1,%2,%3}, [%4];" : "=r"(r0), "=r"(r1), "=r"(r2), "=r"(r3) : "r"(a) : "memory");
}
__device__ __forceinline__ uint32_t movmat(uint32_t a) { uint32_t d; asm volatile("movmatrix.sync.aligned.m8n8.trans.b16 %0, %1;" : "=r"(d) : "r"(a)); return d; }
__device__ __forceinline__ void sts_h(uint32_t a, float v) { asm volatile("st.shared.u16 [%0], %1;" ::"r"(a), "h"((uint16_t)pack_bf16(v, v)) : "memory"); }
__device__ __forceinline__ float2 lds_f2(uint32_t a) { float2 v; asm volatile("ld.shared.v2.f32 {%0,%1}, [%2];" : "=f"(v.x), "=f"(v.y) : "r"(a)); return v; }
__device__ __forceinline__ float lds_f(uint32_t a) { float v; asm volatile("ld.shared.f32 %0, [%1];" : "=f"(v) : "r"(a)); return v; }
__device__ __forceinline__ float4 lds_f4(uint32_t a) { float4 v; asm volatile("ld.shared.v4.f32 {%0,%1,%2,%3}, [%4];" : "=f"(v.x), "=f"(v.y), "=f"(v.z), "=f"(v.w) : "r"(a)); return v; }
__device__ __forceinline__ uint32_t lds_u(uint32_t a) { uint32_t v; asm volatile("ld.shared.u32 %0, [%1];" : "=r"(v) : "r"(a) : "memory"); return v; }
__device__ __forceinline__ uint4 lds_u4(uint32_t a) { uint4 v; asm volatile("ld.shared.v4.u32 {%0,%1,%2,%3}, [%4];" : "=r"(v.x), "=r"(v.y), "=r"(v.z), "=r"(v.w) : "r"(a) : "memory"); return v; }
__device__ __forceinline__ void sts_u(uint32_t a, uint32_t v) { asm volatile("st.shared.u32 [%0], %1;" ::"r"(a), "r"(v) : "memory"); }
__device__ __forceinline__ void sts_u4(uint32_t a, uint4 v) { asm volatile("st.shared.v4.u32 [%0], {%1,%2,%3,%4};" ::"r"(a), "r"(v.x), "r"(v.y), "r"(v.z), "r"(v.w) : "memory"); }
__device__ __forceinline__ uint4 ldx4(const void* p) { uint4 v; asm volatile("ld.relaxed.gpu.global.v4.u32 {%0,%1,%2,%3}, [%4];" : "=r"(v.x), "=r"(v.y), "=r"(v.z), "=r"(v.w) : "l"(p) : "memory"); return v; }
__device__ __forceinline__ uint2 ldx2(const void* p) { uint2 v; asm volatile("ld.relaxed.gpu.global.v2.u32 {%0,%1}, [%2];" : "=r"(v.x), "=r"(v.y) : "l"(p) : "memory"); return v; }
__device__ __forceinline__ uint32_t ldx1(const void* p) { uint32_t v; asm volatile("ld.relaxed.gpu.global.u32 %0, [%1];" : "=r"(v) : "l"(p) : "memory"); return v; }
__device__ __forceinline__ void stx4(void* p, uint32_t a, uint32_t b, uint32_t c, uint32_t d) {
  asm volatile("st.relaxed.gpu.global.v4.u32 [%0], {%1,%2,%3,%4};" ::"l"(p), "r"(a), "r"(b), "r"(c), "r"(d) : "memory");
}
__device__ __forceinline__ void stx2(void* p, uint32_t a, uint32_t b) { asm volatile("st.relaxed.gpu.global.v2.u32 [%0], {%1,%2};" ::"l"(p), "r"(a), "r"(b) : "memory"); }
__device__ __forceinline__ void stx1(void* p, uint32_t a) { asm volatile("st.relaxed.gpu.global.u32 [%0], %1;" ::"l"(p), "r"(a) : "memory"); }
__device__ __forceinline__ uint32_t umax4(uint4 v) { return max(max(v.x, v.y), max(v.z, v.w)); }
__device__ __forceinline__ uint32_t f2x(float f) { return min(__float_as_uint(f), 0xFFFFFFFEu); }
__device__ __forceinline__ void red4(float* p, float a, float b, float c, float d) { asm volatile("red.relaxed.gpu.global.add.v4.f32 [%0], {%1,%2,%3,%4};" ::"l"(p), "f"(a), "f"(b), "f"(c), "f"(d) : "memory"); }
__device__ __forceinline__ void cnt_arrive(int c) { asm volatile("red.release.gpu.global.add.u32 [%0], 1;" ::"l"(&G.cnt[c]) : "memory"); }
__device__ __forceinline__ void cnt_wait(int c, uint32_t target) {
#pragma unroll 1
  for (uint32_t it = 0; it < SPIN_MAX; it++) {
    uint32_t v;
    asm volatile("ld.acquire.gpu.global.u32 %0, [%1];" : "=r"(v) : "l"(&G.cnt[c]) : "memory");
    if (v >= target) break;
    __nanosleep(POLLNS);
  }
}
__device__ __forceinline__ void spin_cycles(uint32_t n) {
  uint32_t t0, t1;
  asm volatile("mov.u32 %0, %%clock;" : "=r"(t0));
#pragma unroll 1
  do { __nanosleep(20); asm volatile("mov.u32 %0, %%clock;" : "=r"(t1)); } while (t1 - t0 < n);
}
__device__ __forceinline__ void cnt_done() {
  uint32_t t;
  asm volatile("atom.acq_rel.gpu.global.add.u32 %0, [%1], 1;" : "=r"(t) : "l"(&G.cnt[C_DONE]) : "memory");
  if (t == NCTA + NSVC - 1) {
#pragma unroll 1
    for (int i = 0; i < NCNT; i++) G.cnt[i * 32] = 0;
  }
}
__device__ __forceinline__ float phi(float u, float rs, float rl) {
  float a = fmaf(u, rs, 1.000001f), e = ex2(u * rl), r;
  asm("add.sat.f32 %0, %1, 0f358637BD;" : "=f"(e) : "f"(e));
  asm("max.NaN.f32 %0, %1, %2;" : "=f"(r) : "f"(a), "f"(e));
  return r;
}

constexpr float LOG2E = 1.4426950408889634f, LN2 = 0.6931471805599453f;
__device__ __forceinline__ uint32_t phi2l(float u0, float rl0, float u1, float rl1) {
  const float l0 = u0 * rl0, l1 = u1 * rl1;
  float e0, e1;
  asm("{\n.reg .f32 t;\nabs.f32 t, %1;\nneg.f32 t, t;\nex2.approx.ftz.f32 %0, t;\n}" : "=f"(e0) : "f"(l0));
  asm("{\n.reg .f32 t;\nabs.f32 t, %1;\nneg.f32 t, t;\nex2.approx.ftz.f32 %0, t;\n}" : "=f"(e1) : "f"(l1));
  uint32_t e = pack_bf16(e0, e1), r;
  const uint32_t a = pack_bf16(fmaf(l0, LN2, 1.000001f), fmaf(l1, LN2, 1.000001f));
  asm("add.rn.bf16x2 %0, %0, %1;" : "+r"(e) : "r"(0x35863586u));
  asm("max.NaN.bf16x2 %0, %1, %2;" : "=r"(r) : "r"(a), "r"(e));
  return r;
}
template <bool V = false>
__device__ __forceinline__ uint32_t phi2(float u0, float rs0, float rl0, float u1, float rs1, float rl1) {
  float e0, e1;
  if (V) {
    asm volatile("{\n.reg .f32 t;\nabs.f32 t, %1;\nneg.f32 t, t;\nex2.approx.ftz.f32 %0, t;\n}" : "=f"(e0) : "f"(u0 * rl0));
    asm volatile("{\n.reg .f32 t;\nabs.f32 t, %1;\nneg.f32 t, t;\nex2.approx.ftz.f32 %0, t;\n}" : "=f"(e1) : "f"(u1 * rl1));
  } else {
    asm("{\n.reg .f32 t;\nabs.f32 t, %1;\nneg.f32 t, t;\nex2.approx.ftz.f32 %0, t;\n}" : "=f"(e0) : "f"(u0 * rl0));
    asm("{\n.reg .f32 t;\nabs.f32 t, %1;\nneg.f32 t, t;\nex2.approx.ftz.f32 %0, t;\n}" : "=f"(e1) : "f"(u1 * rl1));
  }
  uint32_t e = pack_bf16(e0, e1), r;
  const uint32_t a = pack_bf16(fmaf(u0, rs0, 1.000001f), fmaf(u1, rs1, 1.000001f));
  asm("add.rn.bf16x2 %0, %0, %1;" : "+r"(e) : "r"(0x35863586u));
  asm("max.NaN.bf16x2 %0, %1, %2;" : "=r"(r) : "r"(a), "r"(e));
  return r;
}

__device__ __forceinline__ int kstep1(int e, int hg) { return e < 14 ? (e < 2 * hg ? e : e + 2) : 2 * hg + e - 14; }
__device__ __forceinline__ int slab(int n, int hg) {
  return n + (((n + 7 - hg) * 37) >> 8);
}
__host__ __device__ constexpr uint32_t d_off(int i) { return i < 3 ? 12 * SLOT + (NR == 4 ? i : (i == 2 ? 0 : i + 1)) * MT : (i < 5 ? S_D0 * SLOT + (i - 3) * 8192 : S_D1 * SLOT + (i - 5) * 8192); }
__host__ __device__ constexpr uint32_t h_off(int i) { return i < 3 ? 12 * SLOT + i * MT + 8192 : (i < 5 ? A_ONES + (i - 3) * 1024 : MISC + M_MOE + (i - 5) * 1024); }
__device__ __forceinline__ uint32_t m_off(int r) { return r < 3 ? 12 * SLOT + r * MT : S_M3 * SLOT; }
__device__ __forceinline__ int x_slot(int e, int s) { return NQ == 5 ? (e < 14 ? s : e - 11) : (e < 13 ? s : 3 + s); }
__device__ __forceinline__ uint32_t wo_slot(int i) { return (uint32_t)(WO_SLOTS >> (4 * i)) & 15u; }

__global__ void __launch_bounds__(512, 1)
fused_kernel(const __nv_bfloat16* __restrict__ x, const __nv_bfloat16* __restrict__ wqkv, const __nv_bfloat16* __restrict__ wo,
             const __nv_bfloat16* __restrict__ wr, const __nv_bfloat16* __restrict__ wd, __nv_bfloat16* __restrict__ outp, const int by_sm,
             const __grid_constant__ CUtensorMap tmX, const __grid_constant__ CUtensorMap tmW,
             const __grid_constant__ CUtensorMap tmWo, const __grid_constant__ CUtensorMap tmOut,
             const __grid_constant__ CUtensorMap tmG, const __grid_constant__ CUtensorMap tmU,
             const __grid_constant__ CUtensorMap tmD, const __grid_constant__ CUtensorMap tmR,
             const __grid_constant__ CUtensorMap tmWp) {
  if (TMP && threadIdx.x == 32 * TMPW) { map_pf(&tmX); map_pf(&tmW); }
  extern __shared__ __align__(1024) uint8_t smem_raw[];
  const uint32_t sb = (uint32_t)__cvta_generic_to_shared(smem_raw);
  const uint32_t bars = sb + MISC + M_BAR;
  uint32_t smid;
  asm("mov.u32 %0, %%smid;" : "=r"(smid));
  const int tpc = smid >> 1;
  int cl = tpc + max(((tpc - 25) * 37) >> 8, 0);
  cl = tpc < 60 ? cl : cl - 1;
  cl = tpc < 62 ? cl : (tpc - 58) * 8;
  const int u = by_sm ? 2 * cl + (blockIdx.x & 1) : blockIdx.x;
  const int hg = (u >> 4) & 7, tb = u & 15;
  const int b = tb * 8 + hg;
  const int lane = threadIdx.x & 31;
  const int warp = __shfl_sync(~0u, threadIdx.x >> 5, 0);
  const int ltid = threadIdx.x;
  const int g = lane >> 2, t = lane & 3;
  const uint32_t d0 = (sb & 0x3FFFF) >> 4;
#define BAR(i) (bars + 8 * (i))
  TLS(0, 0);

  const int rank = u & 1;
  auto load_entry = [&](int e, int s) {
    const int k0 = kstep1(e, hg) * 64;
    mbar_expect_tx(BAR(B_FXQ + s), e < NF ? 2 * SLOT : SLOT);
    mbar_expect_tx(BAR(B_FKV + s), R5 ? SLOT : 2 * SLOT);
    if (R5 && e < 11) mbar_expect_tx(BAR(B_FV + s), SLOT);
    const uint32_t vb = R5 ? BAR(B_FV + s) : BAR(B_FKV + s);
    tma2d(sb + x_slot(e, s) * SLOT, &tmX, k0, tb * 128, BAR(B_FXQ + s));
    if (e < MC0 || !(MC & 1)) {
      if (e < NF) tma3d(sb + (3 + s) * SLOT, &tmW, k0, 2 * hg, BAR(B_FXQ + s));
      tma3d(sb + (6 + 2 * s) * SLOT, &tmW, k0, 16 + 2 * hg, BAR(B_FKV + s));
      tma3d(sb + (7 + 2 * s) * SLOT, &tmW, k0, 32 + 2 * hg, vb);
    } else {
      if (e < NF && (e & 1) == rank) tma3d_mc(sb + (3 + s) * SLOT, &tmW, k0, 2 * hg, BAR(B_FXQ + s));
      if (R5 && e >= 11) { if (rank == 0) tma3d_mc(sb + ((K_SLOTS >> (4 * (e - 10))) & 15u) * SLOT, &tmW, k0, 16 + 2 * hg, BAR(B_FKV + s)); }
      else tma3d_mc(sb + (6 + 2 * s + rank) * SLOT, &tmW, k0, 16 + 16 * rank + 2 * hg, rank ? vb : BAR(B_FKV + s));
    }
  };
  if (warp == FW && u < NCTA) {
    if (elect_one()) {
      mbar_init(BAR(B_FXQ), 1); mbar_init(BAR(B_FKV), 1);
      if (R5) mbar_init(BAR(B_FV), 1);
      load_entry(0, 0);
      asm volatile("fence.mbarrier_init.release.cluster;" ::: "memory");
      TLS(FW * 32, 61);
    }
    __syncwarp();
  }
  if (u >= NCTA) {
    const int j = u - NCTA;
    if (warp == 8 && elect_one()) {
#pragma unroll
      for (int i = 0; i < 13; i++) mbar_init(BAR(i), 1);
    }
    if (ltid < 64) sts_u4(sb + MISC + ltid * 16, make_uint4(0x3F803F80u, 0x3F803F80u, 0x3F803F80u, 0x3F803F80u));
    fence_async_smem();
    __syncthreads();
    if (warp < 4) {
      int s = 0, p = 0;
#pragma unroll 1
      for (int pass = 0; pass < 3; pass++) {
        float acc[4][4];
#pragma unroll
        for (int c = 0; c < 4; c++) acc[c][0] = acc[c][1] = acc[c][2] = acc[c][3] = 0.f;
#pragma unroll 1
        for (int k = 0; k < 16; k++) {
          mbar_wait(BAR(s), p);
          wg_fence();
#pragma unroll
          for (int c = 0; c < 4; c++)
#pragma unroll
            for (int kk = 0; kk < 4; kk++)
              wgmma_ss_n8<1, 0>(acc[c], mkdesc((d0 + s * 2048 + c * 512 + kk * 128) | (512u << 16), HI_SW128), mkdesc((d0 + (MISC >> 4)) | (1u << 16), HI_SW128));
          wg_commit();
          wg_wait<0>();
          if (ltid == 0) mbar_arrive(BAR(6 + s));
          if (++s == SVS) { s = 0; p ^= 1; }
        }
        uint32_t* pc = G.cs + (pass < 2 ? DM + pass * DM : 0) + j * 256 + warp * 16 + g;
#pragma unroll
        for (int c = 0; c < 4; c++) {
          reg_fence(acc[c]);
          const uint32_t v = __float_as_uint((t & 1) ? acc[c][2] : acc[c][0]);
          if (t < 2) stx1(pc + c * 64 + t * 8, v ? v : 0x80000000u);
        }
        TLS(0, 1 + pass);
      }
    } else if (warp >= 8 && j == 0) {
      const int wq = warp - 8;
      const uint32_t top = sb + MISC + 1024;
#pragma unroll 1
      for (uint32_t it = 0; it < SPIN_MAX; it++) {
        const uint4 v0 = ldx4(G.key + wq * 256 + lane * 4), v1 = ldx4(G.key + wq * 256 + 128 + lane * 4);
        uint32_t ok;
        asm volatile("{\n.reg .pred p, q;\nsetp.ne.u32 p, %1, 0;\nbar.red.and.pred q, 2, 256, p;\nselp.b32 %0, 1, 0, q;\n}" : "=r"(ok) : "r"((v0.x & v0.y & v0.z & v0.w & v1.x & v1.y & v1.z & v1.w) >> 27) : "memory");
        ok = __any_sync(~0u, ok);
        if (!ok && it) continue;
        TLS(256, 4);
        uint32_t np = 0u - (1u << 28), mine = 0;
#pragma unroll 1
        for (int r = 0; r < 8; r++) {
          const uint32_t m0 = __viaddmax_u32(v0.x, np, v0.y + np), m1 = __viaddmax_u32(v0.z, np, v0.w + np), m2 = __viaddmax_u32(v1.x, np, v1.y + np), m3 = __viaddmax_u32(v1.z, np, v1.w + np);
          np -= __reduce_max_sync(~0u, max(max(m0, m1), max(m2, m3)));
          if (g == r) mine = 0u - np;
        }
        if (t == 0) sts_u(top + (wq * 8 + g) * 4, mine);
        bar_sync<2, 256>();
        TLS(256, 5);
        int rk = 0;
#pragma unroll
        for (int i = 0; i < 4; i++) {
          const uint4 o = lds_u4(top + t * 64 + i * 16);
          rk += (o.x > mine) + (o.y > mine) + (o.z > mine) + (o.w > mine);
        }
        rk += __shfl_xor_sync(~0u, rk, 1);
        rk += __shfl_xor_sync(~0u, rk, 2);
        if (ok) { if (rk < 8) stx1(G.top + t * 32 + rk, mine); break; }
        __nanosleep(2500);
      }
      TLS(256, 7);
    } else if (warp == 4) {
      int s = 0, p = 1;
      if (SVD) __nanosleep(SVD);
#pragma unroll 1
      for (int i = 0; i < 48; i++) {
        mbar_wait(BAR(6 + s), p);
        if (j == 0 && i >= SV0A && i < SV0B) mbar_wait(BAR(s >= SV0 ? s - SV0 : s - SV0 + SVS), s >= SV0 ? p ^ 1 : p);
        if (elect_one()) {
          mbar_expect_tx(BAR(s), 2 * SLOT);
          const int ch = (i < 32 ? 16 + (i & 16) : 0) + j * 4, k0 = (i & 15) * 64;
          tma3d(sb + s * 2 * SLOT, &tmW, k0, ch, BAR(s));
          tma3d(sb + s * 2 * SLOT + SLOT, &tmW, k0, ch + 2, BAR(s));
        }
        if (++s == SVS) { s = 0; p ^= 1; }
      }
    }
    if (ltid == 0) cnt_wait(C_DONE, NCTA);
    __syncthreads();
    const uint4 zero = make_uint4(0, 0, 0, 0);
    if (ltid < 128) reinterpret_cast<uint4*>(G.key)[j * 128 + ltid] = zero;
    else if (ltid < 320) reinterpret_cast<uint4*>(G.cs)[j * 192 + ltid - 128] = zero;
    else if (ltid < 322) reinterpret_cast<uint4*>(G.top)[j * 8 + ltid - 320] = zero;
    if (ltid == 0) { cnt_done(); TLDUMP(); }
    return;
  }

  if (warp == 12) {
    if (elect_one()) {
#pragma unroll
      for (int i = 1; i < 7; i++) if (i != B_FKV) mbar_init(BAR(i), 1);
      if (R5) { mbar_init(BAR(B_FV + 1), 1); mbar_init(BAR(B_FV + 2), 1); }
      if (E1E) load_entry(1, 1);
      asm volatile("fence.mbarrier_init.release.cluster;" ::: "memory");
    }
  } else if (warp >= 13) {
    if (elect_one()) {
      if (warp == 15) {
#pragma unroll
        for (int i = B_FAUX; i < NBAR; i++) mbar_init(BAR(i), i < B_E || !MC ? 2 : 4);
        mbar_init(BAR(B_KV4), 4); mbar_init(BAR(B_MS), 2); mbar_init(BAR(B_GQ), 1); mbar_init(BAR(B_GT), 1);
        if (R5) { mbar_init(BAR(B_EK), 4); mbar_init(BAR(B_EK + 1), 4); mbar_init(BAR(B_EK + 2), 4); }
      } else {
#pragma unroll
        for (int i = 0; i < 23; i++) mbar_init(BAR((warp == 13 ? 7 : 30) + i), 1);
      }
      asm volatile("fence.mbarrier_init.release.cluster;" ::: "memory");
    }
  }
  __syncthreads();
  if (MC) asm volatile("barrier.cluster.arrive.relaxed.aligned;" ::: "memory");

  const bool unit = u < NUNIT;
  const int dcol = (u & 15) * 64, drow = (u >> 4) * 448;
  if (warp >= 12) {
    asm volatile("setmaxnreg.dec.sync.aligned.u32 %0;" ::"n"(PROD_REGS));
    if (MC && warp != 12) asm volatile("barrier.cluster.wait.aligned;" ::: "memory");
    if (warp == 12) {
      int s = 1 + E1E, p = 1, pn = 3;
#pragma unroll 1
      for (int e = 1 + E1E; e < 16; e++) {
        if (MC && e == MC0) asm volatile("barrier.cluster.wait.aligned;" ::: "memory");
        if (e == GATE) mbar_wait(BAR(B_FXQ), 0);
        if (R4E && R5 && e >= 11) mbar_wait(BAR(B_EK + (s == 2 ? 0 : s + 1)), e >= 14);
        else mbar_wait(BAR(B_E + s), p);
        if (elect_one()) {
          load_entry(e, s);
          if (NR == 4 && e == 11) mbar_arrive(BAR(B_ME + 3));
          if (e == ASTE) {
            mbar_expect_tx(BAR(B_AST), 2 * SLOT + 2048);
            bulk_ld(sb + 12 * SLOT, x + (size_t)b * 16 * DM, 2 * SLOT, BAR(B_AST));
            bulk_ld(sb + MISC + M_MOE, wr, 2048, BAR(B_AST));
          } else if (e >= 3) {
            if (WSP == 0) { if (e < 6) bulk_pf(wqkv + (size_t)((e - 2) * 256 + 2 * b) * 3 * DM, 2 * 3 * DM * 2); }
            else if (e < 9) bulk_pf(wqkv + (size_t)((e - 1) * 128 + b) * 3 * DM, 3 * DM * 2);
            if (WOP >= 0 && e >= WOP && e < WOP + 4) bulk_pf(wo + (size_t)((e - WOP) * 256 + 2 * b) * DM, 2 * DM * 2);
            if (NUNIT) {
#pragma unroll 1
              for (int i = (PFTAB >> (4 * (e - 3))) & 15; i > 0; i--, pn++) {
                if (pn >= 16) { if (!(MX & 8)) tma2d_pf(&tmD, dcol, drow + (pn - 16) * 64); }
                else if (unit && !(MX & 2)) tma2d_pf(rank ? &tmU : &tmG, (u >> 1) * 64, pn * 64);
              }
            }
          }
        }
        if (R5 && e >= 11) {
          if (R4E) mbar_wait(BAR(B_E + (s == 2 ? 0 : s + 1)), ((e - 2) / 3) & 1);
          else mbar_wait(BAR(B_EK + (s == 2 ? 0 : s + 1)), e >= 14);
          if (elect_one()) {
            mbar_expect_tx(BAR(B_FV + s), SLOT);
            if (rank) tma3d_mc(sb + ((V_SLOTS >> (4 * (e - 10))) & 15u) * SLOT, &tmW, kstep1(e, hg) * 64, 32 + 2 * hg, BAR(B_FV + s));
          }
        }
        if (++s == 3) { s = 0; p ^= 1; }
      }
#pragma unroll 1
      for (int k = 0; k < NQ; k++) {
        if (k == 0) mbar_wait(BAR(B_E + 1), 0);
        if (k == 1) mbar_wait(BAR(B_EK + 2), 1);
        if (k == 2) mbar_wait(BAR(B_EK + 0), 0);
        if (k == 3) mbar_wait(BAR(B_STG), 0);
        if (k == 5) mbar_wait(BAR(B_EQ), 0);
        if (elect_one()) {
          const int k0 = kstep1(NF + k, hg) * 64;
          mbar_expect_tx(BAR(B_FQ + k), SLOT);
          if (!(MC & 2)) tma3d(sb + ((QW_SLOTS >> (4 * k)) & 15u) * SLOT, &tmW, k0, 2 * hg, BAR(B_FQ + k));
          else if ((k & 1) == rank) tma3d_mc(sb + ((QW_SLOTS >> (4 * k)) & 15u) * SLOT, &tmW, k0, 2 * hg, BAR(B_FQ + k));
        }
      }
#pragma unroll 1
      for (int i = 0; i < 16; i++) {
        mbar_wait(i < 7 ? BAR(B_EQ + ((i + WQ0) >> 1)) : (i < 9 ? BAR(B_DE) : BAR(B_EO + i - 9)), 0);
        if (i == WOK) mbar_wait(BAR(B_KVB), 0);
        mbar_wait(BAR(B_FWO + i - (i < WOK ? WOD1 : WOD)), 0);
        if (elect_one()) {
          mbar_expect_tx(BAR(B_FWO + i), SLOT);
#pragma unroll
          for (int hf = 0; hf < ((MC & 4) ? 1 : 2); hf++) {
            const int n = 2 * i + ((MC & 4) ? rank : hf), m = slab(n - 4, hg), hd = n < 4 ? 4 * hg + n : 4 * (m & 7) + (m >> 3);
            if (i < 2 + NDIR) tma5d(sb + wo_slot(i) * SLOT + (n & 1) * 8192, &tmWp, hd * 4, 2 * hg, BAR(B_FWO + i), MC & 4);
            else if (MC & 4) tma3d_mc(sb + wo_slot(i) * SLOT + rank * 8192, &tmWo, hd * 32, 2 * hg, BAR(B_FWO + i));
            else tma3d(sb + wo_slot(i) * SLOT + hf * 8192, &tmWo, hd * 32, 2 * hg, BAR(B_FWO + i));
          }
        }
      }
    } else if (warp == 13) {
      if (elect_one()) {
        map_pf(rank ? &tmU : &tmG); map_pf(&tmR); map_pf(&tmD); map_pf(&tmWo); map_pf(&tmWp); map_pf(&tmOut);
      }
      bar_sync<6, 64>();
      if (elect_one()) {
        cnt_wait(C_B, NCTA);
        fence_async_gmem();
        mbar_expect_tx(BAR(B_FAUX), 1024);
        bulk_ld(sb + A_ST, G.stats + tb * 128, 1024, BAR(B_FAUX));
      }
      __syncwarp();
      TLS(416, 68);
#pragma unroll 1
      for (int m = 1; m < 4; m++) {
        const int part = m == 3 ? 0 : m;
        uint4 c;
#pragma unroll 1
        for (uint32_t it = 0; it < SPIN_MAX; it++) {
          c = ldx4(G.cs + part * DM + hg * 128 + lane * 4);
          if (__all_sync(~0u, min(min(c.x, c.y), min(c.z, c.w)))) break;
          __nanosleep(POLLNS);
        }
        if (CQ4 && part == 0) {
          const uint32_t o = sb + A_CS + (lane >> 2) * 64 + (lane & 1) * 32 + ((lane >> 1) & 1) * 8;
          asm volatile("st.shared.v2.u32 [%0], {%1,%2};\nst.shared.v2.u32 [%0+16], {%3,%4};" ::"r"(o), "r"(c.x), "r"(c.y), "r"(c.z), "r"(c.w) : "memory");
        } else sts_u4(sb + A_CS + part * 512 + lane * 16, c);
        __syncwarp();
        if (m > 1 && lane == 0) mbar_arrive(BAR(m == 2 ? B_FAUX : B_CQ));
        TLS(416, 71 + m);
      }
      mbar_wait(BAR(B_XS), 1);
      if (elect_one()) asm volatile("red.relaxed.gpu.global.add.u32 [%0], 1;" ::"l"(&G.cnt[C_DONE]) : "memory");
    } else if (warp == 14) {
      const uint4 sent = make_uint4(SENT, SENT, SENT, SENT);
      uint4* ro = G.o + (tb * 32 + hg) * 512 + lane;
      uint4* rp = G.part + b * 544 + lane;
      if (RSL) bar_sync<5, 160>(); else mbar_wait(BAR(B_AST), 0);
#pragma unroll 1
      for (int i = RS0; i < 40; i++) {
        uint4* q = i < 32 ? ro + (i >> 3) * 4096 + (i & 7) * 64 : rp + (i - 32) * 64;
        q[0] = sent; q[32] = sent;
        __nanosleep(RSNS);
      }
      rp[512] = sent;
#pragma unroll
      for (int i = 0; i < 4; i++) G.y[u * 128 + i * 32 + lane] = sent;
      if (unit) reinterpret_cast<uint4*>(G.h)[u * 32 + lane] = sent;
      G.fin[hg * 640 + tb * 40 + lane] = sent;
      if (lane < 8) G.fin[hg * 640 + tb * 40 + 32 + lane] = sent;
      if (!RSL) bar_sync<5, 160>();
      __syncwarp();
      TLS(448, 67);
      if (lane == 0) cnt_arrive(C_B);
      __syncwarp();
      TLS(448, 32);
      asm volatile("bar.arrive 6, 64;" ::: "memory");
    } else {
      const uint32_t stg = sb + 12 * SLOT;
      auto load_a = [&](int n, int r) {
        mbar_expect_tx(BAR(B_MF + r), (MX & 2) ? 1024 : MT);
        if (!(MX & 2)) tma2d_ef(sb + m_off(r), rank ? &tmU : &tmG, (u >> 1) * 64, n * 64, BAR(B_MF + r));
      };
      mbar_wait(BAR(B_XS), 0);
      if (unit) {
#pragma unroll 1
        for (int i = 0; i < 3; i++) {
          if (elect_one()) load_a(i, i);
          __nanosleep(PFILL);
        }
      }
      uint32_t key;
#pragma unroll 1
      for (uint32_t it = 0; it < SPIN_MAX; it++) {
        key = ldx1(G.top + ((u >> 1) & 3) * 32 + (lane & 7));
        if (__all_sync(~0u, key)) break;
        __nanosleep(TPNS);
      }
      TLS(480, 66);
      if (lane < 8) sts_u(sb + MISC + M_IDX + lane * 4, key);
      __syncwarp();
      if (lane == 0) mbar_arrive(BAR(B_XS));
      if (unit) {
        int tok[8];
#pragma unroll
        for (int i = 0; i < 8; i++) tok[i] = ~__shfl_sync(~0u, key, i) & 2047;
        int r = 0, p = 0;
#pragma unroll 1
        for (int n = 0; n < 16; n++) {
          if (n >= 3) mbar_wait(BAR(B_ME + r), r == 3 ? p : p ^ 1);
          if (elect_one()) {
            if (n >= 3) load_a(n, r);
#pragma unroll
            for (int i = 0; i < 8; i++) tma2d(sb + m_off(r) + 8192 + i * 128, &tmR, n * 64, tok[i], BAR(B_MF + r));
          }
          if (++r == NR) { r = 0; p ^= 1; }
        }
      }
      if (NUNIT) {
        if (lane == 0) mbar_expect_tx(BAR(B_DF), (MX & 8) ? 0 : 7 * 8192);
#pragma unroll 1
        for (int i = 0; i < 7; i++) {
          if (NR == 4) {
            if (i >= 3) mbar_wait(i < 5 ? BAR(B_ME + 3) : (R5 ? BAR(B_EQ + 1) : BAR(B_STG)), 0);
            else if (unit) mbar_wait(BAR(B_ME + i), 1);
          } else {
            if (i >= 3) mbar_wait(BAR(B_EQ + ((i - 3) >> 1)), 0);
            else if (unit) mbar_wait(BAR(B_ME + (i == 2 ? 0 : i + 1)), i == 2);
          }
          if (!(MX & 8) && elect_one()) tma2d_ef(sb + d_off(i), &tmD, dcol, drow + i * 64, BAR(B_DF));
          if (DNS) __nanosleep(DNS);
        }
      }
    }
    if (warp == 14) {
      if (DPF && NUNIT && !(MX & 8)) {
        mbar_wait(DS ? BAR(B_MS) : (DPF == 1 ? BAR(B_FQ) : BAR(B_T0)), 0);
#pragma unroll 1
        for (int pf = 0; pf < 7; pf++) { pf256(sb + MISC + M_DUM, wd + (size_t)(drow + pf * 64 + rank * 32 + lane) * DM + (dcol & ~127)); __nanosleep(PFNS2); }
      }
      const uint32_t* src = reinterpret_cast<const uint32_t*>(G.part + ((lane >> 3) * 32 + hg) * 544 + 512) + tb * 8 + (lane & 7);
      mbar_wait(BAR(B_EQ + MRW), 0);
      if (MRC) spin_cycles(MRC); else if (MRD) __nanosleep(MRD);
      uint32_t z0, z1, z2, z3;
#pragma unroll 1
      for (uint32_t it = 0; it < SPIN_MAX; it++) {
        z0 = ldx1(src); z1 = ldx1(src + 8 * 2176); z2 = ldx1(src + 16 * 2176); z3 = ldx1(src + 24 * 2176);
        if (!__any_sync(~0u, max(max(z0, z1), max(z2, z3)) == SENT)) break;
      }
      if (MRED == 2 && elect_one()) mbar_arrive(BAR(B_ZOK));
      float zz = (__uint_as_float(z0) + __uint_as_float(z1)) + (__uint_as_float(z2) + __uint_as_float(z3));
      zz += __shfl_xor_sync(~0u, zz, 8);
      zz += __shfl_xor_sync(~0u, zz, 16);
      stx1(reinterpret_cast<uint32_t*>(G.fin + hg * 640) + (tb >> 2) * 640 + 512 + ((tb >> 1) & 1) * 64 + (lane & 1) * 32 + (tb & 1) * 16 + ((lane & 7) >> 1) * 4 + (lane >> 3),
           pack_bf16(zz, zz));
      TLS(448, 12);
    }
    if (!MFIN && (warp == 13 || warp == 14)) {
      mbar_wait(BAR(B_EQ + H2W), 0);
      if (H2C) spin_cycles(H2C); else if (H2D) __nanosleep(H2D);
#pragma unroll 1
      for (uint32_t it = 0; it < SPIN_MAX; it++) {
        if (warp == 14 && elect_one()) {
          mbar_expect_tx(BAR(B_FIN), 10240);
          if (FMC && MC && it == 0) bulk_ld_mc(sb + S_KVB * SLOT + rank * 5120, G.fin + hg * 640 + rank * 320, 5120, BAR(B_FIN));
          else bulk_ld(sb + S_KVB * SLOT, G.fin + hg * 640, 10240, BAR(B_FIN));
        }
        mbar_wait(BAR(B_FIN), it & 1);
        uint32_t m = 0;
#pragma unroll
        for (int i = 0; i < 10; i++) m = max(m, lds_u(sb + S_KVB * SLOT + (i * 64 + ltid - 416) * 16 + (g >> 1) * 4));
        uint32_t bad;
        asm volatile("{\n.reg .pred p, q;\nsetp.eq.u32 p, %1, 0xFFFFFFFF;\nbar.red.or.pred q, 7, 64, p;\nselp.b32 %0, 1, 0, q;\n}" : "=r"(bad) : "r"(m) : "memory");
        if (!__any_sync(~0u, bad)) break;
      }
      if (warp == 14 && elect_one()) mbar_arrive(BAR(B_KVB));
      TLS(448, 14);
    }
    if (PH && (warp == 13 || warp == 14)) {
      bar_sync<3, 192>();
      mbar_wait(BAR(B_STG), 0);
#pragma unroll 1
      for (uint32_t it = 0; NUNIT && it < SPIN_MAX; it++) {
        if (elect_one()) {
          const uint32_t* ph = G.h + (u >> 4) * 7 * 256;
          if (warp == 13) { mbar_expect_tx(BAR(B_HF), 7168); bulk_ld(sb + h_off(3), ph + 768, 2048, BAR(B_HF)); bulk_ld(sb + h_off(5), ph + 1280, 2048, BAR(B_HF)); }
          else { bulk_ld(sb + h_off(0), ph, 1024, BAR(B_HF)); bulk_ld(sb + h_off(1), ph + 256, 1024, BAR(B_HF)); bulk_ld(sb + h_off(2), ph + 512, 1024, BAR(B_HF)); }
        }
        mbar_wait(BAR(B_HF), it & 1);
        uint32_t m = 0;
#pragma unroll
        for (int i = 0; i < 7; i++) m = max(m, lds_u(sb + h_off(i) + (ltid - 416) * 16 + (g >> 1) * 4));
        uint32_t bad;
        asm volatile("{\n.reg .pred p, q;\nsetp.eq.u32 p, %1, 0xFFFFFFFF;\nbar.red.or.pred q, 7, 64, p;\nselp.b32 %0, 1, 0, q;\n}" : "=r"(bad) : "r"(m) : "memory");
        if (!__any_sync(~0u, bad)) break;
        __nanosleep(POLLNS);
      }
      if (warp == 14 && elect_one()) mbar_arrive(BAR(B_KVB));
    }
    __syncwarp();
    if (warp >= 13) {
      const char* og = reinterpret_cast<const char*>(G.o + tb * 16384);
      auto probe = [&](uint32_t m) {
        const char* p = og + m * 8192u + (lane & 15) * 512 + 496;
#pragma unroll 1
        for (uint32_t it = 0; it < SPIN_MAX; it++)
          if (!__any_sync(~0u, ldx1(p) == SENT)) break;
      };
      if (warp == 15) {
        int r = 0, p = 1;
        mbar_wait(BAR(B_EAUX), 0);
#pragma unroll 1
        for (int i = I0; i < 16; i++) {
          const uint32_t dst = sb + ((A_SLOTS >> (4 * r)) & 15u) * SLOT, m0 = slab(2 * i - 4, hg), m1 = slab(2 * i - 3, hg);
          if (i == I0 + 3) mbar_wait(BAR(B_DE), 0);
          mbar_wait(BAR(B_EA + r), p);
          if ((PROBE >> i) & 1) probe(lane < 16 ? m0 : m1);
          if (elect_one()) {
            mbar_expect_tx(BAR(B_AF + r), SLOT);
            bulk_ld(dst, og + m0 * 8192u, 8192, BAR(B_AF + r)); bulk_ld(dst + 8192, og + m1 * 8192u, 8192, BAR(B_AF + r));
          }
          if (++r == NA) { r = 0; p ^= 1; }
        }
      } else {
        const uint32_t lo = lane * 32 + g * 4, hb = sb + (warp - 13) * 8192;
        uint32_t ph = 0;
        int r = 0, p = 0;
#pragma unroll 1
        for (int i = I0; i < 16; i++) {
          const uint32_t mine = hb + ((A_SLOTS >> (4 * r)) & 15u) * SLOT;
          auto bad = [&]() {
            uint32_t v[8];
#pragma unroll
            for (int j = 0; j < 8; j++) v[j] = lds_u(mine + lo + j * 1024);
            return __any_sync(~0u, max(max(max(v[0], v[1]), max(v[2], v[3])), max(max(v[4], v[5]), max(v[6], v[7]))) == SENT);
          };
          mbar_wait(BAR(B_AF + r), p);
          if (!NOVAL && bad()) {
            const uint32_t m = slab(2 * i - 17 + warp, hg);
#pragma unroll 1
            for (uint32_t it = 0; it < 64; it++) {
              probe(m);
              if (elect_one()) { mbar_expect_tx(BAR(B_AR + warp - 13), 8192); bulk_ld(mine, og + m * 8192u, 8192, BAR(B_AR + warp - 13)); }
              mbar_wait(BAR(B_AR + warp - 13), ph);
              ph ^= 1;
              if (!bad()) break;
            }
          }
          if (elect_one()) mbar_arrive(BAR(B_VAL + r));
          if (++r == NA) { r = 0; p ^= 1; }
        }
      }
    }
  } else if (warp >= 8) {
    asm volatile("setmaxnreg.dec.sync.aligned.u32 %0;" ::"n"(MOE_REGS));
    if (MC) asm volatile("barrier.cluster.wait.aligned;" ::: "memory");
    const int aw = warp - 8;
    const uint32_t mbuf = sb + MISC + M_MOE, stg = sb + 12 * SLOT;
    mbar_wait(BAR(B_AST), 0);
    TLS(288, 64);
    {
      float v[16];
#pragma unroll
      for (int r = 0; r < 16; r++) v[r] = 0.f;
      const uint32_t base = stg + aw * 4 * 2048 + lane * 8;
#pragma unroll 1
      for (int c = 0; c < 8; c++) {
        const float2 w2 = lds_f2(mbuf + c * 256 + lane * 8);
        const float w[4] = {bf_lo(__float_as_uint(w2.x)), bf_hi(__float_as_uint(w2.x)), bf_lo(__float_as_uint(w2.y)), bf_hi(__float_as_uint(w2.y))};
        v[12] += (w[0] + w[1]) + (w[2] + w[3]);
#pragma unroll
        for (int r = 0; r < 4; r++) {
          const float2 x2 = lds_f2(base + r * 2048 + c * 256);
#pragma unroll
          for (int e = 0; e < 2; e++) {
            const uint32_t xx = __float_as_uint(e ? x2.y : x2.x);
            const float lo = bf_lo(xx), hi = bf_hi(xx);
            v[r] += lo; v[4 + r] = fmaf(lo, lo, v[4 + r]); v[8 + r] = fmaf(lo, w[2 * e], v[8 + r]);
            v[r] += hi; v[4 + r] = fmaf(hi, hi, v[4 + r]); v[8 + r] = fmaf(hi, w[2 * e + 1], v[8 + r]);
          }
        }
      }
#pragma unroll
      for (int l = 0; l < 4; l++) {
        const int n = 8 >> l;
        const bool up = lane & (2 * n);
#pragma unroll
        for (int r = 0; r < 8; r++) {
          if (r < n) { const float a = v[r], c = v[n + r]; v[r] = (up ? c : a) + __shfl_xor_sync(~0u, up ? a : c, 2 * n); }
        }
      }
      v[0] += __shfl_xor_sync(~0u, v[0], 1);
      const float sx = __shfl_sync(~0u, v[0], 2 * t), sq = __shfl_sync(~0u, v[0], 8 + 2 * t), sw = __shfl_sync(~0u, v[0], 16 + 2 * t), ws = __shfl_sync(~0u, v[0], 24);
      if (lane < 4) {
        const int row = b * 16 + aw * 4 + lane;
        const float mean = sx * (1.f / DM);
        const float var = fmaxf(fmaf(-mean, mean, sq * (1.f / DM)), 0.f);
        float sd;
        asm("sqrt.approx.ftz.f32 %0, %1;" : "=f"(sd) : "f"(bf_round(bf_round(var) + 1e-5f)));
        const float rstd = rcp(bf_round(sd));
        const float mb = bf_round(mean);
        uint32_t rb = pack_bf16(fmaf(-mb, ws, sw) * rstd, 0.f) & 0xFFFFu;
        rb = (rb & 0x8000u) ? (~rb & 0xFFFFu) : (rb | 0x8000u);
        const uint32_t key = (1u << 27) | (rb << 11) | (uint32_t)(2047 - row);
        if (KEY1) sts_u(sb + MISC + M_KEY + (aw * 4 + lane) * 4, key); else stx1(G.key + row, key);
        G.stats[row] = make_float2(mb, SL2 ? rstd * LOG2E : rstd);
      }
    }
    bar_sync<2, 128>();
    if (KEY1 && ltid < 272) stx1(G.key + b * 16 + lane, lds_u(sb + MISC + M_KEY + lane * 4));
    TLS(288, 65);
    sts_u4(sb + A_ONES + (ltid - 256) * 16, make_uint4(0x3F803F80u, 0x3F803F80u, 0x3F803F80u, 0x3F803F80u));
    fence_async_smem();
    asm volatile("bar.arrive 5, 160;" ::: "memory");
    if (ltid == 256) { if (unit && rank == 0) mbar_expect_tx(BAR(B_UP), 2048); mbar_arrive(BAR(B_XS)); }
    bar_sync<2, 128>();
    mbar_wait(BAR(B_XS), 1);
    TLS(288, 70);
    if (NUNIT) {
      if (unit) {
        int r = 0, p = 0;
        uint32_t rel = 0;
        float acc[8];
        uint2 s0, s1;
#pragma unroll
        for (int i = 0; i < 8; i++) acc[i] = 0.f;
        if (MS == 16) mbar_wait(BAR(B_T0), 0); else if (MS) mbar_wait(BAR(B_MS), 0);
#pragma unroll 1
        for (int n = 0; n < 16; n++) {
          if (n == 15) {
            mbar_wait(BAR(B_FAUX), 0);
            s0 = ldx2(G.stats + (~lds_u(sb + MISC + M_IDX + t * 8) & 2047)); s1 = ldx2(G.stats + (~lds_u(sb + MISC + M_IDX + t * 8 + 4) & 2047));
            if (SL2) { s0.y = __float_as_uint(__uint_as_float(s0.y) * LN2); s1.y = __float_as_uint(__uint_as_float(s1.y) * LN2); }
          }
          mbar_wait(BAR(B_MF + r), p);
          if (!(n & 3)) TLS(288, 56 + (n >> 2));
          const uint32_t mo = m_off(r) >> 4, da = (d0 + mo) | (512u << 16), db = (d0 + mo + 512) | (1u << 16);
          const uint32_t hb = 0x40000000u | ((A_ONES >> 4) - 512 - mo);
          wg_fence();
#pragma unroll
          for (int kk = 0; kk < ((MX & 1) ? 1 : 4); kk++) wgmma_ss_n16<1, 0>(acc, mkdesc(da + kk * 128, HI_SW128), mkdesc(db + kk * 2, hb));
          wg_commit();
          wg_wait<1>();
          if (n > 0 && !rel && ltid == 256) mbar_arrive(BAR(B_ME + (r == 0 ? NR - 1 : r - 1)));
          rel = 0;
          const int r0 = r;
          if (++r == NR) { r = 0; p ^= 1; }
        }
        wg_wait<0>();
        reg_fence(acc);
        {
          if (!MW0 && !rel && ltid == 256) mbar_arrive(BAR(B_ME + 15 % NR));
          TLS(288, 71);
          const float v0 = bf_round(fmaf(-__uint_as_float(s0.x), acc[4], acc[0]) * __uint_as_float(s0.y));
          const float v1 = bf_round(fmaf(-__uint_as_float(s1.x), acc[4], acc[1]) * __uint_as_float(s1.y));
          const float v2 = bf_round(fmaf(-__uint_as_float(s0.x), acc[6], acc[2]) * __uint_as_float(s0.y));
          const float v3 = bf_round(fmaf(-__uint_as_float(s1.x), acc[6], acc[3]) * __uint_as_float(s1.y));
          if (rank) {
            asm volatile("{\n.reg .b32 ra, rb;\nmapa.shared::cluster.u32 ra, %0, 0;\nmapa.shared::cluster.u32 rb, %1, 0;\n"
                         "st.async.weak.shared::cluster.mbarrier::complete_tx::bytes.v4.f32 [ra], {%2, %3, %4, %5}, [rb];\n}"
                         ::"r"(mbuf + (ltid - 256) * 16), "r"(BAR(B_UP)), "f"(v0), "f"(v1), "f"(v2), "f"(v3) : "memory");
          } else {
            const float g0 = bf_round(v0 * sigmoid(v0)), g1 = bf_round(v1 * sigmoid(v1)), g2 = bf_round(v2 * sigmoid(v2)), g3 = bf_round(v3 * sigmoid(v3));
            mbar_wait(BAR(B_UP), 0);
            const uint4 uu = lds_u4(mbuf + (ltid - 256) * 16);
            const uint32_t h0 = movmat(pack_bf16(g0 * __uint_as_float(uu.x), g1 * __uint_as_float(uu.y)));
            const uint32_t h1 = movmat(pack_bf16(g2 * __uint_as_float(uu.z), g3 * __uint_as_float(uu.w)));
            uint32_t* ph = G.h + (u >> 1) * 256 + g * 32 + t;
            stx1(ph + ((2 * aw) ^ g) * 4, h0); stx1(ph + ((2 * aw + 1) ^ g) * 4, h1);
          }
          TLS(288, 60);
        }
      }
    }
    if (PH) asm volatile("bar.arrive 3, 192;" ::: "memory");
    {
      const int wd_ = ltid & 63;
      const uint32_t* src = reinterpret_cast<const uint32_t*>(G.part + hg * 544 + (aw >> 1) * 256 + tb * 16) + wd_;
      mbar_wait(MRED == 2 ? BAR(B_ZOK) : BAR(B_EQ + MRW), 0);
      if (MRC) spin_cycles(MRC); else if (MRD) __nanosleep(MRD);
      TLS(256, 48);
      uint32_t v[16];
#pragma unroll 1
      for (uint32_t it = 0; it < SPIN_MAX; it++) {
        uint32_t m = 0;
#pragma unroll
        for (int i = 0; i < 16; i++) v[i] = ldx1(src + i * 8 * 2176);
#pragma unroll
        for (int i = 0; i < 16; i++) m = max(m, v[i]);
        if (!__any_sync(~0u, m == SENT)) break;
      }
      TLS(256, 55);
      float lo[4], hi[4];
#pragma unroll
      for (int i = 0; i < 4; i++) {
        lo[i] = (bf_lo(v[4 * i]) + bf_lo(v[4 * i + 1])) + (bf_lo(v[4 * i + 2]) + bf_lo(v[4 * i + 3]));
        hi[i] = (bf_hi(v[4 * i]) + bf_hi(v[4 * i + 1])) + (bf_hi(v[4 * i + 2]) + bf_hi(v[4 * i + 3]));
      }
      stx1(reinterpret_cast<uint32_t*>(G.fin + hg * 640) + (tb >> 2) * 640 + ((tb >> 1) & 1) * 64 + (tb & 1) * 16 + (aw >> 1) * 32 + ((wd_ >> 2) & 3) * 128 + (wd_ >> 4) * 4 + (wd_ & 3),
           pack_bf16((lo[0] + lo[1]) + (lo[2] + lo[3]), (hi[0] + hi[1]) + (hi[2] + hi[3])));
      TLS(256, 5);
    }
    if (NUNIT) {
      mbar_wait(BAR(B_STG), 0);
      bar_sync<2, 128>();
      if (HW) __nanosleep(HW);
#pragma unroll 1
      for (uint32_t it = 0; it < SPIN_MAX; it++) {
        if (elect_one()) {
          const uint32_t* ph = G.h + (u >> 4) * 7 * 256;
          if (aw == 3) { mbar_expect_tx(BAR(B_HF), 7168); bulk_ld(sb + h_off(3), ph + 768, 2048, BAR(B_HF)); bulk_ld(sb + h_off(5), ph + 1280, 2048, BAR(B_HF)); }
          else bulk_ld(stg + aw * MT + 8192, ph + aw * 256, 1024, BAR(B_HF));
        }
        mbar_wait(BAR(B_HF), it & 1);
        const uint32_t o = (ltid & 63) * 16 + (g >> 1) * 4, o2 = o + (aw >> 1) * 1024;
        const uint32_t m = max(max(lds_u(sb + h_off(0) + (aw >> 1) * MT + o), lds_u(sb + h_off(2) + o)), max(lds_u(sb + h_off(3) + o2), lds_u(sb + h_off(5) + o2)));
        uint32_t bad;
        asm volatile("{\n.reg .pred p, q;\nsetp.eq.u32 p, %1, 0xFFFFFFFF;\nbar.red.or.pred q, 2, 128, p;\nselp.b32 %0, 1, 0, q;\n}" : "=r"(bad) : "r"(m) : "memory");
        if (!__any_sync(~0u, bad)) break;
        __nanosleep(POLLNS);
      }
      TLS(288, 62);
      float acc[4] = {0.f, 0.f, 0.f, 0.f};
      mbar_wait(BAR(B_DF), 0);
      TLS(288, 63);
#pragma unroll 1
      for (int i = 0; i < 7; i++) {
        const uint32_t da = (d0 + (d_off(i) >> 4)) | (512u << 16), db = (d0 + (h_off(i) >> 4)) | (1u << 16);
        wg_fence();
#pragma unroll
        for (int kk = 0; kk < ((MX & 4) ? 1 : 4); kk++) wgmma_ss_n8<1, 0>(acc, mkdesc(da + kk * 128, HI_SW128), mkdesc(db + kk * 2, HI_SW128));
        wg_commit();
      }
      wg_wait<0>();
      reg_fence(acc);
      if (ltid < 258) { if (MC) mbar_arrive_cta(BAR(B_DE), ltid & 1); else mbar_arrive(BAR(B_DE)); }
      {
        uint32_t* py = reinterpret_cast<uint32_t*>(G.y) + u * 512 + t * 128 + aw * 16 + g;
        stx1(py, f2x(acc[0])); stx1(py + 64, f2x(acc[1])); stx1(py + 8, f2x(acc[2])); stx1(py + 72, f2x(acc[3]));
      }
      TLS(288, 69);
      const uint32_t key = lds_u(sb + MISC + M_IDX + (lane & 7) * 4);
      uint32_t rb = (key >> 11) & 0xFFFFu;
      rb = (rb & 0x8000u) ? (rb & 0x7FFFu) : (~rb & 0xFFFFu);
      const float sg = bf_round(sigmoid(__uint_as_float(rb << 16)));
      uint32_t hits = __ballot_sync(~0u, ((~key >> 7) & 15) == tb) & 255u;
      const uint32_t* py = reinterpret_cast<const uint32_t*>(G.y) + (2 * hg + (aw >> 1)) * 512 + (ltid & 63);
      if (hits) {
        sts_u4(mbuf + (ltid - 256) * 16, make_uint4(0, 0, 0, 0));
        bar_sync<2, 128>();
        if (YW >= 0) mbar_wait(BAR(B_EO + YW), 0); else if (YW == -2) mbar_wait(BAR(B_EAUX), 0);
      }
#pragma unroll 1
      while (hits) {
        const int n0 = __ffs(hits) - 1;
        hits &= hits - 1;
        const int n1 = hits ? __ffs(hits) - 1 : n0;
        hits &= hits - 1;
        uint32_t v[16];
#pragma unroll 1
        for (uint32_t it = 0; it < SPIN_MAX; it++) {
          uint32_t m = 0;
#pragma unroll
          for (int i = 0; i < 8; i++) { v[i] = ldx1(py + n0 * 64 + i * 8192); v[8 + i] = ldx1(py + n1 * 64 + i * 8192); }
#pragma unroll
          for (int i = 0; i < 16; i++) m = max(m, v[i]);
          if (!__any_sync(~0u, m == SENT)) break;
          __nanosleep(POLLNS);
        }
#pragma unroll
        for (int e = 0; e < 2; e++) {
          const uint32_t* w8 = v + 8 * e;
          const float y = ((__uint_as_float(w8[0]) + __uint_as_float(w8[1])) + (__uint_as_float(w8[2]) + __uint_as_float(w8[3]))) +
                          ((__uint_as_float(w8[4]) + __uint_as_float(w8[5])) + (__uint_as_float(w8[6]) + __uint_as_float(w8[7])));
          const int n = e ? n1 : n0;
          sts_h(mbuf + (aw >> 1) * 1024 + n * 128 + ((((ltid >> 3) & 7) ^ n) << 4) + (lane & 7) * 2, bf_round(y) * __shfl_sync(~0u, sg, n));
        }
      }
    }
    if (!NUNIT && ltid < 258) mbar_arrive(BAR(B_DE));
    fence_async_smem();
    bar_sync<2, 128>();
    TLS(288, 33);
    if (ltid == 288) mbar_arrive(BAR(B_MOE));
  } else {
    asm volatile("setmaxnreg.inc.sync.aligned.u32 %0;" ::"n"(CON_REGS));
    if (MC) asm volatile("barrier.cluster.wait.aligned;" ::: "memory");
    const int w = warp >> 2, wq = warp & 3, tid = ltid;
    const bool lead = (tid & 127) == 0;
    const uint32_t dA = (d0 + w * 512) | (1u << 16);
    const uint32_t dB = d0 | (512u << 16);
    auto release = [&](int bar) { if (lead) mbar_arrive(BAR(bar)); };
    auto release2 = [&](int bar) {
      if (MC) { if ((tid & 127) < 2) mbar_arrive_cta(BAR(bar), tid & 1); } else release(bar);
    };
    float aq[64], ak[64], av[64];
#pragma unroll
    for (int i = 0; i < 64; i++) aq[i] = ak[i] = av[i] = 0.f;
    auto q_step = [&](uint32_t bar, int p, uint32_t xs, uint32_t qs) {
      mbar_wait_b(bar, p);
      wg_fence();
#pragma unroll
      for (int kk = 0; kk < 4; kk++)
        wgmma_ss_n128<0, 1>(aq, mkdesc(dA + xs * 1024 + kk * 2, HI_SW128), mkdesc(dB + qs * 1024 + kk * 128, HI_SW128));
      wg_commit();
    };
    const uint32_t dT = dB + w * 512, dX = d0 | (1u << 16);
    auto t_step = [&](float (&a)[64], uint32_t ws, uint32_t xs) {
      wg_fence();
#pragma unroll
      for (int kk = 0; kk < 4; kk++)
        wgmma_ss_n128<1, 0>(a, mkdesc(dT + ws * 1024 + kk * 128, HI_SW128), mkdesc(dX + xs * 1024 + kk * 2, HI_SW128));
      wg_commit();
    };
    {
      int s = 0, p = 0, sp = 2;
#pragma unroll 1
      for (int e = 0; e < NF; e++) {
        TLS(0, 16 + e);
        if (((MS && MS < NF) || (DS && DS < NF)) && e == (MS ? MS : DS)) release(B_MS);
        q_step(BAR(B_FXQ + s), p, s, 3 + s);
        wg_wait<1>();
        if (e > 0) release2(B_E + sp);
        mbar_wait(BAR(B_FKV + s), p);
        t_step(ak, 6 + 2 * s, s);
        if (R5) mbar_wait(BAR(B_FV + s), p);
        t_step(av, 7 + 2 * s, s);
        if (R5 && e == NF - 1) { wg_wait<1>(); release2(B_EK + s); }
        sp = s;
        if (++s == 3) { s = 0; p ^= 1; }
      }
#pragma unroll 1
      for (int e = NF; e < 16; e++) {
        TLS(0, 16 + e);
        if (((MS >= NF && MS < 16) || DS >= NF) && e == (MS ? MS : DS)) release(B_MS);
        if (ST && e == 16 - ST && w == 1) mbar_wait(BAR(B_GT), 0);
        mbar_wait(BAR(B_FXQ + s), p);
        mbar_wait(BAR(B_FKV + s), p);
        t_step(ak, R5 ? (K_SLOTS >> (4 * (e - 10))) & 15u : 6 + 2 * s, x_slot(e, s));
        wg_wait<1>();
        release2(B_E + sp);
        if (R5) mbar_wait(BAR(B_FV + s), p);
        t_step(av, R5 ? (V_SLOTS >> (4 * (e - 10))) & 15u : 7 + 2 * s, x_slot(e, s));
        if (ST && e == 15 && tid == 0) mbar_arrive(BAR(B_GT));
        if (R5) { wg_wait<1>(); release2(B_EK + s); }
        sp = s;
        if (++s == 3) { s = 0; p ^= 1; }
      }
    }
    const uint32_t aux = sb;
    mbar_wait(BAR(B_FAUX), 0);
    const int row0 = w * 64 + wq * 16 + g;
    const float ck0 = lds_f(aux + A_CS + 512 + row0 * 4), ck1 = lds_f(aux + A_CS + 512 + (row0 + 8) * 4);
    const float cv0 = lds_f(aux + A_CS + 1024 + row0 * 4), cv1 = lds_f(aux + A_CS + 1024 + (row0 + 8) * 4);
    const uint32_t moff = (uint32_t)(w * 64 + wq * 16 + (lane & 15)) * 128 + (((lane >> 4) ^ (lane & 7)) << 4);
    const uint32_t sta = aux + A_ST + t * 16;
    float kvp[36], ao[64];
    uint32_t xr[32];
    float nm0, nm1, rs0, rs1, rl0, rl1;
    auto row_stats = [&]() {
      const float2 st0 = lds_f2(aux + A_ST + row0 * 8), st1 = lds_f2(aux + A_ST + (row0 + 8) * 8);
      nm0 = -st0.x; nm1 = -st1.x;
      if (SL2) { rl0 = st0.y; rl1 = st1.y; rs0 = rl0 * LN2; rs1 = rl1 * LN2; }
      else { rs0 = st0.y; rs1 = st1.y; rl0 = rs0 * LOG2E; rl1 = rs1 * LOG2E; }
    };
    auto ld_x = [&]() {
#pragma unroll
      for (int j = 0; j < 16; j += 2) ldsm4(sb + (j < 8 ? SX14 : SX15) * SLOT + (moff ^ ((j & 7) << 4)), xr[2 * j], xr[2 * j + 1], xr[2 * j + 2], xr[2 * j + 3]);
    };
    auto resid = [&]() {
      const float c0 = 1.f + rs0, c1 = 1.f + rs1, e0 = nm0 * rs0, e1 = nm1 * rs1;
#pragma unroll
      for (int j = 0; j < 16; j++) {
        ao[4 * j + 0] = fmaf(bf_lo(xr[2 * j]), c0, e0); ao[4 * j + 1] = fmaf(bf_hi(xr[2 * j]), c0, e0);
        ao[4 * j + 2] = fmaf(bf_lo(xr[2 * j + 1]), c1, e1); ao[4 * j + 3] = fmaf(bf_hi(xr[2 * j + 1]), c1, e1);
      }
    };
    {
      uint32_t pa[32];
      float4 st[16];
      auto ld = [&](int j) { st[j] = lds_f4(sta + j * 64); };
      auto k_blk = [&](int c) {
#pragma unroll
        for (int i = 0; i < 2; i++) {
          const float4 u = st[2 * c + i];
          const float l0 = u.y * LOG2E, l1 = u.w * LOG2E;
          const float* a = ak + 8 * c + 4 * i;
          pa[4 * c + 2 * i] = SL2 ? phi2l(FOLD(-u.x, ck0, a[0]), u.y, FOLD(-u.z, ck0, a[1]), u.w) : phi2<(VOL & 1) != 0>(FOLD(-u.x, ck0, a[0]), u.y, l0, FOLD(-u.z, ck0, a[1]), u.w, l1);
          pa[4 * c + 2 * i + 1] = SL2 ? phi2l(FOLD(-u.x, ck1, a[2]), u.y, FOLD(-u.z, ck1, a[3]), u.w) : phi2<(VOL & 1) != 0>(FOLD(-u.x, ck1, a[2]), u.y, l0, FOLD(-u.z, ck1, a[3]), u.w, l1);
        }
      };
      const uint32_t voff = sb + w * 8192 + (uint32_t)(8 * (lane >> 4) + (lane & 7)) * 128 + (((2 * wq + ((lane >> 3) & 1)) ^ (lane & 7)) << 4);
      auto v_blk = [&](int c) {
        uint32_t r[4];
#pragma unroll
        for (int i = 0; i < 2; i++) {
          const float4 u = st[2 * c + i];
          const float* a = av + 8 * c + 4 * i;
          r[2 * i] = pack_bf16(FOLD(-u.x, cv0, a[0]) * u.y, FOLD(-u.z, cv0, a[1]) * u.w);
          r[2 * i + 1] = pack_bf16(FOLD(-u.x, cv1, a[2]) * u.y, FOLD(-u.z, cv1, a[3]) * u.w);
        }
        stsm4t(voff + (c < 4 ? S_V0 : S_V1) * SLOT + (c & 3) * 2048, r[0], r[1], r[2], r[3]);
      };
      auto kv_mma = [&](int c) {
        const uint32_t bo = (c < 4 ? S_V0 : S_V1) * 1024 + w * 512 + (c & 3) * 128;
        const uint64_t bb = mkdesc((d0 + bo) | (((A_ONES >> 4) - bo) << 16), HI_SW128);
        if (c == 0) wgmma_rz_n72<1>(kvp, pa[4 * c], pa[4 * c + 1], pa[4 * c + 2], pa[4 * c + 3], bb);
        else wgmma_rs_n72<1>(kvp, pa[4 * c], pa[4 * c + 1], pa[4 * c + 2], pa[4 * c + 3], bb);
      };
      if (NOFOLD == 2) {
        wg_fence();
        wgmma_rs_n128<0>(ak, __float_as_uint(ck0), __float_as_uint(ck1), 0u, 0u, mkdesc(dX + SX14 * 1024, HI_SW128));
        wgmma_rs_n128<0>(av, __float_as_uint(cv0), __float_as_uint(cv1), 0u, 0u, mkdesc(dX + SX14 * 1024, HI_SW128));
        wg_commit();
      }
      if (SH2 && R5) {
        reg_fence(ak);
        ld(6); ld(7); k_blk(3);
        asm volatile("" : "+r"(pa[12]), "+r"(pa[13]), "+r"(pa[14]), "+r"(pa[15]));
      }
      ld(0); ld(1);
      wg_wait<0>();
      if (!(SH2 && R5)) reg_fence(ak);
      reg_fence(av);
      TLS(0, 2);
      if (!R5) release2(B_E);
      release(B_T0);
      if (LQ) { v_blk(0); ld(2); ld(3); } else { ld(2); ld(3); v_blk(0); }
      ld(4); ld(5); v_blk(1); k_blk(0);
      ld(6); ld(7); v_blk(2); ld(8); ld(9); v_blk(3); k_blk(1);
      ld(10); ld(11); v_blk(4); ld(12); ld(13); v_blk(5); k_blk(2);
      ld(14); ld(15); v_blk(6); v_blk(7); if (!(SH2 && R5)) k_blk(3);
      if (RL) { ld(8); ld(9); }
#pragma unroll
      for (int c = 4; c < KS; c++) k_blk(c);
      TLS(0, 3);
      fence_async_smem();
      asm volatile("bar.sync %0, 128;" ::"r"(3 + w) : "memory");
      if (XP == 0) ld_x();
      wg_fence();
#pragma unroll
      for (int c = 0; c < KS; c++) kv_mma(c);
      wg_commit();
#pragma unroll
      for (int c = KS; c < 8; c++) {
        if (RL && c < 7) { ld(2 * c + 2); ld(2 * c + 3); }
        k_blk(c);
        wg_fence();
        kv_mma(c);
        wg_commit();
      }
      if (XP == 3 && (RK == 0 || RK == 9)) ld_x();
      if (QE) { q_step(BAR(B_FQ), 0, SXQ0, QW_SLOTS & 15u); wg_wait<1>(); } else wg_wait<0>();
      reg_fence(kvp);
      auto hand_back = [&]() { release2(B_STG); __syncwarp(); };
      if (!SF) hand_back();
      TLS(0, 4);
      uint4* pp = G.part + b * 544;
      uint32_t pk[8];
#pragma unroll
      for (int j = 0; j < 8; j++) pk[j] = wq >= 2 ? pack_bf16(kvp[16 + 2 * j], kvp[17 + 2 * j]) : pack_bf16(kvp[2 * j], kvp[2 * j + 1]);
      stx4(pp + tid, pk[0], pk[2], pk[4], pk[6]);
      stx4(pp + 256 + tid, pk[1], pk[3], pk[5], pk[7]);
      if (t == 0) stx2(reinterpret_cast<uint2*>(pp + 512) + (tid >> 2), f2x(kvp[32]), f2x(kvp[34]));
      if (SF == 1) hand_back();
      if (XP == 1) ld_x();
      if (!QE) q_step(BAR(B_FQ), 0, SXQ0, QW_SLOTS & 15u);
      if (XP == 2) ld_x();
      if (SF == 2) hand_back();
      if (RK == 0 || RK == 9) {
        uint32_t chk = 0;
#pragma unroll
        for (int j = 0; j < 8; j++) chk ^= xr[4 * j];
        asm volatile("{\n.reg .pred p;\nsetp.eq.u32 p, %0, 0x7FC17FC3;\n@p st.shared.u32 [%1], %0;\n}" ::"r"(chk), "r"(sb + MISC + M_DUM) : "memory");
      }
      const int wd_ = wq * 16 + (lane & 15);
      const uint32_t* src = reinterpret_cast<const uint32_t*>(G.part + ((lane >> 4) * 64 + hg) * 544 + w * 256 + tb * 16) + wd_;
      uint32_t* fin = reinterpret_cast<uint32_t*>(G.fin + hg * 640) + (tb >> 2) * 640 + ((tb >> 1) & 1) * 64 + (tb & 1) * 16 + w * 32 + ((wd_ >> 2) & 3) * 128 + wq * 4 + (wd_ & 3);
      uint32_t v[8];
      auto part_load = [&]() {
#pragma unroll
        for (int i = 0; i < 8; i++) v[i] = ldx1(src + i * 8 * 2176);
      };
#pragma unroll
      for (int k = 1; k < NQ; k++) {
        if (SQ && k == NQ - SQ && w == 1) mbar_wait(BAR(B_GQ), 0);
        q_step(BAR(B_FQ + k), 0, (QX_SLOTS >> (4 * k)) & 15u, (QW_SLOTS >> (4 * k)) & 15u);
        if (SQ && k == NQ - 1 && tid == 0) mbar_arrive(BAR(B_GQ));
        TLS(0, 48 + k);
        if (!MRED && k == PLP) part_load();
        if (!MRED && k == PLC) {
#pragma unroll 1
          for (uint32_t it = 0; it < SPIN_MAX; it++) {
            if (!__any_sync(~0u, max(max(max(v[0], v[1]), max(v[2], v[3])), max(max(v[4], v[5]), max(v[6], v[7]))) == SENT)) break;
            part_load();
          }
          float lo = ((bf_lo(v[0]) + bf_lo(v[1])) + (bf_lo(v[2]) + bf_lo(v[3]))) + ((bf_lo(v[4]) + bf_lo(v[5])) + (bf_lo(v[6]) + bf_lo(v[7])));
          float hi = ((bf_hi(v[0]) + bf_hi(v[1])) + (bf_hi(v[2]) + bf_hi(v[3]))) + ((bf_hi(v[4]) + bf_hi(v[5])) + (bf_hi(v[6]) + bf_hi(v[7])));
          lo += __shfl_xor_sync(~0u, lo, 16); hi += __shfl_xor_sync(~0u, hi, 16);
          if (lane < 16) stx1(fin, pack_bf16(lo, hi));
          TLS(0, 5);
        }
        wg_wait<1>();
        release2(B_EQ + k - 1);
        if (k == RK) { row_stats(); ld_x(); resid(); reg_fence(ao); }
      }
      TLS(0, 13);
      if (!NOCQ) mbar_wait(BAR(B_CQ), 0);
    }
    float4 cq4[8];
    auto ld_cq = [&](int j) {
      if (CQ4) cq4[j >> 1] = lds_f4(aux + A_CS + (j * 8 + 4 * t) * 4);
      else { const float2 ca = lds_f2(aux + A_CS + (j * 8 + 2 * t) * 4), cb = lds_f2(aux + A_CS + (j * 8 + 8 + 2 * t) * 4); cq4[j >> 1] = make_float4(ca.x, ca.y, cb.x, cb.y); }
    };
    if (CQE) {
      if (RK == 0 || RK == 9) row_stats();
#pragma unroll
      for (int j = 0; j < 16; j += 2) ld_cq(j);
    }
    wg_wait<0>();
    reg_fence(aq);
    TLS(0, 15);
    if (!CQE && (RK == 0 || RK == 9)) row_stats();
    uint32_t pq[32];
#pragma unroll
    for (int j = 0; j < 16; j += 2) {
      if (!CQE) ld_cq(j);
      const float4 c4 = cq4[j >> 1];
#pragma unroll
      for (int i = 0; i < 2; i++) {
        const float cx = i ? c4.z : c4.x, cy = i ? c4.w : c4.y;
        const float* a = aq + 4 * (j + i);
        pq[2 * (j + i)] = SL2 ? phi2l(fmaf(nm0, cx, a[0]), rl0, fmaf(nm0, cy, a[1]), rl0) : phi2<(VOL & 2) != 0>(fmaf(nm0, cx, a[0]), rs0, rl0, fmaf(nm0, cy, a[1]), rs0, rl0);
        pq[2 * (j + i) + 1] = SL2 ? phi2l(fmaf(nm1, cx, a[2]), rl1, fmaf(nm1, cy, a[3]), rl1) : phi2<(VOL & 2) != 0>(fmaf(nm1, cx, a[2]), rs1, rl1, fmaf(nm1, cy, a[3]), rs1, rl1);
      }
    }
    TLS(0, 6);
    if (RK == 9) { resid(); if (RF) reg_fence(ao); }
    mbar_wait_b(BAR(MFIN ? B_KV4 : B_KVB), 0);
    TLS(0, 7);
    uint32_t of[32];
    uint4* mine = G.o + (tb * 32 + hg) * 512 + warp * 64 + g * 4 + (t ^ (g >> 1));
    const uint32_t dW = d0 | (256u << 16);
    auto o_store = [&](int h) {
#pragma unroll
      for (int c = 0; c < 2; c++) stx4(mine + h * 4096 + c * 32, of[8 * h + c], of[8 * h + 2 + c], of[8 * h + 4 + c], of[8 * h + 6 + c]);
    };
    auto out_step = [&](uint32_t slot, const uint32_t* a) {
      const uint32_t d = dW + slot * 1024;
      wg_fence();
#pragma unroll
      for (int kk = 0; kk < 4; kk++) wgmma_rs_n128<1>(ao, a[4 * kk], a[4 * kk + 1], a[4 * kk + 2], a[4 * kk + 3], mkdesc(d + (kk >> 1) * 512 + (kk & 1) * 128, HI_SW128));
      wg_commit();
    };
    uint4 v[NDIR][4];
    auto ld_o = [&](int k) {
      const uint4* p0 = mine + (slab(2 * k, hg) - hg) * 512;
      const uint4* p1 = mine + (slab(2 * k + 1, hg) - hg) * 512;
      v[k][0] = ldx4(p0); v[k][1] = ldx4(p0 + 32); v[k][2] = ldx4(p1); v[k][3] = ldx4(p1 + 32);
    };
    auto ld_all = [&]() {
#pragma unroll
      for (int k = 0; k < NDIR; k++) ld_o(k);
    };
    {
      float oa[4][20];
      const uint32_t dK = (d0 + S_KVB * 1024) | (8u << 16);
      auto o_mma = [&](int h) {
        wgmma_rz_n40<1>(oa[h], pq[8 * h], pq[8 * h + 1], pq[8 * h + 2], pq[8 * h + 3], mkdesc(dK + h * 160, HI_NOSW));
        wgmma_rs_n40<1>(oa[h], pq[8 * h + 4], pq[8 * h + 5], pq[8 * h + 6], pq[8 * h + 7], mkdesc(dK + h * 160 + 16, HI_NOSW));
      };
      wg_fence();
      o_mma(0);
      wg_commit();
      if (OH == 0) { o_mma(1); o_mma(2); o_mma(3); wg_commit(); }
      if (OH == 2) { o_mma(1); wg_commit(); }
      auto norm = [&](int h) {
        const float r0 = SL2 ? rcp(fmaf(oa[h][16], LOG2E, 1e-6f * LOG2E)) : rcp(oa[h][16] + 1e-6f);
        const float r1 = SL2 ? rcp(fmaf(oa[h][18], LOG2E, 1e-6f * LOG2E)) : rcp(oa[h][18] + 1e-6f);
#pragma unroll
        for (int j = 0; j < 4; j++) {
          of[8 * h + 2 * j] = pack_bf16(oa[h][4 * j] * r0, oa[h][4 * j + 1] * r0);
          of[8 * h + 2 * j + 1] = pack_bf16(oa[h][4 * j + 2] * r1, oa[h][4 * j + 3] * r1);
        }
      };
      if (OH == 1) wg_wait<0>(); else wg_wait<1>();
      reg_fence(oa[0]);
      norm(0);
      if (LE == 4) ld_all();
      o_store(0);
      if (LE == 3) ld_all();
      TLS(0, 8);
      if (OH == 1) { wg_fence(); o_mma(1); o_mma(2); o_mma(3); wg_commit(); }
      if (OH == 2) { wg_fence(); o_mma(2); o_mma(3); wg_commit(); }
      wg_wait<0>();
      reg_fence(oa[1]); reg_fence(oa[2]); reg_fence(oa[3]);
      TLP_(0);
      release(B_EAUX);
      norm(1);
      if (OS1 == 3) o_store(1);
      if (E7 && NP == 0 && SL7 && hg == 7) o_store(1);
      if (NP == 0) { norm(2); norm(3); }
      if (E7 && NP == 0 && SL7 && hg == 7) { o_store(2); o_store(3); }
      TLP_(1);
      mbar_wait_b(BAR(B_FWO), 0);
      TLP_(2);
      if (RK == 0) resid();
      if (LE == 2) ld_all();
      TLP_(3);
      out_step(WO_SLOTS & 15u, of);
      TLP_(4);
      if (NP == 1) { norm(2); norm(3); }
      if (LE == 1) ld_all();
      if (LE == 5) ld_o(0);
    }
    if (OS1 == 0) o_store(1);
    mbar_wait(BAR(B_FWO + 1), 0);
    TLP_(5);
    out_step((WO_SLOTS >> 4) & 15u, of + 16);
    TLP_(6);
    const bool early = SL7 && hg == 7;
    if (OS1 == 1 && !(E7 && early)) o_store(1);
    TLP_(7);
    if (early && !E7) { o_store(2); o_store(3); }
    {
      if (DW) __nanosleep(DW);
      if (LE == 0) ld_all();
      if (LE == 5 && NDIR > 1) ld_o(NDIR - 1);
      if (OS1 == 2 && !(E7 && early)) o_store(1);
#pragma unroll
      for (int k = 0; k < NDIR; k++) {
#pragma unroll 1
        for (uint32_t it = 0; it < SPIN_MAX; it++) {
          if (!__any_sync(~0u, max(max(v[k][0].x, v[k][1].x), max(v[k][2].x, v[k][3].x)) == SENT)) break;
#pragma unroll
          for (int j = k; j < (LE == 5 ? k + 1 : NDIR); j++) ld_o(j);
        }
        TLP_(8);
        const uint32_t a[16] = {v[k][0].x, v[k][1].x, v[k][0].y, v[k][1].y, v[k][0].z, v[k][1].z, v[k][0].w, v[k][1].w,
                                v[k][2].x, v[k][3].x, v[k][2].y, v[k][3].y, v[k][2].z, v[k][3].z, v[k][2].w, v[k][3].w};
        mbar_wait(BAR(B_FWO + 2 + k), 0);
        TLS(0, 34 + k);
        out_step((WO_SLOTS >> (8 + 4 * k)) & 15u, a);
        TLP_(9);
        if (k) { wg_wait<1>(); release2(B_EO); }
      }
      if (!early) o_store(2);
    }
    auto routed = [&]() {
      mbar_wait(BAR(B_MOE), 0);
      const float2 kk = lds_f2(sb + MISC + M_IDX + t * 8);
      const int k0 = (int)(~__float_as_uint(kk.x) & 2047u) - tb * 128, k1 = (int)(~__float_as_uint(kk.y) & 2047u) - tb * 128;
      if (NUNIT && __any_sync(~0u, (k0 >> 6) == w || (k1 >> 6) == w)) {
        const uint32_t a0 = (k0 == row0 ? 0x3F80u : 0u) | (k1 == row0 ? 0x3F800000u : 0u);
        const uint32_t a1 = (k0 == row0 + 8 ? 0x3F80u : 0u) | (k1 == row0 + 8 ? 0x3F800000u : 0u);
        wg_fence();
        wgmma_rs_n128<1>(ao, a0, a1, 0u, 0u, mkdesc((d0 + ((MISC + M_MOE) >> 4)) | (64u << 16), 0x40000000u));
        wg_commit();
      }
    };
    auto out_half = [&](int h, const float* v) {
      const uint32_t ost = sb + (w ? S_D1 : S_D0) * SLOT + wq * 4096 + h * 2048;
#pragma unroll
      for (int j = 0; j < 8; j += 2)
        stsm4(ost + ((moff & 2047) ^ (j << 4)), pack_bf16(v[4 * j], v[4 * j + 1]), pack_bf16(v[4 * j + 2], v[4 * j + 3]),
              pack_bf16(v[4 * j + 4], v[4 * j + 5]), pack_bf16(v[4 * j + 6], v[4 * j + 7]));
      if (OUTV == 3 || (OUTV == 4 && h == 0)) {
        __syncwarp();
        __nv_bfloat16* dst = outp + (size_t)(tb * 128 + warp * 16 + (lane >> 3)) * DM + hg * 128 + h * 64 + (lane & 7) * 8;
#pragma unroll
        for (int i = 0; i < 4; i++) {
          const int r = 4 * i + (lane >> 3);
          const uint4 u4 = lds_u4(ost + r * 128 + (((lane & 7) ^ (r & 7)) << 4));
          asm volatile("st.global.v4.u32 [%0], {%1,%2,%3,%4};" ::"l"(dst + (size_t)i * 4 * DM), "r"(u4.x), "r"(u4.y), "r"(u4.z), "r"(u4.w) : "memory");
        }
        return;
      }
      fence_async_smem();
      __syncwarp();
      if (elect_one()) {
        if (OEF) asm volatile("cp.async.bulk.tensor.2d.global.shared::cta.bulk_group.L2::cache_hint [%0, {%2, %3}], [%1], %4;" ::"l"(&tmOut), "r"(ost), "r"(hg * 128 + h * 64), "r"(tb * 128 + warp * 16), "l"(POL_FIRST) : "memory");
        else asm volatile("cp.async.bulk.tensor.2d.global.shared::cta.bulk_group [%0, {%2, %3}], [%1];" ::"l"(&tmOut), "r"(ost), "r"(hg * 128 + h * 64), "r"(tb * 128 + warp * 16) : "memory");
        if (h) asm volatile("cp.async.bulk.commit_group;\ncp.async.bulk.wait_group.read 0;" ::: "memory");
      }
      __syncwarp();
    };
    bool done = false;
    {
      const uint32_t dO = (d0 + w * 256) | (1u << 16);
      auto step = [&](int i, int r, int p, uint32_t as, uint32_t ws) {
        mbar_wait(BAR(B_FWO + i), 0);
        mbar_wait(BAR(B_VAL + r), p);
        TLS(0, 32 + i);
        const uint32_t da = dO + as * 1024, db = dW + ws * 1024;
        wg_fence();
#pragma unroll
        for (int kk = 0; kk < 4; kk++)
          wgmma_ss_n128<0, 1>(ao, mkdesc(da + (kk >> 1) * 512 + (kk & 1) * 2, HI_SW64), mkdesc(db + (kk >> 1) * 512 + (kk & 1) * 128, HI_SW128));
        wg_commit();
      };
      uint64_t tbl = WO_SLOTS >> (4 * I0);
      int r = 0, p = 0, rp = 0;
#pragma unroll 1
      for (int i = I0; i < 12; i++) {
        step(i, r, p, (A_SLOTS >> (4 * r)) & 15u, (uint32_t)tbl & 15u);
        tbl >>= 4;
#pragma unroll
        for (int c = 0; c < 2; c++)
          if (i == OS3 + c && !early) stx4(mine + 3 * 4096 + c * 32, of[24 + c], of[26 + c], of[28 + c], of[30 + c]);
        wg_wait<1>();
        if (i > I0) release(B_EA + rp);
        rp = r;
        if (++r == NA) { r = 0; p ^= 1; }
        if (i >= 3 && i <= 9) release2(B_EO + i - 3);
      }
      if (SPL && w == 1) {
        float bl[32], bh[32];
        mbar_wait(BAR(B_GO), 0);
        routed();
#pragma unroll
        for (int h = 0; h < 2; h++) {
#pragma unroll
          for (int i = 12; i < 16; i++) {
            const int r_ = (i - I0) % NA;
            if (h == 0) { mbar_wait(BAR(B_FWO + i), 0); mbar_wait(BAR(B_VAL + r_), ((i - I0) / NA) & 1); }
            const uint32_t da = dO + ((A_SLOTS >> (4 * r_)) & 15u) * 1024, db = dW + ((uint32_t)(WO_SLOTS >> (4 * i)) & 15u) * 1024 + h * 256;
            if (h == 0 || i == 12) wg_fence();
#pragma unroll
            for (int kk = 0; kk < 4; kk++) {
              const uint64_t a = mkdesc(da + (kk >> 1) * 512 + (kk & 1) * 2, HI_SW64), bb = mkdesc(db + (kk >> 1) * 512 + (kk & 1) * 128, HI_SW128);
              if (i == 12 && kk == 0) wgmma_sz_n64<0, 1>(h ? bh : bl, a, bb); else wgmma_ss_n64<0, 1>(h ? bh : bl, a, bb);
            }
          }
          wg_commit();
        }
        wg_wait<1>();
        reg_fence(ao); reg_fence(bl);
#pragma unroll
        for (int j = 0; j < 32; j++) bl[j] += ao[j];
        out_half(0, bl);
        wg_wait<0>();
        reg_fence(bh);
#pragma unroll
        for (int j = 0; j < 32; j++) bh[j] += ao[32 + j];
        out_half(1, bh);
        done = true;
      } else
#pragma unroll
      for (int i = 12; i < 16; i++) {
        if (i == 16 - STAG && w == 1) mbar_wait(BAR(B_GO), 0);
        step(i, (i - I0) % NA, ((i - I0) / NA) & 1, (A_SLOTS >> (4 * ((i - I0) % NA))) & 15u, (uint32_t)(WO_SLOTS >> (4 * i)) & 15u);
        if (STAG && i == 15 - GOE && tid == 0) mbar_arrive(BAR(B_GO));
      }
    }
    if (!done) {
      routed();
      wg_wait<0>();
      reg_fence(ao);
      TLS(0, 10);
      out_half(0, ao);
      out_half(1, ao + 32);
    }
    TLS(0, 11);
    TLS(128, 9);
  }
}

typedef CUresult (*EncFn)(CUtensorMap*, CUtensorMapDataType, cuuint32_t, void*, const cuuint64_t*, const cuuint64_t*, const cuuint32_t*,
                          const cuuint32_t*, CUtensorMapInterleave, CUtensorMapSwizzle, CUtensorMapL2promotion, CUtensorMapFloatOOBfill);

void make_map2(EncFn enc, CUtensorMap* m, void* p, uint64_t rows, uint64_t cols, uint32_t brows, CUtensorMapL2promotion promo) {
  cuuint64_t gd[2] = {cols, rows}, gs[1] = {cols * 2};
  cuuint32_t bd[2] = {64, brows}, es[2] = {1, 1};
  enc(m, CU_TENSOR_MAP_DATA_TYPE_BFLOAT16, 2, p, gd, gs, bd, es, CU_TENSOR_MAP_INTERLEAVE_NONE, CU_TENSOR_MAP_SWIZZLE_128B, promo,
      CU_TENSOR_MAP_FLOAT_OOB_FILL_NONE);
}
void make_map3(EncFn enc, CUtensorMap* m, void* p, uint64_t rows, uint64_t cols, uint32_t brows) {
  cuuint64_t gd[3] = {64, rows, cols / 64}, gs[2] = {cols * 2, 128};
  cuuint32_t bd[3] = {64, brows, 2}, es[3] = {1, 1, 1};
  enc(m, CU_TENSOR_MAP_DATA_TYPE_BFLOAT16, 3, p, gd, gs, bd, es, CU_TENSOR_MAP_INTERLEAVE_NONE, CU_TENSOR_MAP_SWIZZLE_128B,
      CU_TENSOR_MAP_L2_PROMOTION_L2_256B, CU_TENSOR_MAP_FLOAT_OOB_FILL_NONE);
}

}

extern "C" void kernel_launch(void* const* d_in, const int* in_sizes, int n_in, void* d_out, int out_size) {
  static EncFn enc = nullptr;
  static int by_sm = 0;
  if (!enc) {
    void* fn = nullptr;
    cudaDriverEntryPointQueryResult qr;
    cudaGetDriverEntryPoint("cuTensorMapEncodeTiled", &fn, cudaEnableDefault, &qr);
    enc = (EncFn)fn;
    int dev = 0, sms = 0;
    cudaGetDevice(&dev);
    cudaDeviceGetAttribute(&sms, cudaDevAttrMultiProcessorCount, dev);
    by_sm = MAP == 2 && sms == NCTA + NSVC;
    cudaFuncSetAttribute(fused_kernel, cudaFuncAttributeMaxDynamicSharedMemorySize, SMEM_BYTES);
  }
  CUtensorMap tmX, tmW, tmWo, tmOut, tmG, tmU, tmD, tmR, tmWp;
  {
    cuuint64_t gd[5] = {64, 2, 128, 4, 16}, gs[4] = {2048, 16384, 4096, 128};
    cuuint32_t bd[5] = {64, 2, 4, 4, 2}, es[5] = {1, 1, 1, 1, 1};
    enc(&tmWp, CU_TENSOR_MAP_DATA_TYPE_BFLOAT16, 5, d_in[2], gd, gs, bd, es, CU_TENSOR_MAP_INTERLEAVE_NONE, CU_TENSOR_MAP_SWIZZLE_128B,
        CU_TENSOR_MAP_L2_PROMOTION_L2_256B, CU_TENSOR_MAP_FLOAT_OOB_FILL_NONE);
  }
  make_map2(enc, &tmR, d_in[0], SEQ, DM, 1, CU_TENSOR_MAP_L2_PROMOTION_L2_128B);
  make_map2(enc, &tmX, d_in[0], SEQ, DM, 128, XPROMO);
  make_map3(enc, &tmW, d_in[1], DM, 3 * DM, 64);
  make_map3(enc, &tmWo, d_in[2], DM, DM, 32);
  if (OUTV) make_map2(enc, &tmOut, d_out, SEQ, DM, 16, CU_TENSOR_MAP_L2_PROMOTION_L2_128B); else make_map3(enc, &tmOut, d_out, SEQ, DM, 64);
  make_map2(enc, &tmG, d_in[5], DM, FF, 64, MPROMO);
  make_map2(enc, &tmU, d_in[6], DM, FF, 64, MPROMO);
  make_map2(enc, &tmD, d_in[7], FF, DM, 64, MPROMO);
  typedef const __nv_bfloat16* P;
  cudaLaunchConfig_t cfg = {};
  cfg.gridDim = dim3(NCTA + NSVC); cfg.blockDim = dim3(512); cfg.dynamicSmemBytes = SMEM_BYTES; cfg.stream = cudaStreamPerThread;
  cudaLaunchAttribute at[1];
  at[0].id = cudaLaunchAttributeClusterDimension;
  at[0].val.clusterDim.x = 2; at[0].val.clusterDim.y = 1; at[0].val.clusterDim.z = 1;
  cfg.attrs = at; cfg.numAttrs = 1;
  cudaLaunchKernelEx(&cfg, fused_kernel, (P)d_in[0], (P)d_in[1], (P)d_in[2], (P)d_in[4], (P)d_in[7], (__nv_bfloat16*)d_out, by_sm, tmX, tmW, tmWo, tmOut, tmG, tmU, tmD, tmR, tmWp);
}
```

```cpp
#include <cuda_runtime.h>
#include <cuda.h>
#include <cuda_bf16.h>
#include <stdint.h>

#define WK 0
#define NOCQ 0
#define NOFOLD 0
#define FOLD(m, c, a) fmaf(m, c, a)
#define OEF 0
namespace {

template <int TA, int TB> __device__ __forceinline__ void wgmma_ss_n128(float (&d)[64], uint64_t da, uint64_t db) {
  asm volatile("wgmma.mma_async.sync.aligned.m64n128k16.f32.bf16.bf16 "
  "{%0,%1,%2,%3,%4,%5,%6,%7,%8,%9,%10,%11,%12,%13,%14,%15,%16,%17,%18,%19,%20,%21,%22,%23,%24,%25,%26,%27,%28,%29,%30,%31,%32,%33,%34,%35,%36,%37,%38,%39,%40,%41,%42,%43,%44,%45,%46,%47,%48,%49,%50,%51,%52,%53,%54,%55,%56,%57,%58,%59,%60,%61,%62,%63}, "
  "%64, %65, 1, 1, 1, %66, %67;"
  : "+f"(d[0]),"+f"(d[1]),"+f"(d[2]),"+f"(d[3]),"+f"(d[4]),"+f"(d[5]),"+f"(d[6]),"+f"(d[7]),"+f"(d[8]),"+f"(d[9]),"+f"(d[10]),"+f"(d[11]),"+f"(d[12]),"+f"(d[13]),"+f"(d[14]),"+f"(d[15]),"+f"(d[16]),"+f"(d[17]),"+f"(d[18]),"+f"(d[19]),"+f"(d[20]),"+f"(d[21]),"+f"(d[22]),"+f"(d[23]),"+f"(d[24]),"+f"(d[25]),"+f"(d[26]),"+f"(d[27]),"+f"(d[28]),"+f"(d[29]),"+f"(d[30]),"+f"(d[31]),"+f"(d[32]),"+f"(d[33]),"+f"(d[34]),"+f"(d[35]),"+f"(d[36]),"+f"(d[37]),"+f"(d[38]),"+f"(d[39]),"+f"(d[40]),"+f"(d[41]),"+f"(d[42]),"+f"(d[43]),"+f"(d[44]),"+f"(d[45]),"+f"(d[46]),"+f"(d[47]),"+f"(d[48]),"+f"(d[49]),"+f"(d[50]),"+f"(d[51]),"+f"(d[52]),"+f"(d[53]),"+f"(d[54]),"+f"(d[55]),"+f"(d[56]),"+f"(d[57]),"+f"(d[58]),"+f"(d[59]),"+f"(d[60]),"+f"(d[61]),"+f"(d[62]),"+f"(d[63])
  : "l"(da), "l"(db), "n"(TA), "n"(TB));
}
template <int TA, int TB> __device__ __forceinline__ void wgmma_ss_n64(float (&d)[32], uint64_t da, uint64_t db) {
  asm volatile("wgmma.mma_async.sync.aligned.m64n64k16.f32.bf16.bf16 "
  "{%0,%1,%2,%3,%4,%5,%6,%7,%8,%9,%10,%11,%12,%13,%14,%15,%16,%17,%18,%19,%20,%21,%22,%23,%24,%25,%26,%27,%28,%29,%30,%31}, "
  "%32, %33, 1, 1, 1, %34, %35;"
  : "+f"(d[0]),"+f"(d[1]),"+f"(d[2]),"+f"(d[3]),"+f"(d[4]),"+f"(d[5]),"+f"(d[6]),"+f"(d[7]),"+f"(d[8]),"+f"(d[9]),"+f"(d[10]),"+f"(d[11]),"+f"(d[12]),"+f"(d[13]),"+f"(d[14]),"+f"(d[15]),"+f"(d[16]),"+f"(d[17]),"+f"(d[18]),"+f"(d[19]),"+f"(d[20]),"+f"(d[21]),"+f"(d[22]),"+f"(d[23]),"+f"(d[24]),"+f"(d[25]),"+f"(d[26]),"+f"(d[27]),"+f"(d[28]),"+f"(d[29]),"+f"(d[30]),"+f"(d[31])
  : "l"(da), "l"(db), "n"(TA), "n"(TB));
}
template <int TA, int TB> __device__ __forceinline__ void wgmma_sz_n64(float (&d)[32], uint64_t da, uint64_t db) {
  asm volatile("wgmma.mma_async.sync.aligned.m64n64k16.f32.bf16.bf16 "
  "{%0,%1,%2,%3,%4,%5,%6,%7,%8,%9,%10,%11,%12,%13,%14,%15,%16,%17,%18,%19,%20,%21,%22,%23,%24,%25,%26,%27,%28,%29,%30,%31}, "
  "%32, %33, 0, 1, 1, %34, %35;"
  : "=f"(d[0]),"=f"(d[1]),"=f"(d[2]),"=f"(d[3]),"=f"(d[4]),"=f"(d[5]),"=f"(d[6]),"=f"(d[7]),"=f"(d[8]),"=f"(d[9]),"=f"(d[10]),"=f"(d[11]),"=f"(d[12]),"=f"(d[13]),"=f"(d[14]),"=f"(d[15]),"=f"(d[16]),"=f"(d[17]),"=f"(d[18]),"=f"(d[19]),"=f"(d[20]),"=f"(d[21]),"=f"(d[22]),"=f"(d[23]),"=f"(d[24]),"=f"(d[25]),"=f"(d[26]),"=f"(d[27]),"=f"(d[28]),"=f"(d[29]),"=f"(d[30]),"=f"(d[31])
  : "l"(da), "l"(db), "n"(TA), "n"(TB));
}
template <int TB> __device__ __forceinline__ void wgmma_rs_n72(float (&d)[36], uint32_t a0, uint32_t a1, uint32_t a2, uint32_t a3, uint64_t db) {
  asm volatile("wgmma.mma_async.sync.aligned.m64n72k16.f32.bf16.bf16 "
  "{%0,%1,%2,%3,%4,%5,%6,%7,%8,%9,%10,%11,%12,%13,%14,%15,%16,%17,%18,%19,%20,%21,%22,%23,%24,%25,%26,%27,%28,%29,%30,%31,%32,%33,%34,%35}, "
  "{%36,%37,%38,%39}, %40, 1, 1, 1, %41;"
  : "+f"(d[0]),"+f"(d[1]),"+f"(d[2]),"+f"(d[3]),"+f"(d[4]),"+f"(d[5]),"+f"(d[6]),"+f"(d[7]),"+f"(d[8]),"+f"(d[9]),"+f"(d[10]),"+f"(d[11]),"+f"(d[12]),"+f"(d[13]),"+f"(d[14]),"+f"(d[15]),"+f"(d[16]),"+f"(d[17]),"+f"(d[18]),"+f"(d[19]),"+f"(d[20]),"+f"(d[21]),"+f"(d[22]),"+f"(d[23]),"+f"(d[24]),"+f"(d[25]),"+f"(d[26]),"+f"(d[27]),"+f"(d[28]),"+f"(d[29]),"+f"(d[30]),"+f"(d[31]),"+f"(d[32]),"+f"(d[33]),"+f"(d[34]),"+f"(d[35])
  : "r"(a0), "r"(a1), "r"(a2), "r"(a3), "l"(db), "n"(TB));
}
template <int TB> __device__ __forceinline__ void wgmma_rz_n72(float (&d)[36], uint32_t a0, uint32_t a1, uint32_t a2, uint32_t a3, uint64_t db) {
  asm volatile("wgmma.mma_async.sync.aligned.m64n72k16.f32.bf16.bf16 "
  "{%0,%1,%2,%3,%4,%5,%6,%7,%8,%9,%10,%11,%12,%13,%14,%15,%16,%17,%18,%19,%20,%21,%22,%23,%24,%25,%26,%27,%28,%29,%30,%31,%32,%33,%34,%35}, "
  "{%36,%37,%38,%39}, %40, 0, 1, 1, %41;"
  : "=f"(d[0]),"=f"(d[1]),"=f"(d[2]),"=f"(d[3]),"=f"(d[4]),"=f"(d[5]),"=f"(d[6]),"=f"(d[7]),"=f"(d[8]),"=f"(d[9]),"=f"(d[10]),"=f"(d[11]),"=f"(d[12]),"=f"(d[13]),"=f"(d[14]),"=f"(d[15]),"=f"(d[16]),"=f"(d[17]),"=f"(d[18]),"=f"(d[19]),"=f"(d[20]),"=f"(d[21]),"=f"(d[22]),"=f"(d[23]),"=f"(d[24]),"=f"(d[25]),"=f"(d[26]),"=f"(d[27]),"=f"(d[28]),"=f"(d[29]),"=f"(d[30]),"=f"(d[31]),"=f"(d[32]),"=f"(d[33]),"=f"(d[34]),"=f"(d[35])
  : "r"(a0), "r"(a1), "r"(a2), "r"(a3), "l"(db), "n"(TB));
}
template <int TB> __device__ __forceinline__ void wgmma_rs_n40(float (&d)[20], uint32_t a0, uint32_t a1, uint32_t a2, uint32_t a3, uint64_t db) {
  asm volatile("wgmma.mma_async.sync.aligned.m64n40k16.f32.bf16.bf16 "
  "{%0,%1,%2,%3,%4,%5,%6,%7,%8,%9,%10,%11,%12,%13,%14,%15,%16,%17,%18,%19}, "
  "{%20,%21,%22,%23}, %24, 1, 1, 1, %25;"
  : "+f"(d[0]),"+f"(d[1]),"+f"(d[2]),"+f"(d[3]),"+f"(d[4]),"+f"(d[5]),"+f"(d[6]),"+f"(d[7]),"+f"(d[8]),"+f"(d[9]),"+f"(d[10]),"+f"(d[11]),"+f"(d[12]),"+f"(d[13]),"+f"(d[14]),"+f"(d[15]),"+f"(d[16]),"+f"(d[17]),"+f"(d[18]),"+f"(d[19])
  : "r"(a0), "r"(a1), "r"(a2), "r"(a3), "l"(db), "n"(TB));
}
template <int TB> __device__ __forceinline__ void wgmma_rz_n40(float (&d)[20], uint32_t a0, uint32_t a1, uint32_t a2, uint32_t a3, uint64_t db) {
  asm volatile("wgmma.mma_async.sync.aligned.m64n40k16.f32.bf16.bf16 "
  "{%0,%1,%2,%3,%4,%5,%6,%7,%8,%9,%10,%11,%12,%13,%14,%15,%16,%17,%18,%19}, "
  "{%20,%21,%22,%23}, %24, 0, 1, 1, %25;"
  : "=f"(d[0]),"=f"(d[1]),"=f"(d[2]),"=f"(d[3]),"=f"(d[4]),"=f"(d[5]),"=f"(d[6]),"=f"(d[7]),"=f"(d[8]),"=f"(d[9]),"=f"(d[10]),"=f"(d[11]),"=f"(d[12]),"=f"(d[13]),"=f"(d[14]),"=f"(d[15]),"=f"(d[16]),"=f"(d[17]),"=f"(d[18]),"=f"(d[19])
  : "r"(a0), "r"(a1), "r"(a2), "r"(a3), "l"(db), "n"(TB));
}
template <int TB> __device__ __forceinline__ void wgmma_rs_n128(float (&d)[64], uint32_t a0, uint32_t a1, uint32_t a2, uint32_t a3, uint64_t db) {
  asm volatile("wgmma.mma_async.sync.aligned.m64n128k16.f32.bf16.bf16 "
  "{%0,%1,%2,%3,%4,%5,%6,%7,%8,%9,%10,%11,%12,%13,%14,%15,%16,%17,%18,%19,%20,%21,%22,%23,%24,%25,%26,%27,%28,%29,%30,%31,%32,%33,%34,%35,%36,%37,%38,%39,%40,%41,%42,%43,%44,%45,%46,%47,%48,%49,%50,%51,%52,%53,%54,%55,%56,%57,%58,%59,%60,%61,%62,%63}, "
  "{%64,%65,%66,%67}, %68, 1, 1, 1, %69;"
  : "+f"(d[0]),"+f"(d[1]),"+f"(d[2]),"+f"(d[3]),"+f"(d[4]),"+f"(d[5]),"+f"(d[6]),"+f"(d[7]),"+f"(d[8]),"+f"(d[9]),"+f"(d[10]),"+f"(d[11]),"+f"(d[12]),"+f"(d[13]),"+f"(d[14]),"+f"(d[15]),"+f"(d[16]),"+f"(d[17]),"+f"(d[18]),"+f"(d[19]),"+f"(d[20]),"+f"(d[21]),"+f"(d[22]),"+f"(d[23]),"+f"(d[24]),"+f"(d[25]),"+f"(d[26]),"+f"(d[27]),"+f"(d[28]),"+f"(d[29]),"+f"(d[30]),"+f"(d[31]),"+f"(d[32]),"+f"(d[33]),"+f"(d[34]),"+f"(d[35]),"+f"(d[36]),"+f"(d[37]),"+f"(d[38]),"+f"(d[39]),"+f"(d[40]),"+f"(d[41]),"+f"(d[42]),"+f"(d[43]),"+f"(d[44]),"+f"(d[45]),"+f"(d[46]),"+f"(d[47]),"+f"(d[48]),"+f"(d[49]),"+f"(d[50]),"+f"(d[51]),"+f"(d[52]),"+f"(d[53]),"+f"(d[54]),"+f"(d[55]),"+f"(d[56]),"+f"(d[57]),"+f"(d[58]),"+f"(d[59]),"+f"(d[60]),"+f"(d[61]),"+f"(d[62]),"+f"(d[63])
  : "r"(a0), "r"(a1), "r"(a2), "r"(a3), "l"(db), "n"(TB));
}
template <int TA, int TB> __device__ __forceinline__ void wgmma_ss_n8(float (&d)[4], uint64_t da, uint64_t db) {
  asm volatile("wgmma.mma_async.sync.aligned.m64n8k16.f32.bf16.bf16 "
  "{%0,%1,%2,%3}, "
  "%4, %5, 1, 1, 1, %6, %7;"
  : "+f"(d[0]),"+f"(d[1]),"+f"(d[2]),"+f"(d[3])
  : "l"(da), "l"(db), "n"(TA), "n"(TB));
}
template <int TA, int TB> __device__ __forceinline__ void wgmma_ss_n16(float (&d)[8], uint64_t da, uint64_t db) {
  asm volatile("wgmma.mma_async.sync.aligned.m64n16k16.f32.bf16.bf16 "
  "{%0,%1,%2,%3,%4,%5,%6,%7}, "
  "%8, %9, 1, 1, 1, %10, %11;"
  : "+f"(d[0]),"+f"(d[1]),"+f"(d[2]),"+f"(d[3]),"+f"(d[4]),"+f"(d[5]),"+f"(d[6]),"+f"(d[7])
  : "l"(da), "l"(db), "n"(TA), "n"(TB));
}

constexpr int SEQ = 2048, DM = 1024, FF = 3584;
constexpr int NCTA = 128, NSVC = 4;
constexpr int NUNIT = 112;
constexpr uint32_t SLOT = 16384;
constexpr uint32_t MISC = 14 * SLOT;
constexpr uint32_t SMEM_BYTES = MISC + 3072;
constexpr uint32_t M_MOE = 0;
constexpr uint32_t M_BAR = 2048;
constexpr uint32_t M_DUM = 2048 + 1020;
constexpr uint32_t M_IDX = 2048 + 768;
constexpr uint32_t M_KEY = 2048 + 960;
#define R5 1
#define NQ (R5 ? 6 : 5)
constexpr int NF = 16 - NQ, NR = (NQ == 5 || R5) ? 4 : 3;
constexpr int B_FXQ = 0, B_FKV = 3, B_AST = 6, B_MOE = 7, B_MF = 8  , B_CQ = 12, B_XS = 13, B_DF = 14, B_ZOK = 15, B_FWO = 21  , B_FQ = B_FWO - NQ,
              B_UP = 37, B_FIN = 38, B_KVB = 39, B_ME = 40  , B_HF = 44, B_AF = 45  , B_AR = 50  , B_GO = 52,
              B_FAUX = 53, B_EAUX = 54, B_T0 = 55, B_DE = 56, B_EA = 57  , B_VAL = 62  ,
              B_E = 67  , B_STG = 70, B_EQ = 71  , B_EO = 76  , NBAR = 83, B_KV4 = 83, B_MS = 84,
              B_FV = 85  , B_EK = 88  , B_GQ = 91, B_GT = 92;
constexpr uint32_t MT = 9216, A_ONES = 12 * SLOT + 3 * MT, A_CS = A_ONES + 2048, A_ST = A_CS + 1536;
constexpr uint32_t A_TL = MISC + 2048 + 808;
constexpr int S_V0 = R5 ? 7 : 11, S_V1 = R5 ? 9 : 7;
constexpr uint32_t K_SLOTS = 0x8697A8u, V_SLOTS = 0x97A869u;
constexpr int C_B = 0, C_DONE = 32, NCNT = 2;
constexpr uint32_t QX_SLOTS = NQ == 5 ? 0x43102u : 0x354021u;
constexpr uint32_t QW_SLOTS = R5 ? 0xA9786Au : 0xB76A98u;
constexpr uint32_t qx(int k) { return (QX_SLOTS >> (4 * k)) & 15u; }
constexpr uint32_t qw(int k) { return (QW_SLOTS >> (4 * k)) & 15u; }
constexpr uint32_t S_KVB = R5 ? 1 : 8, S_D0 = R5 ? 11 : (NQ == 5 ? 5 : 1), S_D1 = R5 ? 2 : (NQ == 5 ? 11 : 2);
constexpr uint32_t S_M3 = R5 ? 11 : 5;
constexpr int WQ0 = NQ == 5 ? 1 : 3;
constexpr uint32_t wo_slot_c(int i) { return i >= 9 ? wo_slot_c(i - 9) : (i == 7 ? S_D0 : (i == 8 ? S_D1 : (((i & 1) || i + WQ0 == 1) ? qx((i + WQ0) >> 1) : qw((i + WQ0) >> 1)))); }
constexpr uint64_t wo_slots() { uint64_t t = 0; for (int i = 0; i < 16; i++) t |= (uint64_t)wo_slot_c(i) << (4 * i); return t; }
constexpr uint64_t WO_SLOTS = wo_slots();
constexpr uint32_t A_SLOTS = 0xDC000u | (S_KVB << 8) | (qw(NQ - 1) << 4) | qx(NQ - 1);
constexpr uint32_t SX14 = qx(NQ - 2), SX15 = qx(NQ - 1), SXQ0 = qx(0);
#define WOD 2
#define PLC 3
#define RS0 0
#define POLLNS 150
#define MPROMO CU_TENSOR_MAP_L2_PROMOTION_L2_128B
#define MW0 0
#define PFILL 0
#define H2W (NQ - 3)
#define SV0 2
#define SV0A 14
#define SV0B 22
#define ASTE 2
#define PFS 1
#define PFTAB 0x0012222220000ull
#define HW 0
#define DPF 1
#define PROBE 0x8
#define OS1 0
#define YW 0
#define NOVAL 0
#define NDIR 1
#define I0 (2 + NDIR)
#define DW 0
#define NA 5
#define STAG 4
#define GOE 0
#define KEY1 0
#define HYB 0
#define FW 0
#define E1E 1
#define GATE 0
#define SVD 0
#define XPROMO CU_TENSOR_MAP_L2_PROMOTION_L2_128B
#define MC0 3
#define MX 0
#define OUTV 1
#define NP 0
#define FINCP 0
#define DNS 0
#define WOK 99
#define WOD1 2
#define MRED 1
#define MRW -1
#define ST 0
#define RW 0
#define SL2 0
#define CQ4 0
#define CQE 0
#define VOL 0
#define FMC 0
#define KO 0
#define GPF 0
#define GPD 0
#define OH 0
#define R4E 0
#define WOP 3
#define WSP 0
#define SH2 0
#define KS 7
#define SQ 2
#define H2D 200
#define MRC 0
#define H2C 0
#define MRD 300
#define STP 0
#define TPNS 50
#define MFIN 0
#define MFD 300
#define SF 1
#define PH MFIN
#define RSL 0
#define OS3 4
#define PLP 2
#define PFNS2 200
#define MAP 2
#define RSNS 60
#define SVS 6
#define MC 7
#define QE 0
#define TMP 1
#define TMPW 4
#define DS 15
#define RL 0
#define EV 0
#define LQ 0
#define SPL 0
#define PHI2 1
#define E7 1
#define RF 1
#define RK 0
#define LE 1
#define SL7 0
#define XP 3
#define MS 0
constexpr int CON_REGS = 224, MOE_REGS = 40, PROD_REGS = 24;
constexpr uint32_t SPIN_MAX = 2000000;
constexpr uint32_t SENT = 0xFFFFFFFFu;

struct __align__(128) Scratch {
  uint4 o[NCTA * 2048];
  uint4 part[NCTA * 544];
  uint4 fin[8 * 640];
  float2 stats[SEQ];
  uint32_t key[SEQ];
  uint32_t cs[3 * DM];
  uint4 y[NCTA * 128];
  uint32_t h[56 * 256];
  uint32_t top[128];
  uint32_t cnt[NCNT * 32];
};
__device__ Scratch G;
#define TLS(th, i)
#define TLP_(i)
#define TLG(i)
#define TLDUMP()

__device__ __forceinline__ bool elect_one() {
  uint32_t p;
  asm volatile("{\n.reg .pred P;\nelect.sync _|P, 0xffffffff;\nselp.b32 %0, 1, 0, P;\n}" : "=r"(p));
  return p;
}
__device__ __forceinline__ void mbar_init(uint32_t b, uint32_t c) { asm volatile("mbarrier.init.shared::cta.b64 [%0], %1;" ::"r"(b), "r"(c) : "memory"); }
__device__ __forceinline__ void mbar_expect_tx(uint32_t b, uint32_t bytes) { asm volatile("mbarrier.arrive.expect_tx.shared::cta.b64 _, [%0], %1;" ::"r"(b), "r"(bytes) : "memory"); }
__device__ __forceinline__ void mbar_arrive(uint32_t b) { asm volatile("mbarrier.arrive.shared::cta.b64 _, [%0];" ::"r"(b) : "memory"); }
__device__ __forceinline__ void mbar_wait_b(uint32_t b, uint32_t parity) {
  asm volatile(
      "{\n.reg .pred p;\n.reg .u32 cnt;\nmov.u32 cnt, 0;\n"
      "LW:\nmbarrier.try_wait.parity.shared::cta.b64 p, [%0], %1;\n@p bra LD;\n"
      "add.u32 cnt, cnt, 1;\nsetp.lt.u32 p, cnt, 4000000;\n@p bra LW;\ntrap;\nLD:\n}" ::"r"(b), "r"(parity) : "memory");
}
__device__ __forceinline__ void mbar_wait(uint32_t b, uint32_t parity) {
  asm volatile("{\n.reg .pred p;\nLW:\nmbarrier.try_wait.parity.shared::cta.b64 p, [%0], %1;\n@!p bra LW;\n}" ::"r"(b), "r"(parity) : "memory");
}
__device__ __forceinline__ bool mbar_test(uint32_t b, uint32_t parity) {
  uint32_t r;
  asm volatile("{\n.reg .pred p;\nmbarrier.test_wait.parity.shared::cta.b64 p, [%1], %2;\nselp.b32 %0, 1, 0, p;\n}" : "=r"(r) : "r"(b), "r"(parity) : "memory");
  return r;
}
__device__ __forceinline__ uint32_t ev_arrive(uint32_t a) { uint32_t r; asm volatile("atom.shared.add.u32 %0, [%1], 1;" : "=r"(r) : "r"(a) : "memory"); return r; }
__device__ __forceinline__ void tma2d(uint32_t dst, const CUtensorMap* m, int c0, int c1, uint32_t bar) {
  asm volatile("cp.async.bulk.tensor.2d.shared::cluster.global.mbarrier::complete_tx::bytes [%0], [%1, {%3, %4}], [%2];" ::"r"(dst), "l"(m), "r"(bar), "r"(c0), "r"(c1) : "memory");
}
__device__ __forceinline__ void tma3d(uint32_t dst, const CUtensorMap* m, int c1, int c2, uint32_t bar) {
  asm volatile("cp.async.bulk.tensor.3d.shared::cluster.global.mbarrier::complete_tx::bytes [%0], [%1, {%3, %4, %5}], [%2];" ::"r"(dst), "l"(m), "r"(bar), "r"(0), "r"(c1), "r"(c2) : "memory");
}
__device__ __forceinline__ void tma3d_mc(uint32_t dst, const CUtensorMap* m, int c1, int c2, uint32_t bar) {
  asm volatile("cp.async.bulk.tensor.3d.shared::cluster.global.mbarrier::complete_tx::bytes.multicast::cluster [%0], [%1, {%3, %4, %5}], [%2], %6;" ::"r"(dst), "l"(m), "r"(bar), "r"(0), "r"(c1), "r"(c2), "h"((uint16_t)3) : "memory");
}
__device__ __forceinline__ void tma5d(uint32_t dst, const CUtensorMap* m, int c2, int c4, uint32_t bar, bool mc) {
  if (mc) asm volatile("cp.async.bulk.tensor.5d.shared::cluster.global.mbarrier::complete_tx::bytes.multicast::cluster [%0], [%1, {%3, %3, %4, %3, %5}], [%2], %6;" ::"r"(dst), "l"(m), "r"(bar), "r"(0), "r"(c2), "r"(c4), "h"((uint16_t)3) : "memory");
  else asm volatile("cp.async.bulk.tensor.5d.shared::cluster.global.mbarrier::complete_tx::bytes [%0], [%1, {%3, %3, %4, %3, %5}], [%2];" ::"r"(dst), "l"(m), "r"(bar), "r"(0), "r"(c2), "r"(c4) : "memory");
}
__device__ __forceinline__ void mbar_arrive_cta(uint32_t b, uint32_t cta) {
  asm volatile("{\n.reg .b32 ra;\nmapa.shared::cluster.u32 ra, %0, %1;\nmbarrier.arrive.shared::cluster.b64 _, [ra];\n}" ::"r"(b), "r"(cta) : "memory");
}
constexpr uint64_t POL_FIRST = 0x12F0000000000000ull;
__device__ __forceinline__ void tma2d_ef(uint32_t dst, const CUtensorMap* m, int c0, int c1, uint32_t bar) {
  asm volatile("cp.async.bulk.tensor.2d.shared::cluster.global.mbarrier::complete_tx::bytes.L2::cache_hint [%0], [%1, {%3, %4}], [%2], %5;" ::"r"(dst), "l"(m), "r"(bar), "r"(c0), "r"(c1), "l"(POL_FIRST) : "memory");
}
__device__ __forceinline__ void bulk_ld(uint32_t dst, const void* src, uint32_t bytes, uint32_t bar) {
  asm volatile("cp.async.bulk.shared::cluster.global.mbarrier::complete_tx::bytes [%0], [%1], %2, [%3];" ::"r"(dst), "l"(src), "r"(bytes), "r"(bar) : "memory");
}
__device__ __forceinline__ void bulk_ld_mc(uint32_t dst, const void* src, uint32_t bytes, uint32_t bar) {
  asm volatile("cp.async.bulk.shared::cluster.global.mbarrier::complete_tx::bytes.multicast::cluster [%0], [%1], %2, [%3], %4;" ::"r"(dst), "l"(src), "r"(bytes), "r"(bar), "h"((uint16_t)3) : "memory");
}
__device__ __forceinline__ void bulk_pf(const void* src, uint32_t bytes) { asm volatile("cp.async.bulk.prefetch.L2.global [%0], %1;" ::"l"(src), "r"(bytes) : "memory"); }
__device__ __forceinline__ void tma2d_pf(const CUtensorMap* m, int c0, int c1) {
  asm volatile("cp.async.bulk.prefetch.tensor.2d.L2.global [%0, {%1, %2}];" ::"l"(m), "r"(c0), "r"(c1) : "memory");
}
__device__ __forceinline__ void map_pf(const CUtensorMap* m) { asm volatile("prefetch.tensormap [%0];" ::"l"(m) : "memory"); }
__device__ __forceinline__ void line_pf(const void* p) { asm volatile("prefetch.global.L2 [%0];" ::"l"(p)); }
__device__ __forceinline__ void pf128(uint32_t dummy, const void* src) { asm volatile("cp.async.ca.shared.global.L2::128B [%0], [%1], 4;" ::"r"(dummy), "l"(src) : "memory"); }
__device__ __forceinline__ void pf256(uint32_t dummy, const void* src) { asm volatile("cp.async.ca.shared.global.L2::256B [%0], [%1], 4;" ::"r"(dummy), "l"(src) : "memory"); }
__device__ __forceinline__ void cp16x2(uint32_t dst, const void* src) {
  asm volatile("cp.async.cg.shared.global [%0], [%1], 16;\ncp.async.cg.shared.global [%0+4096], [%1+512], 16;" ::"r"(dst), "l"(src) : "memory");
}
constexpr uint32_t HI_SW128 = 0x40000000u | (1024 >> 4), HI_SW64 = 0x80000000u | (512 >> 4), HI_NOSW = 512 >> 4;
__device__ __forceinline__ uint64_t mkdesc(uint32_t lo, uint32_t hi) { uint64_t d; asm("mov.b64 %0, {%1, %2};" : "=l"(d) : "r"(lo), "r"(hi)); return d; }
__device__ __forceinline__ void wg_fence() { asm volatile("wgmma.fence.sync.aligned;" ::: "memory"); }
__device__ __forceinline__ void wg_commit() { asm volatile("wgmma.commit_group.sync.aligned;" ::: "memory"); }
template <int N> __device__ __forceinline__ void wg_wait() { asm volatile("wgmma.wait_group.sync.aligned %0;" ::"n"(N) : "memory"); }
template <int N> __device__ __forceinline__ void reg_fence(float (&a)[N]) {
#pragma unroll
  for (int i = 0; i < N; i++) asm volatile("" : "+f"(a[i])::"memory");
}
template <int ID, int N> __device__ __forceinline__ void bar_sync() { asm volatile("bar.sync %0, %1;" ::"n"(ID), "n"(N) : "memory"); }
__device__ __forceinline__ void fence_async_smem() { asm volatile("fence.proxy.async.shared::cta;" ::: "memory"); }
__device__ __forceinline__ void fence_async_gmem() { asm volatile("fence.proxy.async.global;" ::: "memory"); }
__device__ __forceinline__ uint32_t pack_bf16(float lo, float hi) { uint32_t r; asm("cvt.rn.bf16x2.f32 %0, %1, %2;" : "=r"(r) : "f"(hi), "f"(lo)); return r; }
__device__ __forceinline__ float bf_lo(uint32_t v) { return __uint_as_float(v << 16); }
__device__ __forceinline__ float bf_hi(uint32_t v) { return __uint_as_float(v & 0xFFFF0000u); }
__device__ __forceinline__ float bf_round(float v) { return bf_lo(pack_bf16(v, v)); }
__device__ __forceinline__ uint32_t bf_sub2(uint32_t a, uint32_t b) { uint32_t r; asm("sub.rn.bf16x2 %0, %1, %2;" : "=r"(r) : "r"(a), "r"(b)); return r; }
__device__ __forceinline__ float rcp(float v) { float r; asm("rcp.approx.ftz.f32 %0, %1;" : "=f"(r) : "f"(v)); return r; }
__device__ __forceinline__ float ex2(float v) { float r; asm("ex2.approx.ftz.f32 %0, %1;" : "=f"(r) : "f"(v)); return r; }
__device__ __forceinline__ float sigmoid(float v) { return rcp(1.f + ex2(v * -1.4426950408889634f)); }
__device__ __forceinline__ void stsm4(uint32_t a, uint32_t r0, uint32_t r1, uint32_t r2, uint32_t r3) {
  asm volatile("stmatrix.sync.aligned.m8n8.x4.shared.b16 [%0], {%1,%2,%3,%4};" ::"r"(a), "r"(r0), "r"(r1), "r"(r2), "r"(r3) : "memory");
}
__device__ __forceinline__ void stsm4t(uint32_t a, uint32_t r0, uint32_t r1, uint32_t r2, uint32_t r3) {
  asm volatile("stmatrix.sync.aligned.m8n8.x4.trans.shared.b16 [%0], {%1,%2,%3,%4};" ::"r"(a), "r"(r0), "r"(r1), "r"(r2), "r"(r3) : "memory");
}
__device__ __forceinline__ void ldsm4(uint32_t a, uint32_t& r0, uint32_t& r1, uint32_t& r2, uint32_t& r3) {
  asm volatile("ldmatrix.sync.aligned.m8n8.x4.shared.b16 {%0,%1,%2,%3}, [%4];" : "=r"(r0), "=r"(r1), "=r"(r2), "=r"(r3) : "r"(a) : "memory");
}
__device__ __forceinline__ uint32_t movmat(uint32_t a) { uint32_t d; asm volatile("movmatrix.sync.aligned.m8n8.trans.b16 %0, %1;" : "=r"(d) : "r"(a)); return d; }
__device__ __forceinline__ void sts_h(uint32_t a, float v) { asm volatile("st.shared.u16 [%0], %1;" ::"r"(a), "h"((uint16_t)pack_bf16(v, v)) : "memory"); }
__device__ __forceinline__ float2 lds_f2(uint32_t a) { float2 v; asm volatile("ld.shared.v2.f32 {%0,%1}, [%2];" : "=f"(v.x), "=f"(v.y) : "r"(a)); return v; }
__device__ __forceinline__ float lds_f(uint32_t a) { float v; asm volatile("ld.shared.f32 %0, [%1];" : "=f"(v) : "r"(a)); return v; }
__device__ __forceinline__ float4 lds_f4(uint32_t a) { float4 v; asm volatile("ld.shared.v4.f32 {%0,%1,%2,%3}, [%4];" : "=f"(v.x), "=f"(v.y), "=f"(v.z), "=f"(v.w) : "r"(a)); return v; }
__device__ __forceinline__ uint32_t lds_u(uint32_t a) { uint32_t v; asm volatile("ld.shared.u32 %0, [%1];" : "=r"(v) : "r"(a) : "memory"); return v; }
__device__ __forceinline__ uint4 lds_u4(uint32_t a) { uint4 v; asm volatile("ld.shared.v4.u32 {%0,%1,%2,%3}, [%4];" : "=r"(v.x), "=r"(v.y), "=r"(v.z), "=r"(v.w) : "r"(a) : "memory"); return v; }
__device__ __forceinline__ void sts_u(uint32_t a, uint32_t v) { asm volatile("st.shared.u32 [%0], %1;" ::"r"(a), "r"(v) : "memory"); }
__device__ __forceinline__ void sts_u4(uint32_t a, uint4 v) { asm volatile("st.shared.v4.u32 [%0], {%1,%2,%3,%4};" ::"r"(a), "r"(v.x), "r"(v.y), "r"(v.z), "r"(v.w) : "memory"); }
__device__ __forceinline__ uint4 ldx4(const void* p) { uint4 v; asm volatile("ld.relaxed.gpu.global.v4.u32 {%0,%1,%2,%3}, [%4];" : "=r"(v.x), "=r"(v.y), "=r"(v.z), "=r"(v.w) : "l"(p) : "memory"); return v; }
__device__ __forceinline__ uint2 ldx2(const void* p) { uint2 v; asm volatile("ld.relaxed.gpu.global.v2.u32 {%0,%1}, [%2];" : "=r"(v.x), "=r"(v.y) : "l"(p) : "memory"); return v; }
__device__ __forceinline__ uint32_t ldx1(const void* p) { uint32_t v; asm volatile("ld.relaxed.gpu.global.u32 %0, [%1];" : "=r"(v) : "l"(p) : "memory"); return v; }
__device__ __forceinline__ void stx4(void* p, uint32_t a, uint32_t b, uint32_t c, uint32_t d) {
  asm volatile("st.relaxed.gpu.global.v4.u32 [%0], {%1,%2,%3,%4};" ::"l"(p), "r"(a), "r"(b), "r"(c), "r"(d) : "memory");
}
__device__ __forceinline__ void stx2(void* p, uint32_t a, uint32_t b) { asm volatile("st.relaxed.gpu.global.v2.u32 [%0], {%1,%2};" ::"l"(p), "r"(a), "r"(b) : "memory"); }
__device__ __forceinline__ void stx1(void* p, uint32_t a) { asm volatile("st.relaxed.gpu.global.u32 [%0], %1;" ::"l"(p), "r"(a) : "memory"); }
__device__ __forceinline__ uint32_t umax4(uint4 v) { return max(max(v.x, v.y), max(v.z, v.w)); }
__device__ __forceinline__ uint32_t f2x(float f) { return min(__float_as_uint(f), 0xFFFFFFFEu); }
__device__ __forceinline__ void red4(float* p, float a, float b, float c, float d) { asm volatile("red.relaxed.gpu.global.add.v4.f32 [%0], {%1,%2,%3,%4};" ::"l"(p), "f"(a), "f"(b), "f"(c), "f"(d) : "memory"); }
__device__ __forceinline__ void cnt_arrive(int c) { asm volatile("red.release.gpu.global.add.u32 [%0], 1;" ::"l"(&G.cnt[c]) : "memory"); }
__device__ __forceinline__ void cnt_wait(int c, uint32_t target) {
#pragma unroll 1
  for (uint32_t it = 0; it < SPIN_MAX; it++) {
    uint32_t v;
    asm volatile("ld.acquire.gpu.global.u32 %0, [%1];" : "=r"(v) : "l"(&G.cnt[c]) : "memory");
    if (v >= target) break;
    __nanosleep(POLLNS);
  }
}
__device__ __forceinline__ void spin_cycles(uint32_t n) {
  uint32_t t0, t1;
  asm volatile("mov.u32 %0, %%clock;" : "=r"(t0));
#pragma unroll 1
  do { __nanosleep(20); asm volatile("mov.u32 %0, %%clock;" : "=r"(t1)); } while (t1 - t0 < n);
}
__device__ __forceinline__ void cnt_done() {
  uint32_t t;
  asm volatile("atom.acq_rel.gpu.global.add.u32 %0, [%1], 1;" : "=r"(t) : "l"(&G.cnt[C_DONE]) : "memory");
  if (t == NCTA + NSVC - 1) {
#pragma unroll 1
    for (int i = 0; i < NCNT; i++) G.cnt[i * 32] = 0;
  }
}
__device__ __forceinline__ float phi(float u, float rs, float rl) {
  float a = fmaf(u, rs, 1.000001f), e = ex2(u * rl), r;
  asm("add.sat.f32 %0, %1, 0f358637BD;" : "=f"(e) : "f"(e));
  asm("max.NaN.f32 %0, %1, %2;" : "=f"(r) : "f"(a), "f"(e));
  return r;
}

constexpr float LOG2E = 1.4426950408889634f, LN2 = 0.6931471805599453f;
__device__ __forceinline__ uint32_t phi2l(float u0, float rl0, float u1, float rl1) {
  const float l0 = u0 * rl0, l1 = u1 * rl1;
  float e0, e1;
  asm("{\n.reg .f32 t;\nabs.f32 t, %1;\nneg.f32 t, t;\nex2.approx.ftz.f32 %0, t;\n}" : "=f"(e0) : "f"(l0));
  asm("{\n.reg .f32 t;\nabs.f32 t, %1;\nneg.f32 t, t;\nex2.approx.ftz.f32 %0, t;\n}" : "=f"(e1) : "f"(l1));
  uint32_t e = pack_bf16(e0, e1), r;
  const uint32_t a = pack_bf16(fmaf(l0, LN2, 1.000001f), fmaf(l1, LN2, 1.000001f));
  asm("add.rn.bf16x2 %0, %0, %1;" : "+r"(e) : "r"(0x35863586u));
  asm("max.NaN.bf16x2 %0, %1, %2;" : "=r"(r) : "r"(a), "r"(e));
  return r;
}
template <bool V = false>
__device__ __forceinline__ uint32_t phi2(float u0, float rs0, float rl0, float u1, float rs1, float rl1) {
  float e0, e1;
  if (V) {
    asm volatile("{\n.reg .f32 t;\nabs.f32 t, %1;\nneg.f32 t, t;\nex2.approx.ftz.f32 %0, t;\n}" : "=f"(e0) : "f"(u0 * rl0));
    asm volatile("{\n.reg .f32 t;\nabs.f32 t, %1;\nneg.f32 t, t;\nex2.approx.ftz.f32 %0, t;\n}" : "=f"(e1) : "f"(u1 * rl1));
  } else {
    asm("{\n.reg .f32 t;\nabs.f32 t, %1;\nneg.f32 t, t;\nex2.approx.ftz.f32 %0, t;\n}" : "=f"(e0) : "f"(u0 * rl0));
    asm("{\n.reg .f32 t;\nabs.f32 t, %1;\nneg.f32 t, t;\nex2.approx.ftz.f32 %0, t;\n}" : "=f"(e1) : "f"(u1 * rl1));
  }
  uint32_t e = pack_bf16(e0, e1), r;
  const uint32_t a = pack_bf16(fmaf(u0, rs0, 1.000001f), fmaf(u1, rs1, 1.000001f));
  asm("add.rn.bf16x2 %0, %0, %1;" : "+r"(e) : "r"(0x35863586u));
  asm("max.NaN.bf16x2 %0, %1, %2;" : "=r"(r) : "r"(a), "r"(e));
  return r;
}

__device__ __forceinline__ int kstep1(int e, int hg) { return e < 14 ? (e < 2 * hg ? e : e + 2) : 2 * hg + e - 14; }
__device__ __forceinline__ int slab(int n, int hg) {
  return n + (((n + 7 - hg) * 37) >> 8);
}
__host__ __device__ constexpr uint32_t d_off(int i) { return i < 3 ? 12 * SLOT + (NR == 4 ? i : (i == 2 ? 0 : i + 1)) * MT : (i < 5 ? S_D0 * SLOT + (i - 3) * 8192 : S_D1 * SLOT + (i - 5) * 8192); }
__host__ __device__ constexpr uint32_t h_off(int i) { return i < 3 ? 12 * SLOT + i * MT + 8192 : (i < 5 ? A_ONES + (i - 3) * 1024 : MISC + M_MOE + (i - 5) * 1024); }
__device__ __forceinline__ uint32_t m_off(int r) { return r < 3 ? 12 * SLOT + r * MT : S_M3 * SLOT; }
__device__ __forceinline__ int x_slot(int e, int s) { return NQ == 5 ? (e < 14 ? s : e - 11) : (e < 13 ? s : 3 + s); }
__device__ __forceinline__ uint32_t wo_slot(int i) { return (uint32_t)(WO_SLOTS >> (4 * i)) & 15u; }

__global__ void __launch_bounds__(512, 1)
fused_kernel(const __nv_bfloat16* __restrict__ x, const __nv_bfloat16* __restrict__ wqkv, const __nv_bfloat16* __restrict__ wo,
             const __nv_bfloat16* __restrict__ wr, const __nv_bfloat16* __restrict__ wd, __nv_bfloat16* __restrict__ outp,
             const __nv_bfloat16* __restrict__ wg, const __nv_bfloat16* __restrict__ wu, const int by_sm,
             const __grid_constant__ CUtensorMap tmX, const __grid_constant__ CUtensorMap tmW,
             const __grid_constant__ CUtensorMap tmWo, const __grid_constant__ CUtensorMap tmOut,
             const __grid_constant__ CUtensorMap tmG, const __grid_constant__ CUtensorMap tmU,
             const __grid_constant__ CUtensorMap tmD, const __grid_constant__ CUtensorMap tmR,
             const __grid_constant__ CUtensorMap tmWp) {
  if (TMP && threadIdx.x == 32 * TMPW) { map_pf(&tmX); map_pf(&tmW); }
  extern __shared__ __align__(1024) uint8_t smem_raw[];
  const uint32_t sb = (uint32_t)__cvta_generic_to_shared(smem_raw);
  const uint32_t bars = sb + MISC + M_BAR;
  uint32_t smid;
  asm("mov.u32 %0, %%smid;" : "=r"(smid));
  const int tpc = smid >> 1;
  int cl = tpc + max(((tpc - 25) * 37) >> 8, 0);
  cl = tpc < 60 ? cl : cl - 1;
  cl = tpc < 62 ? cl : (tpc - 58) * 8;
  const int u = by_sm ? 2 * cl + (blockIdx.x & 1) : blockIdx.x;
  const int hg = (u >> 4) & 7, tb = u & 15;
  const int b = tb * 8 + hg;
  const int lane = threadIdx.x & 31;
  const int warp = __shfl_sync(~0u, threadIdx.x >> 5, 0);
  const int ltid = threadIdx.x;
  const int g = lane >> 2, t = lane & 3;
  const uint32_t d0 = (sb & 0x3FFFF) >> 4;
#define BAR(i) (bars + 8 * (i))
  TLS(0, 0);

  const int rank = u & 1;
  auto load_entry = [&](int e, int s) {
    const int k0 = kstep1(e, hg) * 64;
    mbar_expect_tx(BAR(B_FXQ + s), e < NF ? 2 * SLOT : SLOT);
    mbar_expect_tx(BAR(B_FKV + s), R5 ? SLOT : 2 * SLOT);
    if (R5 && e < 11) mbar_expect_tx(BAR(B_FV + s), SLOT);
    const uint32_t vb = R5 ? BAR(B_FV + s) : BAR(B_FKV + s);
    tma2d(sb + x_slot(e, s) * SLOT, &tmX, k0, tb * 128, BAR(B_FXQ + s));
    if (e < MC0 || !(MC & 1)) {
      if (e < NF) tma3d(sb + (3 + s) * SLOT, &tmW, k0, 2 * hg, BAR(B_FXQ + s));
      tma3d(sb + (6 + 2 * s) * SLOT, &tmW, k0, 16 + 2 * hg, BAR(B_FKV + s));
      tma3d(sb + (7 + 2 * s) * SLOT, &tmW, k0, 32 + 2 * hg, vb);
    } else {
      if (e < NF && (e & 1) == rank) tma3d_mc(sb + (3 + s) * SLOT, &tmW, k0, 2 * hg, BAR(B_FXQ + s));
      if (R5 && e >= 11) { if (rank == 0) tma3d_mc(sb + ((K_SLOTS >> (4 * (e - 10))) & 15u) * SLOT, &tmW, k0, 16 + 2 * hg, BAR(B_FKV + s)); }
      else tma3d_mc(sb + (6 + 2 * s + rank) * SLOT, &tmW, k0, 16 + 16 * rank + 2 * hg, rank ? vb : BAR(B_FKV + s));
    }
  };
  if (warp == FW && u < NCTA) {
    if (elect_one()) {
      mbar_init(BAR(B_FXQ), 1); mbar_init(BAR(B_FKV), 1);
      if (R5) mbar_init(BAR(B_FV), 1);
      load_entry(0, 0);
      asm volatile("fence.mbarrier_init.release.cluster;" ::: "memory");
      TLS(FW * 32, 61);
    }
    __syncwarp();
  }
  if (u >= NCTA) {
    const int j = u - NCTA;
    if (warp == 8 && elect_one()) {
#pragma unroll
      for (int i = 0; i < 13; i++) mbar_init(BAR(i), 1);
    }
    if (ltid < 64) sts_u4(sb + MISC + ltid * 16, make_uint4(0x3F803F80u, 0x3F803F80u, 0x3F803F80u, 0x3F803F80u));
    fence_async_smem();
    __syncthreads();
    if (warp < 4) {
      int s = 0, p = 0;
#pragma unroll 1
      for (int pass = 0; pass < 3; pass++) {
        float acc[4][4];
#pragma unroll
        for (int c = 0; c < 4; c++) acc[c][0] = acc[c][1] = acc[c][2] = acc[c][3] = 0.f;
#pragma unroll 1
        for (int k = 0; k < 16; k++) {
          mbar_wait(BAR(s), p);
          wg_fence();
#pragma unroll
          for (int c = 0; c < 4; c++)
#pragma unroll
            for (int kk = 0; kk < 4; kk++)
              wgmma_ss_n8<1, 0>(acc[c], mkdesc((d0 + s * 2048 + c * 512 + kk * 128) | (512u << 16), HI_SW128), mkdesc((d0 + (MISC >> 4)) | (1u << 16), HI_SW128));
          wg_commit();
          wg_wait<0>();
          if (ltid == 0) mbar_arrive(BAR(6 + s));
          if (++s == SVS) { s = 0; p ^= 1; }
        }
        uint32_t* pc = G.cs + (pass < 2 ? DM + pass * DM : 0) + j * 256 + warp * 16 + g;
#pragma unroll
        for (int c = 0; c < 4; c++) {
          reg_fence(acc[c]);
          const uint32_t v = __float_as_uint((t & 1) ? acc[c][2] : acc[c][0]);
          if (t < 2) stx1(pc + c * 64 + t * 8, v ? v : 0x80000000u);
        }
        TLS(0, 1 + pass);
      }
    } else if (warp >= 8 && j == 0) {
      const int wq = warp - 8;
      const uint32_t top = sb + MISC + 1024;
#pragma unroll 1
      for (uint32_t it = 0; it < SPIN_MAX; it++) {
        const uint4 v0 = ldx4(G.key + wq * 256 + lane * 4), v1 = ldx4(G.key + wq * 256 + 128 + lane * 4);
        uint32_t ok;
        asm volatile("{\n.reg .pred p, q;\nsetp.ne.u32 p, %1, 0;\nbar.red.and.pred q, 2, 256, p;\nselp.b32 %0, 1, 0, q;\n}" : "=r"(ok) : "r"((v0.x & v0.y & v0.z & v0.w & v1.x & v1.y & v1.z & v1.w) >> 27) : "memory");
        ok = __any_sync(~0u, ok);
        if (!ok && it) continue;
        TLS(256, 4);
        uint32_t np = 0u - (1u << 28), mine = 0;
#pragma unroll 1
        for (int r = 0; r < 8; r++) {
          const uint32_t m0 = __viaddmax_u32(v0.x, np, v0.y + np), m1 = __viaddmax_u32(v0.z, np, v0.w + np), m2 = __viaddmax_u32(v1.x, np, v1.y + np), m3 = __viaddmax_u32(v1.z, np, v1.w + np);
          np -= __reduce_max_sync(~0u, max(max(m0, m1), max(m2, m3)));
          if (g == r) mine = 0u - np;
        }
        if (t == 0) sts_u(top + (wq * 8 + g) * 4, mine);
        bar_sync<2, 256>();
        TLS(256, 5);
        int rk = 0;
#pragma unroll
        for (int i = 0; i < 4; i++) {
          const uint4 o = lds_u4(top + t * 64 + i * 16);
          rk += (o.x > mine) + (o.y > mine) + (o.z > mine) + (o.w > mine);
        }
        rk += __shfl_xor_sync(~0u, rk, 1);
        rk += __shfl_xor_sync(~0u, rk, 2);
        if (ok) { if (rk < 8) stx1(G.top + t * 32 + rk, mine); break; }
        __nanosleep(2500);
      }
      TLS(256, 7);
    } else if (warp == 4) {
      int s = 0, p = 1;
      if (SVD) __nanosleep(SVD);
#pragma unroll 1
      for (int i = 0; i < 48; i++) {
        mbar_wait(BAR(6 + s), p);
        if (j == 0 && i >= SV0A && i < SV0B) mbar_wait(BAR(s >= SV0 ? s - SV0 : s - SV0 + SVS), s >= SV0 ? p ^ 1 : p);
        if (elect_one()) {
          mbar_expect_tx(BAR(s), 2 * SLOT);
          const int ch = (i < 32 ? 16 + (i & 16) : 0) + j * 4, k0 = (i & 15) * 64;
          tma3d(sb + s * 2 * SLOT, &tmW, k0, ch, BAR(s));
          tma3d(sb + s * 2 * SLOT + SLOT, &tmW, k0, ch + 2, BAR(s));
        }
        if (++s == SVS) { s = 0; p ^= 1; }
      }
    }
    if (ltid == 0) cnt_wait(C_DONE, NCTA);
    __syncthreads();
    const uint4 zero = make_uint4(0, 0, 0, 0);
    if (ltid < 128) reinterpret_cast<uint4*>(G.key)[j * 128 + ltid] = zero;
    else if (ltid < 320) reinterpret_cast<uint4*>(G.cs)[j * 192 + ltid - 128] = zero;
    else if (ltid < 322) reinterpret_cast<uint4*>(G.top)[j * 8 + ltid - 320] = zero;
    if (ltid == 0) { cnt_done(); TLDUMP(); }
    return;
  }

  if (warp == 12) {
    if (elect_one()) {
#pragma unroll
      for (int i = 1; i < 7; i++) if (i != B_FKV) mbar_init(BAR(i), 1);
      if (R5) { mbar_init(BAR(B_FV + 1), 1); mbar_init(BAR(B_FV + 2), 1); }
      if (E1E) load_entry(1, 1);
      if (E1E == 2) {
        load_entry(2, 2);
        mbar_expect_tx(BAR(B_AST), 2 * SLOT + 2048);
        bulk_ld(sb + 12 * SLOT, x + (size_t)b * 16 * DM, 2 * SLOT, BAR(B_AST));
        bulk_ld(sb + MISC + M_MOE, wr, 2048, BAR(B_AST));
      }
      asm volatile("fence.mbarrier_init.release.cluster;" ::: "memory");
    }
  } else if (warp >= 13) {
    if (elect_one()) {
      if (warp == 15) {
#pragma unroll
        for (int i = B_FAUX; i < NBAR; i++) mbar_init(BAR(i), i < B_E || !MC ? 2 : 4);
        mbar_init(BAR(B_KV4), 4); mbar_init(BAR(B_MS), 2); mbar_init(BAR(B_GQ), 1); mbar_init(BAR(B_GT), 1);
        if (R5) { mbar_init(BAR(B_EK), 4); mbar_init(BAR(B_EK + 1), 4); mbar_init(BAR(B_EK + 2), 4); }
      } else {
#pragma unroll
        for (int i = 0; i < 23; i++) mbar_init(BAR((warp == 13 ? 7 : 30) + i), 1);
      }
      asm volatile("fence.mbarrier_init.release.cluster;" ::: "memory");
    }
  }
  __syncthreads();
  if (MC) asm volatile("barrier.cluster.arrive.relaxed.aligned;" ::: "memory");

  const bool unit = u < NUNIT;
  const int dcol = (u & 15) * 64, drow = (u >> 4) * 448;
  if (warp >= 12) {
    asm volatile("setmaxnreg.dec.sync.aligned.u32 %0;" ::"n"(PROD_REGS));
    if (MC && warp != 12) asm volatile("barrier.cluster.wait.aligned;" ::: "memory");
    if (warp == 12) {
      int s = E1E == 2 ? 0 : 1 + E1E, p = E1E == 2 ? 0 : 1, pn = 3;
#pragma unroll 1
      for (int e = 1 + E1E; e < 16; e++) {
        if (MC && e == MC0) asm volatile("barrier.cluster.wait.aligned;" ::: "memory");
        if (e == GATE) mbar_wait(BAR(B_FXQ), 0);
        if (R4E && R5 && e >= 11) mbar_wait(BAR(B_EK + (s == 2 ? 0 : s + 1)), e >= 14);
        else mbar_wait(BAR(B_E + s), p);
        if (elect_one()) {
          load_entry(e, s);
          if (NR == 4 && e == 11) mbar_arrive(BAR(B_ME + 3));
          if (E1E != 2 && e == ASTE) {
            mbar_expect_tx(BAR(B_AST), 2 * SLOT + 2048);
            bulk_ld(sb + 12 * SLOT, x + (size_t)b * 16 * DM, 2 * SLOT, BAR(B_AST));
            bulk_ld(sb + MISC + M_MOE, wr, 2048, BAR(B_AST));
          } else if (e >= 3) {
            if (WSP == 0) { if (e < 6) bulk_pf(wqkv + (size_t)((e - 2) * 256 + 2 * b) * 3 * DM, 2 * 3 * DM * 2); }
            else if (e < 9) bulk_pf(wqkv + (size_t)((e - 1) * 128 + b) * 3 * DM, 3 * DM * 2);
            if (WOP >= 0 && e >= WOP && e < WOP + 4) bulk_pf(wo + (size_t)((e - WOP) * 256 + 2 * b) * DM, 2 * DM * 2);
            if (NUNIT) {
#pragma unroll 1
              for (int i = GPF ? 0 : (PFTAB >> (4 * (e - 3))) & 15; i > 0; i--, pn++) {
                if (pn >= 16) { if (!(MX & 8)) tma2d_pf(&tmD, dcol, drow + (pn - 16) * 64); }
                else if (unit && !(MX & 2)) tma2d_pf(rank ? &tmU : &tmG, (u >> 1) * 64, pn * 64);
              }
            }
          }
        }
        if (R5 && e >= 11) {
          if (R4E) mbar_wait(BAR(B_E + (s == 2 ? 0 : s + 1)), ((e - 2) / 3) & 1);
          else mbar_wait(BAR(B_EK + (s == 2 ? 0 : s + 1)), e >= 14);
          if (elect_one()) {
            mbar_expect_tx(BAR(B_FV + s), SLOT);
            if (rank) tma3d_mc(sb + ((V_SLOTS >> (4 * (e - 10))) & 15u) * SLOT, &tmW, kstep1(e, hg) * 64, 32 + 2 * hg, BAR(B_FV + s));
          }
        }
        if (++s == 3) { s = 0; p ^= 1; }
      }
#pragma unroll 1
      for (int k = 0; k < NQ; k++) {
        if (k == 0) mbar_wait(BAR(B_E + 1), 0);
        if (k == 1) mbar_wait(BAR(B_EK + 2), 1);
        if (k == 2) mbar_wait(BAR(B_EK + 0), 0);
        if (k == 3) mbar_wait(BAR(B_STG), 0);
        if (k == 5) mbar_wait(BAR(B_EQ), 0);
        if (elect_one()) {
          const int k0 = kstep1(NF + k, hg) * 64;
          mbar_expect_tx(BAR(B_FQ + k), SLOT);
          if (!(MC & 2)) tma3d(sb + ((QW_SLOTS >> (4 * k)) & 15u) * SLOT, &tmW, k0, 2 * hg, BAR(B_FQ + k));
          else if ((k & 1) == rank) tma3d_mc(sb + ((QW_SLOTS >> (4 * k)) & 15u) * SLOT, &tmW, k0, 2 * hg, BAR(B_FQ + k));
        }
      }
#pragma unroll 1
      for (int i = 0; i < 16; i++) {
        mbar_wait(i < 7 ? BAR(B_EQ + ((i + WQ0) >> 1)) : (i < 9 ? BAR(B_DE) : BAR(B_EO + i - 9)), 0);
        if (i == WOK) mbar_wait(BAR(B_KVB), 0);
        mbar_wait(BAR(B_FWO + i - (i < WOK ? WOD1 : WOD)), 0);
        if (elect_one()) {
          mbar_expect_tx(BAR(B_FWO + i), SLOT);
#pragma unroll
          for (int hf = 0; hf < ((MC & 4) ? 1 : 2); hf++) {
            const int n = 2 * i + ((MC & 4) ? rank : hf), m = slab(n - 4, hg), hd = n < 4 ? 4 * hg + n : 4 * (m & 7) + (m >> 3);
            if (i < 2 + NDIR) tma5d(sb + wo_slot(i) * SLOT + (n & 1) * 8192, &tmWp, hd * 4, 2 * hg, BAR(B_FWO + i), MC & 4);
            else if (MC & 4) tma3d_mc(sb + wo_slot(i) * SLOT + rank * 8192, &tmWo, hd * 32, 2 * hg, BAR(B_FWO + i));
            else tma3d(sb + wo_slot(i) * SLOT + hf * 8192, &tmWo, hd * 32, 2 * hg, BAR(B_FWO + i));
          }
        }
      }
    } else if (warp == 13) {
      if (elect_one()) {
        map_pf(rank ? &tmU : &tmG); map_pf(&tmR); map_pf(&tmD); map_pf(&tmWo); map_pf(&tmWp); map_pf(&tmOut);
      }
      bar_sync<6, 64>();
      if (elect_one()) {
        cnt_wait(C_B, NCTA);
        fence_async_gmem();
        mbar_expect_tx(BAR(B_FAUX), 1024);
        bulk_ld(sb + A_ST, G.stats + tb * 128, 1024, BAR(B_FAUX));
      }
      __syncwarp();
      TLS(416, 68);
#pragma unroll 1
      for (int m = 1; m < 4; m++) {
        const int part = m == 3 ? 0 : m;
        uint4 c;
#pragma unroll 1
        for (uint32_t it = 0; it < SPIN_MAX; it++) {
          c = ldx4(G.cs + part * DM + hg * 128 + lane * 4);
          if (__all_sync(~0u, min(min(c.x, c.y), min(c.z, c.w)))) break;
          __nanosleep(POLLNS);
        }
        if (CQ4 && part == 0) {
          const uint32_t o = sb + A_CS + (lane >> 2) * 64 + (lane & 1) * 32 + ((lane >> 1) & 1) * 8;
          asm volatile("st.shared.v2.u32 [%0], {%1,%2};\nst.shared.v2.u32 [%0+16], {%3,%4};" ::"r"(o), "r"(c.x), "r"(c.y), "r"(c.z), "r"(c.w) : "memory");
        } else sts_u4(sb + A_CS + part * 512 + lane * 16, c);
        __syncwarp();
        if (m > 1 && lane == 0) mbar_arrive(BAR(m == 2 ? B_FAUX : B_CQ));
        TLS(416, 71 + m);
      }
      mbar_wait(BAR(B_XS), 1);
      if (elect_one()) asm volatile("red.relaxed.gpu.global.add.u32 [%0], 1;" ::"l"(&G.cnt[C_DONE]) : "memory");
    } else if (warp == 14) {
      const uint4 sent = make_uint4(SENT, SENT, SENT, SENT);
      uint4* ro = G.o + (tb * 32 + hg) * 512 + lane;
      uint4* rp = G.part + b * 544 + lane;
      if (RSL) bar_sync<5, 160>(); else mbar_wait(BAR(B_AST), 0);
#pragma unroll 1
      for (int i = RS0; i < 40; i++) {
        uint4* q = i < 32 ? ro + (i >> 3) * 4096 + (i & 7) * 64 : rp + (i - 32) * 64;
        q[0] = sent; q[32] = sent;
        __nanosleep(RSNS);
      }
      rp[512] = sent;
#pragma unroll
      for (int i = 0; i < 4; i++) G.y[u * 128 + i * 32 + lane] = sent;
      if (unit) reinterpret_cast<uint4*>(G.h)[u * 32 + lane] = sent;
      G.fin[hg * 640 + tb * 40 + lane] = sent;
      if (lane < 8) G.fin[hg * 640 + tb * 40 + 32 + lane] = sent;
      if (!RSL) bar_sync<5, 160>();
      __syncwarp();
      TLS(448, 67);
      if (lane == 0) cnt_arrive(C_B);
      __syncwarp();
      TLS(448, 32);
      asm volatile("bar.arrive 6, 64;" ::: "memory");
    } else {
      const uint32_t stg = sb + 12 * SLOT;
      auto load_a = [&](int n, int r) {
        mbar_expect_tx(BAR(B_MF + r), (MX & 2) ? 1024 : MT);
        if (!(MX & 2)) tma2d_ef(sb + m_off(r), rank ? &tmU : &tmG, (u >> 1) * 64, n * 64, BAR(B_MF + r));
      };
      mbar_wait(BAR(B_XS), 0);
      if (unit) {
#pragma unroll 1
        for (int i = 0; i < 3; i++) {
          if (elect_one()) load_a(i, i);
          __nanosleep(PFILL);
        }
      }
      uint32_t key;
#pragma unroll 1
      for (uint32_t it = 0; it < SPIN_MAX; it++) {
        key = ldx1(G.top + ((u >> 1) & 3) * 32 + (lane & 7));
        if (__all_sync(~0u, key)) break;
        __nanosleep(TPNS);
      }
      TLS(480, 66);
      if (lane < 8) sts_u(sb + MISC + M_IDX + lane * 4, key);
      __syncwarp();
      if (lane == 0) mbar_arrive(BAR(B_XS));
      if (unit) {
        int tok[8];
#pragma unroll
        for (int i = 0; i < 8; i++) tok[i] = ~__shfl_sync(~0u, key, i) & 2047;
        int r = 0, p = 0;
#pragma unroll 1
        for (int n = 0; n < 16; n++) {
          if (n >= 3) mbar_wait(BAR(B_ME + r), r == 3 ? p : p ^ 1);
          if (elect_one()) {
            if (n >= 3) load_a(n, r);
#pragma unroll
            for (int i = 0; i < 8; i++) tma2d(sb + m_off(r) + 8192 + i * 128, &tmR, n * 64, tok[i], BAR(B_MF + r));
          }
          if (++r == NR) { r = 0; p ^= 1; }
        }
      }
      if (NUNIT) {
        if (lane == 0) mbar_expect_tx(BAR(B_DF), (MX & 8) ? 0 : 7 * 8192);
#pragma unroll 1
        for (int i = 0; i < 7; i++) {
          if (NR == 4) {
            if (i >= 3) mbar_wait(i < 5 ? BAR(B_ME + 3) : (R5 ? BAR(B_EQ + 1) : BAR(B_STG)), 0);
            else if (unit) mbar_wait(BAR(B_ME + i), 1);
          } else {
            if (i >= 3) mbar_wait(BAR(B_EQ + ((i - 3) >> 1)), 0);
            else if (unit) mbar_wait(BAR(B_ME + (i == 2 ? 0 : i + 1)), i == 2);
          }
          if (!(MX & 8) && elect_one()) tma2d_ef(sb + d_off(i), &tmD, dcol, drow + i * 64, BAR(B_DF));
          if (DNS) __nanosleep(DNS);
        }
      }
    }
    if (warp == 14) {
      if (GPF && unit) {
        const __nv_bfloat16* wsrc = (rank ? wu : wg) + (size_t)lane * FF + (u >> 1) * 64;
        if (GPD) __nanosleep(GPD);
#pragma unroll 1
        for (int pn = 3; pn < 16; pn++) {
          pf128(sb + MISC + M_DUM, wsrc + (size_t)(pn * 64) * FF); pf128(sb + MISC + M_DUM, wsrc + (size_t)(pn * 64 + 32) * FF);
          __nanosleep(GPF);
        }
      }
      if (DPF && NUNIT && !(MX & 8)) {
        mbar_wait(DS ? BAR(B_MS) : (DPF == 1 ? BAR(B_FQ) : BAR(B_T0)), 0);
#pragma unroll 1
        for (int pf = 0; pf < 7; pf++) { pf256(sb + MISC + M_DUM, wd + (size_t)(drow + pf * 64 + rank * 32 + lane) * DM + (dcol & ~127)); __nanosleep(PFNS2); }
      }
      const uint32_t* src = reinterpret_cast<const uint32_t*>(G.part + ((lane >> 3) * 32 + hg) * 544 + 512) + tb * 8 + (lane & 7);
      mbar_wait(BAR(B_EQ + MRW), 0);
      if (MRC) spin_cycles(MRC); else if (MRD) __nanosleep(MRD);
      uint32_t z0, z1, z2, z3;
#pragma unroll 1
      for (uint32_t it = 0; it < SPIN_MAX; it++) {
        z0 = ldx1(src); z1 = ldx1(src + 8 * 2176); z2 = ldx1(src + 16 * 2176); z3 = ldx1(src + 24 * 2176);
        if (!__any_sync(~0u, max(max(z0, z1), max(z2, z3)) == SENT)) break;
      }
      if (MRED == 2 && elect_one()) mbar_arrive(BAR(B_ZOK));
      float zz = (__uint_as_float(z0) + __uint_as_float(z1)) + (__uint_as_float(z2) + __uint_as_float(z3));
      zz += __shfl_xor_sync(~0u, zz, 8);
      zz += __shfl_xor_sync(~0u, zz, 16);
      stx1(reinterpret_cast<uint32_t*>(G.fin + hg * 640) + (tb >> 2) * 640 + 512 + ((tb >> 1) & 1) * 64 + (lane & 1) * 32 + (tb & 1) * 16 + ((lane & 7) >> 1) * 4 + (lane >> 3),
           pack_bf16(zz, zz));
      TLS(448, 12);
    }
    if (!MFIN && (warp == 13 || warp == 14)) {
      mbar_wait(BAR(B_EQ + H2W), 0);
      if (H2C) spin_cycles(H2C); else if (H2D) __nanosleep(H2D);
#pragma unroll 1
      for (uint32_t it = 0; it < SPIN_MAX; it++) {
        if (warp == 14 && elect_one()) {
          mbar_expect_tx(BAR(B_FIN), 10240);
          if (FMC && MC && it == 0) bulk_ld_mc(sb + S_KVB * SLOT + rank * 5120, G.fin + hg * 640 + rank * 320, 5120, BAR(B_FIN));
          else bulk_ld(sb + S_KVB * SLOT, G.fin + hg * 640, 10240, BAR(B_FIN));
        }
        mbar_wait(BAR(B_FIN), it & 1);
        uint32_t m = 0;
#pragma unroll
        for (int i = 0; i < 10; i++) m = max(m, lds_u(sb + S_KVB * SLOT + (i * 64 + ltid - 416) * 16 + (g >> 1) * 4));
        uint32_t bad;
        asm volatile("{\n.reg .pred p, q;\nsetp.eq.u32 p, %1, 0xFFFFFFFF;\nbar.red.or.pred q, 7, 64, p;\nselp.b32 %0, 1, 0, q;\n}" : "=r"(bad) : "r"(m) : "memory");
        if (!__any_sync(~0u, bad)) break;
      }
      if (warp == 14 && elect_one()) mbar_arrive(BAR(B_KVB));
      TLS(448, 14);
    }
    if (PH && (warp == 13 || warp == 14)) {
      bar_sync<3, 192>();
      mbar_wait(BAR(B_STG), 0);
#pragma unroll 1
      for (uint32_t it = 0; NUNIT && it < SPIN_MAX; it++) {
        if (elect_one()) {
          const uint32_t* ph = G.h + (u >> 4) * 7 * 256;
          if (warp == 13) { mbar_expect_tx(BAR(B_HF), 7168); bulk_ld(sb + h_off(3), ph + 768, 2048, BAR(B_HF)); bulk_ld(sb + h_off(5), ph + 1280, 2048, BAR(B_HF)); }
          else { bulk_ld(sb + h_off(0), ph, 1024, BAR(B_HF)); bulk_ld(sb + h_off(1), ph + 256, 1024, BAR(B_HF)); bulk_ld(sb + h_off(2), ph + 512, 1024, BAR(B_HF)); }
        }
        mbar_wait(BAR(B_HF), it & 1);
        uint32_t m = 0;
#pragma unroll
        for (int i = 0; i < 7; i++) m = max(m, lds_u(sb + h_off(i) + (ltid - 416) * 16 + (g >> 1) * 4));
        uint32_t bad;
        asm volatile("{\n.reg .pred p, q;\nsetp.eq.u32 p, %1, 0xFFFFFFFF;\nbar.red.or.pred q, 7, 64, p;\nselp.b32 %0, 1, 0, q;\n}" : "=r"(bad) : "r"(m) : "memory");
        if (!__any_sync(~0u, bad)) break;
        __nanosleep(POLLNS);
      }
      if (warp == 14 && elect_one()) mbar_arrive(BAR(B_KVB));
    }
    __syncwarp();
    if (warp >= 13) {
      const char* og = reinterpret_cast<const char*>(G.o + tb * 16384);
      auto probe = [&](uint32_t m) {
        const char* p = og + m * 8192u + (lane & 15) * 512 + 496;
#pragma unroll 1
        for (uint32_t it = 0; it < SPIN_MAX; it++)
          if (!__any_sync(~0u, ldx1(p) == SENT)) break;
      };
      if (warp == 15) {
        int r = 0, p = 1;
        mbar_wait(BAR(B_EAUX), 0);
#pragma unroll 1
        for (int i = I0; i < 16; i++) {
          const uint32_t dst = sb + ((A_SLOTS >> (4 * r)) & 15u) * SLOT, m0 = slab(2 * i - 4, hg), m1 = slab(2 * i - 3, hg);
          if (i == I0 + 3) mbar_wait(BAR(B_DE), 0);
          mbar_wait(BAR(B_EA + r), p);
          if ((PROBE >> i) & 1) probe(lane < 16 ? m0 : m1);
          if (elect_one()) {
            mbar_expect_tx(BAR(B_AF + r), SLOT);
            bulk_ld(dst, og + m0 * 8192u, 8192, BAR(B_AF + r)); bulk_ld(dst + 8192, og + m1 * 8192u, 8192, BAR(B_AF + r));
          }
          if (++r == NA) { r = 0; p ^= 1; }
        }
      } else {
        const uint32_t lo = lane * 32 + g * 4, hb = sb + (warp - 13) * 8192;
        uint32_t ph = 0;
        int r = 0, p = 0;
#pragma unroll 1
        for (int i = I0; i < 16; i++) {
          const uint32_t mine = hb + ((A_SLOTS >> (4 * r)) & 15u) * SLOT;
          auto bad = [&]() {
            uint32_t v[8];
#pragma unroll
            for (int j = 0; j < 8; j++) v[j] = lds_u(mine + lo + j * 1024);
            return __any_sync(~0u, max(max(max(v[0], v[1]), max(v[2], v[3])), max(max(v[4], v[5]), max(v[6], v[7]))) == SENT);
          };
          mbar_wait(BAR(B_AF + r), p);
          if (!NOVAL && bad()) {
            const uint32_t m = slab(2 * i - 17 + warp, hg);
#pragma unroll 1
            for (uint32_t it = 0; it < 64; it++) {
              probe(m);
              if (elect_one()) { mbar_expect_tx(BAR(B_AR + warp - 13), 8192); bulk_ld(mine, og + m * 8192u, 8192, BAR(B_AR + warp - 13)); }
              mbar_wait(BAR(B_AR + warp - 13), ph);
              ph ^= 1;
              if (!bad()) break;
            }
          }
          if (elect_one()) mbar_arrive(BAR(B_VAL + r));
          if (++r == NA) { r = 0; p ^= 1; }
        }
      }
    }
  } else if (warp >= 8) {
    asm volatile("setmaxnreg.dec.sync.aligned.u32 %0;" ::"n"(MOE_REGS));
    if (MC) asm volatile("barrier.cluster.wait.aligned;" ::: "memory");
    const int aw = warp - 8;
    const uint32_t mbuf = sb + MISC + M_MOE, stg = sb + 12 * SLOT;
    mbar_wait(BAR(B_AST), 0);
    TLS(288, 64);
    {
      float v[16];
#pragma unroll
      for (int r = 0; r < 16; r++) v[r] = 0.f;
      const uint32_t base = stg + aw * 4 * 2048 + lane * 8;
#pragma unroll 1
      for (int c = 0; c < 8; c++) {
        const float2 w2 = lds_f2(mbuf + c * 256 + lane * 8);
        const float w[4] = {bf_lo(__float_as_uint(w2.x)), bf_hi(__float_as_uint(w2.x)), bf_lo(__float_as_uint(w2.y)), bf_hi(__float_as_uint(w2.y))};
        v[12] += (w[0] + w[1]) + (w[2] + w[3]);
#pragma unroll
        for (int r = 0; r < 4; r++) {
          const float2 x2 = lds_f2(base + r * 2048 + c * 256);
#pragma unroll
          for (int e = 0; e < 2; e++) {
            const uint32_t xx = __float_as_uint(e ? x2.y : x2.x);
            const float lo = bf_lo(xx), hi = bf_hi(xx);
            v[r] += lo; v[4 + r] = fmaf(lo, lo, v[4 + r]); v[8 + r] = fmaf(lo, w[2 * e], v[8 + r]);
            v[r] += hi; v[4 + r] = fmaf(hi, hi, v[4 + r]); v[8 + r] = fmaf(hi, w[2 * e + 1], v[8 + r]);
          }
        }
      }
#pragma unroll
      for (int l = 0; l < 4; l++) {
        const int n = 8 >> l;
        const bool up = lane & (2 * n);
#pragma unroll
        for (int r = 0; r < 8; r++) {
          if (r < n) { const float a = v[r], c = v[n + r]; v[r] = (up ? c : a) + __shfl_xor_sync(~0u, up ? a : c, 2 * n); }
        }
      }
      v[0] += __shfl_xor_sync(~0u, v[0], 1);
      const float sx = __shfl_sync(~0u, v[0], 2 * t), sq = __shfl_sync(~0u, v[0], 8 + 2 * t), sw = __shfl_sync(~0u, v[0], 16 + 2 * t), ws = __shfl_sync(~0u, v[0], 24);
      if (lane < 4) {
        const int row = b * 16 + aw * 4 + lane;
        const float mean = sx * (1.f / DM);
        const float var = fmaxf(fmaf(-mean, mean, sq * (1.f / DM)), 0.f);
        float sd;
        asm("sqrt.approx.ftz.f32 %0, %1;" : "=f"(sd) : "f"(bf_round(bf_round(var) + 1e-5f)));
        const float rstd = rcp(bf_round(sd));
        const float mb = bf_round(mean);
        uint32_t rb = pack_bf16(fmaf(-mb, ws, sw) * rstd, 0.f) & 0xFFFFu;
        rb = (rb & 0x8000u) ? (~rb & 0xFFFFu) : (rb | 0x8000u);
        const uint32_t key = (1u << 27) | (rb << 11) | (uint32_t)(2047 - row);
        if (KEY1) sts_u(sb + MISC + M_KEY + (aw * 4 + lane) * 4, key); else stx1(G.key + row, key);
        G.stats[row] = make_float2(mb, SL2 ? rstd * LOG2E : rstd);
      }
    }
    bar_sync<2, 128>();
    if (KEY1 && ltid < 272) stx1(G.key + b * 16 + lane, lds_u(sb + MISC + M_KEY + lane * 4));
    TLS(288, 65);
    sts_u4(sb + A_ONES + (ltid - 256) * 16, make_uint4(0x3F803F80u, 0x3F803F80u, 0x3F803F80u, 0x3F803F80u));
    fence_async_smem();
    asm volatile("bar.arrive 5, 160;" ::: "memory");
    if (ltid == 256) { if (unit && rank == 0) mbar_expect_tx(BAR(B_UP), 2048); mbar_arrive(BAR(B_XS)); }
    bar_sync<2, 128>();
    mbar_wait(BAR(B_XS), 1);
    TLS(288, 70);
    if (NUNIT) {
      if (unit) {
        int r = 0, p = 0;
        uint32_t rel = 0;
        float acc[8];
        uint2 s0, s1;
#pragma unroll
        for (int i = 0; i < 8; i++) acc[i] = 0.f;
        if (MS == 16) mbar_wait(BAR(B_T0), 0); else if (MS) mbar_wait(BAR(B_MS), 0);
#pragma unroll 1
        for (int n = 0; n < 16; n++) {
          if (n == 15) {
            mbar_wait(BAR(B_FAUX), 0);
            s0 = ldx2(G.stats + (~lds_u(sb + MISC + M_IDX + t * 8) & 2047)); s1 = ldx2(G.stats + (~lds_u(sb + MISC + M_IDX + t * 8 + 4) & 2047));
            if (SL2) { s0.y = __float_as_uint(__uint_as_float(s0.y) * LN2); s1.y = __float_as_uint(__uint_as_float(s1.y) * LN2); }
          }
          mbar_wait(BAR(B_MF + r), p);
          if (!(n & 3)) TLS(288, 56 + (n >> 2));
          const uint32_t mo = m_off(r) >> 4, da = (d0 + mo) | (512u << 16), db = (d0 + mo + 512) | (1u << 16);
          const uint32_t hb = 0x40000000u | ((A_ONES >> 4) - 512 - mo);
          wg_fence();
#pragma unroll
          for (int kk = 0; kk < ((MX & 1) ? 1 : 4); kk++) wgmma_ss_n16<1, 0>(acc, mkdesc(da + kk * 128, HI_SW128), mkdesc(db + kk * 2, hb));
          wg_commit();
          wg_wait<1>();
          if (n > 0 && !rel && ltid == 256) mbar_arrive(BAR(B_ME + (r == 0 ? NR - 1 : r - 1)));
          rel = 0;
          const int r0 = r;
          if (++r == NR) { r = 0; p ^= 1; }
        }
        wg_wait<0>();
        reg_fence(acc);
        {
          if (!MW0 && !rel && ltid == 256) mbar_arrive(BAR(B_ME + 15 % NR));
          TLS(288, 71);
          const float v0 = bf_round(fmaf(-__uint_as_float(s0.x), acc[4], acc[0]) * __uint_as_float(s0.y));
          const float v1 = bf_round(fmaf(-__uint_as_float(s1.x), acc[4], acc[1]) * __uint_as_float(s1.y));
          const float v2 = bf_round(fmaf(-__uint_as_float(s0.x), acc[6], acc[2]) * __uint_as_float(s0.y));
          const float v3 = bf_round(fmaf(-__uint_as_float(s1.x), acc[6], acc[3]) * __uint_as_float(s1.y));
          if (rank) {
            asm volatile("{\n.reg .b32 ra, rb;\nmapa.shared::cluster.u32 ra, %0, 0;\nmapa.shared::cluster.u32 rb, %1, 0;\n"
                         "st.async.weak.shared::cluster.mbarrier::complete_tx::bytes.v4.f32 [ra], {%2, %3, %4, %5}, [rb];\n}"
                         ::"r"(mbuf + (ltid - 256) * 16), "r"(BAR(B_UP)), "f"(v0), "f"(v1), "f"(v2), "f"(v3) : "memory");
          } else {
            const float g0 = bf_round(v0 * sigmoid(v0)), g1 = bf_round(v1 * sigmoid(v1)), g2 = bf_round(v2 * sigmoid(v2)), g3 = bf_round(v3 * sigmoid(v3));
            mbar_wait(BAR(B_UP), 0);
            const uint4 uu = lds_u4(mbuf + (ltid - 256) * 16);
            const uint32_t h0 = movmat(pack_bf16(g0 * __uint_as_float(uu.x), g1 * __uint_as_float(uu.y)));
            const uint32_t h1 = movmat(pack_bf16(g2 * __uint_as_float(uu.z), g3 * __uint_as_float(uu.w)));
            uint32_t* ph = G.h + (u >> 1) * 256 + g * 32 + t;
            stx1(ph + ((2 * aw) ^ g) * 4, h0); stx1(ph + ((2 * aw + 1) ^ g) * 4, h1);
          }
          TLS(288, 60);
        }
      }
    }
    if (PH) asm volatile("bar.arrive 3, 192;" ::: "memory");
    {
      const int wd_ = ltid & 63;
      const uint32_t* src = reinterpret_cast<const uint32_t*>(G.part + hg * 544 + (aw >> 1) * 256 + tb * 16) + wd_;
      mbar_wait(MRED == 2 ? BAR(B_ZOK) : BAR(B_EQ + MRW), 0);
      if (MRC) spin_cycles(MRC); else if (MRD) __nanosleep(MRD);
      TLS(256, 48);
      uint32_t v[16];
#pragma unroll 1
      for (uint32_t it = 0; it < SPIN_MAX; it++) {
        uint32_t m = 0;
#pragma unroll
        for (int i = 0; i < 16; i++) v[i] = ldx1(src + i * 8 * 2176);
#pragma unroll
        for (int i = 0; i < 16; i++) m = max(m, v[i]);
        if (!__any_sync(~0u, m == SENT)) break;
      }
      TLS(256, 55);
      float lo[4], hi[4];
#pragma unroll
      for (int i = 0; i < 4; i++) {
        lo[i] = (bf_lo(v[4 * i]) + bf_lo(v[4 * i + 1])) + (bf_lo(v[4 * i + 2]) + bf_lo(v[4 * i + 3]));
        hi[i] = (bf_hi(v[4 * i]) + bf_hi(v[4 * i + 1])) + (bf_hi(v[4 * i + 2]) + bf_hi(v[4 * i + 3]));
      }
      stx1(reinterpret_cast<uint32_t*>(G.fin + hg * 640) + (tb >> 2) * 640 + ((tb >> 1) & 1) * 64 + (tb & 1) * 16 + (aw >> 1) * 32 + ((wd_ >> 2) & 3) * 128 + (wd_ >> 4) * 4 + (wd_ & 3),
           pack_bf16((lo[0] + lo[1]) + (lo[2] + lo[3]), (hi[0] + hi[1]) + (hi[2] + hi[3])));
      TLS(256, 5);
    }
    if (NUNIT) {
      mbar_wait(BAR(B_STG), 0);
      bar_sync<2, 128>();
      if (HW) __nanosleep(HW);
#pragma unroll 1
      for (uint32_t it = 0; it < SPIN_MAX; it++) {
        if (elect_one()) {
          const uint32_t* ph = G.h + (u >> 4) * 7 * 256;
          if (aw == 3) { mbar_expect_tx(BAR(B_HF), 7168); bulk_ld(sb + h_off(3), ph + 768, 2048, BAR(B_HF)); bulk_ld(sb + h_off(5), ph + 1280, 2048, BAR(B_HF)); }
          else bulk_ld(stg + aw * MT + 8192, ph + aw * 256, 1024, BAR(B_HF));
        }
        mbar_wait(BAR(B_HF), it & 1);
        const uint32_t o = (ltid & 63) * 16 + (g >> 1) * 4, o2 = o + (aw >> 1) * 1024;
        const uint32_t m = max(max(lds_u(sb + h_off(0) + (aw >> 1) * MT + o), lds_u(sb + h_off(2) + o)), max(lds_u(sb + h_off(3) + o2), lds_u(sb + h_off(5) + o2)));
        uint32_t bad;
        asm volatile("{\n.reg .pred p, q;\nsetp.eq.u32 p, %1, 0xFFFFFFFF;\nbar.red.or.pred q, 2, 128, p;\nselp.b32 %0, 1, 0, q;\n}" : "=r"(bad) : "r"(m) : "memory");
        if (!__any_sync(~0u, bad)) break;
        __nanosleep(POLLNS);
      }
      TLS(288, 62);
      float acc[4] = {0.f, 0.f, 0.f, 0.f};
      mbar_wait(BAR(B_DF), 0);
      TLS(288, 63);
#pragma unroll 1
      for (int i = 0; i < 7; i++) {
        const uint32_t da = (d0 + (d_off(i) >> 4)) | (512u << 16), db = (d0 + (h_off(i) >> 4)) | (1u << 16);
        wg_fence();
#pragma unroll
        for (int kk = 0; kk < ((MX & 4) ? 1 : 4); kk++) wgmma_ss_n8<1, 0>(acc, mkdesc(da + kk * 128, HI_SW128), mkdesc(db + kk * 2, HI_SW128));
        wg_commit();
      }
      wg_wait<0>();
      reg_fence(acc);
      if (ltid < 258) { if (MC) mbar_arrive_cta(BAR(B_DE), ltid & 1); else mbar_arrive(BAR(B_DE)); }
      {
        uint32_t* py = reinterpret_cast<uint32_t*>(G.y) + u * 512 + t * 128 + aw * 16 + g;
        stx1(py, f2x(acc[0])); stx1(py + 64, f2x(acc[1])); stx1(py + 8, f2x(acc[2])); stx1(py + 72, f2x(acc[3]));
      }
      TLS(288, 69);
      const uint32_t key = lds_u(sb + MISC + M_IDX + (lane & 7) * 4);
      uint32_t rb = (key >> 11) & 0xFFFFu;
      rb = (rb & 0x8000u) ? (rb & 0x7FFFu) : (~rb & 0xFFFFu);
      const float sg = bf_round(sigmoid(__uint_as_float(rb << 16)));
      uint32_t hits = __ballot_sync(~0u, ((~key >> 7) & 15) == tb) & 255u;
      const uint32_t* py = reinterpret_cast<const uint32_t*>(G.y) + (2 * hg + (aw >> 1)) * 512 + (ltid & 63);
      if (hits) {
        sts_u4(mbuf + (ltid - 256) * 16, make_uint4(0, 0, 0, 0));
        bar_sync<2, 128>();
        if (YW >= 0) mbar_wait(BAR(B_EO + YW), 0); else if (YW == -2) mbar_wait(BAR(B_EAUX), 0);
      }
#pragma unroll 1
      while (hits) {
        const int n0 = __ffs(hits) - 1;
        hits &= hits - 1;
        const int n1 = hits ? __ffs(hits) - 1 : n0;
        hits &= hits - 1;
        uint32_t v[16];
#pragma unroll 1
        for (uint32_t it = 0; it < SPIN_MAX; it++) {
          uint32_t m = 0;
#pragma unroll
          for (int i = 0; i < 8; i++) { v[i] = ldx1(py + n0 * 64 + i * 8192); v[8 + i] = ldx1(py + n1 * 64 + i * 8192); }
#pragma unroll
          for (int i = 0; i < 16; i++) m = max(m, v[i]);
          if (!__any_sync(~0u, m == SENT)) break;
          __nanosleep(POLLNS);
        }
#pragma unroll
        for (int e = 0; e < 2; e++) {
          const uint32_t* w8 = v + 8 * e;
          const float y = ((__uint_as_float(w8[0]) + __uint_as_float(w8[1])) + (__uint_as_float(w8[2]) + __uint_as_float(w8[3]))) +
                          ((__uint_as_float(w8[4]) + __uint_as_float(w8[5])) + (__uint_as_float(w8[6]) + __uint_as_float(w8[7])));
          const int n = e ? n1 : n0;
          sts_h(mbuf + (aw >> 1) * 1024 + n * 128 + ((((ltid >> 3) & 7) ^ n) << 4) + (lane & 7) * 2, bf_round(y) * __shfl_sync(~0u, sg, n));
        }
      }
    }
    if (!NUNIT && ltid < 258) mbar_arrive(BAR(B_DE));
    fence_async_smem();
    bar_sync<2, 128>();
    TLS(288, 33);
    if (ltid == 288) mbar_arrive(BAR(B_MOE));
  } else {
    asm volatile("setmaxnreg.inc.sync.aligned.u32 %0;" ::"n"(CON_REGS));
    if (MC) asm volatile("barrier.cluster.wait.aligned;" ::: "memory");
    const int w = warp >> 2, wq = warp & 3, tid = ltid;
    const bool lead = (tid & 127) == 0;
    const uint32_t dA = (d0 + w * 512) | (1u << 16);
    const uint32_t dB = d0 | (512u << 16);
    auto release = [&](int bar) { if (lead) mbar_arrive(BAR(bar)); };
    auto release2 = [&](int bar) {
      if (MC) { if ((tid & 127) < 2) mbar_arrive_cta(BAR(bar), tid & 1); } else release(bar);
    };
    float aq[64], ak[64], av[64];
#pragma unroll
    for (int i = 0; i < 64; i++) aq[i] = ak[i] = av[i] = 0.f;
    auto q_step = [&](uint32_t bar, int p, uint32_t xs, uint32_t qs) {
      mbar_wait_b(bar, p);
      wg_fence();
#pragma unroll
      for (int kk = 0; kk < 4; kk++)
        wgmma_ss_n128<0, 1>(aq, mkdesc(dA + xs * 1024 + kk * 2, HI_SW128), mkdesc(dB + qs * 1024 + kk * 128, HI_SW128));
      wg_commit();
    };
    const uint32_t dT = dB + w * 512, dX = d0 | (1u << 16);
    auto t_step = [&](float (&a)[64], uint32_t ws, uint32_t xs) {
      wg_fence();
#pragma unroll
      for (int kk = 0; kk < 4; kk++)
        wgmma_ss_n128<1, 0>(a, mkdesc(dT + ws * 1024 + kk * 128, HI_SW128), mkdesc(dX + xs * 1024 + kk * 2, HI_SW128));
      wg_commit();
    };
    {
      int s = 0, p = 0, sp = 2;
#pragma unroll 1
      for (int e = 0; e < NF; e++) {
        TLS(0, 16 + e);
        if (((MS && MS < NF) || (DS && DS < NF)) && e == (MS ? MS : DS)) release(B_MS);
        q_step(BAR(B_FXQ + s), p, s, 3 + s);
        wg_wait<1>();
        if (e > 0) release2(B_E + sp);
        mbar_wait(BAR(B_FKV + s), p);
        t_step(ak, 6 + 2 * s, s);
        if (R5) mbar_wait(BAR(B_FV + s), p);
        t_step(av, 7 + 2 * s, s);
        if (R5 && e == NF - 1) { wg_wait<1>(); release2(B_EK + s); }
        sp = s;
        if (++s == 3) { s = 0; p ^= 1; }
      }
#pragma unroll 1
      for (int e = NF; e < 16; e++) {
        TLS(0, 16 + e);
        if (((MS >= NF && MS < 16) || DS >= NF) && e == (MS ? MS : DS)) release(B_MS);
        if (ST && e == 16 - ST && w == 1) mbar_wait(BAR(B_GT), 0);
        mbar_wait(BAR(B_FXQ + s), p);
        mbar_wait(BAR(B_FKV + s), p);
        t_step(ak, R5 ? (K_SLOTS >> (4 * (e - 10))) & 15u : 6 + 2 * s, x_slot(e, s));
        wg_wait<1>();
        release2(B_E + sp);
        if (R5) mbar_wait(BAR(B_FV + s), p);
        t_step(av, R5 ? (V_SLOTS >> (4 * (e - 10))) & 15u : 7 + 2 * s, x_slot(e, s));
        if (ST && e == 15 && tid == 0) mbar_arrive(BAR(B_GT));
        if (R5) { wg_wait<1>(); release2(B_EK + s); }
        sp = s;
        if (++s == 3) { s = 0; p ^= 1; }
      }
    }
    const uint32_t aux = sb;
    mbar_wait(BAR(B_FAUX), 0);
    const int row0 = w * 64 + wq * 16 + g;
    const float ck0 = lds_f(aux + A_CS + 512 + row0 * 4), ck1 = lds_f(aux + A_CS + 512 + (row0 + 8) * 4);
    const float cv0 = lds_f(aux + A_CS + 1024 + row0 * 4), cv1 = lds_f(aux + A_CS + 1024 + (row0 + 8) * 4);
    const uint32_t moff = (uint32_t)(w * 64 + wq * 16 + (lane & 15)) * 128 + (((lane >> 4) ^ (lane & 7)) << 4);
    const uint32_t sta = aux + A_ST + t * 16;
    float kvp[36], ao[64];
    uint32_t xr[32];
    float nm0, nm1, rs0, rs1, rl0, rl1;
    auto row_stats = [&]() {
      const float2 st0 = lds_f2(aux + A_ST + row0 * 8), st1 = lds_f2(aux + A_ST + (row0 + 8) * 8);
      nm0 = -st0.x; nm1 = -st1.x;
      if (SL2) { rl0 = st0.y; rl1 = st1.y; rs0 = rl0 * LN2; rs1 = rl1 * LN2; }
      else { rs0 = st0.y; rs1 = st1.y; rl0 = rs0 * LOG2E; rl1 = rs1 * LOG2E; }
    };
    auto ld_x = [&]() {
#pragma unroll
      for (int j = 0; j < 16; j += 2) ldsm4(sb + (j < 8 ? SX14 : SX15) * SLOT + (moff ^ ((j & 7) << 4)), xr[2 * j], xr[2 * j + 1], xr[2 * j + 2], xr[2 * j + 3]);
    };
    auto resid = [&]() {
      const float c0 = 1.f + rs0, c1 = 1.f + rs1, e0 = nm0 * rs0, e1 = nm1 * rs1;
#pragma unroll
      for (int j = 0; j < 16; j++) {
        ao[4 * j + 0] = fmaf(bf_lo(xr[2 * j]), c0, e0); ao[4 * j + 1] = fmaf(bf_hi(xr[2 * j]), c0, e0);
        ao[4 * j + 2] = fmaf(bf_lo(xr[2 * j + 1]), c1, e1); ao[4 * j + 3] = fmaf(bf_hi(xr[2 * j + 1]), c1, e1);
      }
    };
    {
      uint32_t pa[32];
      float4 st[16];
      auto ld = [&](int j) { st[j] = lds_f4(sta + j * 64); };
      auto k_blk = [&](int c) {
#pragma unroll
        for (int i = 0; i < 2; i++) {
          const float4 u = st[2 * c + i];
          const float l0 = u.y * LOG2E, l1 = u.w * LOG2E;
          const float* a = ak + 8 * c + 4 * i;
          pa[4 * c + 2 * i] = SL2 ? phi2l(FOLD(-u.x, ck0, a[0]), u.y, FOLD(-u.z, ck0, a[1]), u.w) : phi2<(VOL & 1) != 0>(FOLD(-u.x, ck0, a[0]), u.y, l0, FOLD(-u.z, ck0, a[1]), u.w, l1);
          pa[4 * c + 2 * i + 1] = SL2 ? phi2l(FOLD(-u.x, ck1, a[2]), u.y, FOLD(-u.z, ck1, a[3]), u.w) : phi2<(VOL & 1) != 0>(FOLD(-u.x, ck1, a[2]), u.y, l0, FOLD(-u.z, ck1, a[3]), u.w, l1);
        }
      };
      const uint32_t voff = sb + w * 8192 + (uint32_t)(8 * (lane >> 4) + (lane & 7)) * 128 + (((2 * wq + ((lane >> 3) & 1)) ^ (lane & 7)) << 4);
      auto v_blk = [&](int c) {
        uint32_t r[4];
#pragma unroll
        for (int i = 0; i < 2; i++) {
          const float4 u = st[2 * c + i];
          const float* a = av + 8 * c + 4 * i;
          r[2 * i] = pack_bf16(FOLD(-u.x, cv0, a[0]) * u.y, FOLD(-u.z, cv0, a[1]) * u.w);
          r[2 * i + 1] = pack_bf16(FOLD(-u.x, cv1, a[2]) * u.y, FOLD(-u.z, cv1, a[3]) * u.w);
        }
        stsm4t(voff + (c < 4 ? S_V0 : S_V1) * SLOT + (c & 3) * 2048, r[0], r[1], r[2], r[3]);
      };
      auto kv_mma = [&](int c) {
        const uint32_t bo = (c < 4 ? S_V0 : S_V1) * 1024 + w * 512 + (c & 3) * 128;
        const uint64_t bb = mkdesc((d0 + bo) | (((A_ONES >> 4) - bo) << 16), HI_SW128);
        if (c == 0) wgmma_rz_n72<1>(kvp, pa[4 * c], pa[4 * c + 1], pa[4 * c + 2], pa[4 * c + 3], bb);
        else wgmma_rs_n72<1>(kvp, pa[4 * c], pa[4 * c + 1], pa[4 * c + 2], pa[4 * c + 3], bb);
      };
      if (NOFOLD == 2) {
        wg_fence();
        wgmma_rs_n128<0>(ak, __float_as_uint(ck0), __float_as_uint(ck1), 0u, 0u, mkdesc(dX + SX14 * 1024, HI_SW128));
        wgmma_rs_n128<0>(av, __float_as_uint(cv0), __float_as_uint(cv1), 0u, 0u, mkdesc(dX + SX14 * 1024, HI_SW128));
        wg_commit();
      }
      if (SH2 && R5) {
        reg_fence(ak);
        ld(6); ld(7); k_blk(3);
        asm volatile("" : "+r"(pa[12]), "+r"(pa[13]), "+r"(pa[14]), "+r"(pa[15]));
      }
      ld(0); ld(1);
      wg_wait<0>();
      if (!(SH2 && R5)) reg_fence(ak);
      reg_fence(av);
      TLS(0, 2);
      if (!R5) release2(B_E);
      release(B_T0);
      if (LQ) { v_blk(0); ld(2); ld(3); } else { ld(2); ld(3); v_blk(0); }
      ld(4); ld(5); v_blk(1); k_blk(0);
      ld(6); ld(7); v_blk(2); ld(8); ld(9); v_blk(3); k_blk(1);
      ld(10); ld(11); v_blk(4); ld(12); ld(13); v_blk(5); k_blk(2);
      ld(14); ld(15); v_blk(6); v_blk(7); if (!(SH2 && R5)) k_blk(3);
      if (RL) { ld(8); ld(9); }
#pragma unroll
      for (int c = 4; c < KS; c++) k_blk(c);
      TLS(0, 3);
      fence_async_smem();
      asm volatile("bar.sync %0, 128;" ::"r"(3 + w) : "memory");
      if (XP == 0) ld_x();
      wg_fence();
#pragma unroll
      for (int c = 0; c < KS; c++) kv_mma(c);
      wg_commit();
#pragma unroll
      for (int c = KS; c < 8; c++) {
        if (RL && c < 7) { ld(2 * c + 2); ld(2 * c + 3); }
        k_blk(c);
        wg_fence();
        kv_mma(c);
        wg_commit();
      }
      if (XP == 3 && (RK == 0 || RK == 9)) ld_x();
      if (QE) { q_step(BAR(B_FQ), 0, SXQ0, QW_SLOTS & 15u); wg_wait<1>(); } else wg_wait<0>();
      reg_fence(kvp);
      auto hand_back = [&]() { release2(B_STG); __syncwarp(); };
      if (!SF) hand_back();
      TLS(0, 4);
      uint4* pp = G.part + b * 544;
      uint32_t pk[8];
#pragma unroll
      for (int j = 0; j < 8; j++) pk[j] = wq >= 2 ? pack_bf16(kvp[16 + 2 * j], kvp[17 + 2 * j]) : pack_bf16(kvp[2 * j], kvp[2 * j + 1]);
      stx4(pp + tid, pk[0], pk[2], pk[4], pk[6]);
      stx4(pp + 256 + tid, pk[1], pk[3], pk[5], pk[7]);
      if (t == 0) stx2(reinterpret_cast<uint2*>(pp + 512) + (tid >> 2), f2x(kvp[32]), f2x(kvp[34]));
      if (SF == 1) hand_back();
      if (XP == 1) ld_x();
      if (!QE) q_step(BAR(B_FQ), 0, SXQ0, QW_SLOTS & 15u);
      if (XP == 2) ld_x();
      if (SF == 2) hand_back();
      if (RK == 0 || RK == 9) {
        uint32_t chk = 0;
#pragma unroll
        for (int j = 0; j < 8; j++) chk ^= xr[4 * j];
        asm volatile("{\n.reg .pred p;\nsetp.eq.u32 p, %0, 0x7FC17FC3;\n@p st.shared.u32 [%1], %0;\n}" ::"r"(chk), "r"(sb + MISC + M_DUM) : "memory");
      }
      const int wd_ = wq * 16 + (lane & 15);
      const uint32_t* src = reinterpret_cast<const uint32_t*>(G.part + ((lane >> 4) * 64 + hg) * 544 + w * 256 + tb * 16) + wd_;
      uint32_t* fin = reinterpret_cast<uint32_t*>(G.fin + hg * 640) + (tb >> 2) * 640 + ((tb >> 1) & 1) * 64 + (tb & 1) * 16 + w * 32 + ((wd_ >> 2) & 3) * 128 + wq * 4 + (wd_ & 3);
      uint32_t v[8];
      auto part_load = [&]() {
#pragma unroll
        for (int i = 0; i < 8; i++) v[i] = ldx1(src + i * 8 * 2176);
      };
#pragma unroll
      for (int k = 1; k < NQ; k++) {
        if (SQ && k == NQ - SQ && w == 1) mbar_wait(BAR(B_GQ), 0);
        q_step(BAR(B_FQ + k), 0, (QX_SLOTS >> (4 * k)) & 15u, (QW_SLOTS >> (4 * k)) & 15u);
        if (SQ && k == NQ - 1 && tid == 0) mbar_arrive(BAR(B_GQ));
        TLS(0, 48 + k);
        if (!MRED && k == PLP) part_load();
        if (!MRED && k == PLC) {
#pragma unroll 1
          for (uint32_t it = 0; it < SPIN_MAX; it++) {
            if (!__any_sync(~0u, max(max(max(v[0], v[1]), max(v[2], v[3])), max(max(v[4], v[5]), max(v[6], v[7]))) == SENT)) break;
            part_load();
          }
          float lo = ((bf_lo(v[0]) + bf_lo(v[1])) + (bf_lo(v[2]) + bf_lo(v[3]))) + ((bf_lo(v[4]) + bf_lo(v[5])) + (bf_lo(v[6]) + bf_lo(v[7])));
          float hi = ((bf_hi(v[0]) + bf_hi(v[1])) + (bf_hi(v[2]) + bf_hi(v[3]))) + ((bf_hi(v[4]) + bf_hi(v[5])) + (bf_hi(v[6]) + bf_hi(v[7])));
          lo += __shfl_xor_sync(~0u, lo, 16); hi += __shfl_xor_sync(~0u, hi, 16);
          if (lane < 16) stx1(fin, pack_bf16(lo, hi));
          TLS(0, 5);
        }
        wg_wait<1>();
        release2(B_EQ + k - 1);
        if (k == RK) { row_stats(); ld_x(); resid(); reg_fence(ao); }
      }
      TLS(0, 13);
      if (!NOCQ) mbar_wait(BAR(B_CQ), 0);
    }
    float4 cq4[8];
    auto ld_cq = [&](int j) {
      if (CQ4) cq4[j >> 1] = lds_f4(aux + A_CS + (j * 8 + 4 * t) * 4);
      else { const float2 ca = lds_f2(aux + A_CS + (j * 8 + 2 * t) * 4), cb = lds_f2(aux + A_CS + (j * 8 + 8 + 2 * t) * 4); cq4[j >> 1] = make_float4(ca.x, ca.y, cb.x, cb.y); }
    };
    if (CQE) {
      if (RK == 0 || RK == 9) row_stats();
#pragma unroll
      for (int j = 0; j < 16; j += 2) ld_cq(j);
    }
    wg_wait<0>();
    reg_fence(aq);
    TLS(0, 15);
    if (!CQE && (RK == 0 || RK == 9)) row_stats();
    uint32_t pq[32];
#pragma unroll
    for (int j = 0; j < 16; j += 2) {
      if (!CQE) ld_cq(j);
      const float4 c4 = cq4[j >> 1];
#pragma unroll
      for (int i = 0; i < 2; i++) {
        const float cx = i ? c4.z : c4.x, cy = i ? c4.w : c4.y;
        const float* a = aq + 4 * (j + i);
        pq[2 * (j + i)] = SL2 ? phi2l(fmaf(nm0, cx, a[0]), rl0, fmaf(nm0, cy, a[1]), rl0) : phi2<(VOL & 2) != 0>(fmaf(nm0, cx, a[0]), rs0, rl0, fmaf(nm0, cy, a[1]), rs0, rl0);
        pq[2 * (j + i) + 1] = SL2 ? phi2l(fmaf(nm1, cx, a[2]), rl1, fmaf(nm1, cy, a[3]), rl1) : phi2<(VOL & 2) != 0>(fmaf(nm1, cx, a[2]), rs1, rl1, fmaf(nm1, cy, a[3]), rs1, rl1);
      }
    }
    TLS(0, 6);
    if (RK == 9) { resid(); if (RF) reg_fence(ao); }
    mbar_wait_b(BAR(MFIN ? B_KV4 : B_KVB), 0);
    TLS(0, 7);
    uint32_t of[32];
    uint4* mine = G.o + (tb * 32 + hg) * 512 + warp * 64 + g * 4 + (t ^ (g >> 1));
    const uint32_t dW = d0 | (256u << 16);
    auto o_store = [&](int h) {
#pragma unroll
      for (int c = 0; c < 2; c++) stx4(mine + h * 4096 + c * 32, of[8 * h + c], of[8 * h + 2 + c], of[8 * h + 4 + c], of[8 * h + 6 + c]);
    };
    auto out_step = [&](uint32_t slot, const uint32_t* a) {
      const uint32_t d = dW + slot * 1024;
      wg_fence();
#pragma unroll
      for (int kk = 0; kk < 4; kk++) wgmma_rs_n128<1>(ao, a[4 * kk], a[4 * kk + 1], a[4 * kk + 2], a[4 * kk + 3], mkdesc(d + (kk >> 1) * 512 + (kk & 1) * 128, HI_SW128));
      wg_commit();
    };
    uint4 v[NDIR][4];
    auto ld_o = [&](int k) {
      const uint4* p0 = mine + (slab(2 * k, hg) - hg) * 512;
      const uint4* p1 = mine + (slab(2 * k + 1, hg) - hg) * 512;
      v[k][0] = ldx4(p0); v[k][1] = ldx4(p0 + 32); v[k][2] = ldx4(p1); v[k][3] = ldx4(p1 + 32);
    };
    auto ld_all = [&]() {
#pragma unroll
      for (int k = 0; k < NDIR; k++) ld_o(k);
    };
    {
      float oa[4][20];
      const uint32_t dK = (d0 + S_KVB * 1024) | (8u << 16);
      auto o_mma = [&](int h) {
        wgmma_rz_n40<1>(oa[h], pq[8 * h], pq[8 * h + 1], pq[8 * h + 2], pq[8 * h + 3], mkdesc(dK + h * 160, HI_NOSW));
        wgmma_rs_n40<1>(oa[h], pq[8 * h + 4], pq[8 * h + 5], pq[8 * h + 6], pq[8 * h + 7], mkdesc(dK + h * 160 + 16, HI_NOSW));
      };
      wg_fence();
      o_mma(0);
      wg_commit();
      if (OH == 0) { o_mma(1); o_mma(2); o_mma(3); wg_commit(); }
      if (OH == 2) { o_mma(1); wg_commit(); }
      auto norm = [&](int h) {
        const float r0 = SL2 ? rcp(fmaf(oa[h][16], LOG2E, 1e-6f * LOG2E)) : rcp(oa[h][16] + 1e-6f);
        const float r1 = SL2 ? rcp(fmaf(oa[h][18], LOG2E, 1e-6f * LOG2E)) : rcp(oa[h][18] + 1e-6f);
#pragma unroll
        for (int j = 0; j < 4; j++) {
          of[8 * h + 2 * j] = pack_bf16(oa[h][4 * j] * r0, oa[h][4 * j + 1] * r0);
          of[8 * h + 2 * j + 1] = pack_bf16(oa[h][4 * j + 2] * r1, oa[h][4 * j + 3] * r1);
        }
      };
      if (OH == 1) wg_wait<0>(); else wg_wait<1>();
      reg_fence(oa[0]);
      norm(0);
      if (LE == 4) ld_all();
      o_store(0);
      if (LE == 3) ld_all();
      TLS(0, 8);
      if (OH == 1) { wg_fence(); o_mma(1); o_mma(2); o_mma(3); wg_commit(); }
      if (OH == 2) { wg_fence(); o_mma(2); o_mma(3); wg_commit(); }
      wg_wait<0>();
      reg_fence(oa[1]); reg_fence(oa[2]); reg_fence(oa[3]);
      TLP_(0);
      release(B_EAUX);
      norm(1);
      if (OS1 == 3) o_store(1);
      if (E7 && NP == 0 && SL7 && hg == 7) o_store(1);
      if (NP == 0) { norm(2); norm(3); }
      if (E7 && NP == 0 && SL7 && hg == 7) { o_store(2); o_store(3); }
      TLP_(1);
      mbar_wait_b(BAR(B_FWO), 0);
      TLP_(2);
      if (RK == 0) resid();
      if (LE == 2) ld_all();
      TLP_(3);
      out_step(WO_SLOTS & 15u, of);
      TLP_(4);
      if (NP == 1) { norm(2); norm(3); }
      if (LE == 1) ld_all();
      if (LE == 5) ld_o(0);
    }
    if (OS1 == 0) o_store(1);
    mbar_wait(BAR(B_FWO + 1), 0);
    TLP_(5);
    out_step((WO_SLOTS >> 4) & 15u, of + 16);
    TLP_(6);
    const bool early = SL7 && hg == 7;
    if (OS1 == 1 && !(E7 && early)) o_store(1);
    TLP_(7);
    if (early && !E7) { o_store(2); o_store(3); }
    {
      if (DW) __nanosleep(DW);
      if (LE == 0) ld_all();
      if (LE == 5 && NDIR > 1) ld_o(NDIR - 1);
      if (OS1 == 2 && !(E7 && early)) o_store(1);
#pragma unroll
      for (int k = 0; k < NDIR; k++) {
#pragma unroll 1
        for (uint32_t it = 0; it < SPIN_MAX; it++) {
          if (!__any_sync(~0u, max(max(v[k][0].x, v[k][1].x), max(v[k][2].x, v[k][3].x)) == SENT)) break;
#pragma unroll
          for (int j = k; j < (LE == 5 ? k + 1 : NDIR); j++) ld_o(j);
        }
        TLP_(8);
        const uint32_t a[16] = {v[k][0].x, v[k][1].x, v[k][0].y, v[k][1].y, v[k][0].z, v[k][1].z, v[k][0].w, v[k][1].w,
                                v[k][2].x, v[k][3].x, v[k][2].y, v[k][3].y, v[k][2].z, v[k][3].z, v[k][2].w, v[k][3].w};
        mbar_wait(BAR(B_FWO + 2 + k), 0);
        TLS(0, 34 + k);
        out_step((WO_SLOTS >> (8 + 4 * k)) & 15u, a);
        TLP_(9);
        if (k) { wg_wait<1>(); release2(B_EO); }
      }
      if (!early) o_store(2);
    }
    auto routed = [&]() {
      mbar_wait(BAR(B_MOE), 0);
      const float2 kk = lds_f2(sb + MISC + M_IDX + t * 8);
      const int k0 = (int)(~__float_as_uint(kk.x) & 2047u) - tb * 128, k1 = (int)(~__float_as_uint(kk.y) & 2047u) - tb * 128;
      if (NUNIT && __any_sync(~0u, (k0 >> 6) == w || (k1 >> 6) == w)) {
        const uint32_t a0 = (k0 == row0 ? 0x3F80u : 0u) | (k1 == row0 ? 0x3F800000u : 0u);
        const uint32_t a1 = (k0 == row0 + 8 ? 0x3F80u : 0u) | (k1 == row0 + 8 ? 0x3F800000u : 0u);
        wg_fence();
        wgmma_rs_n128<1>(ao, a0, a1, 0u, 0u, mkdesc((d0 + ((MISC + M_MOE) >> 4)) | (64u << 16), 0x40000000u));
        wg_commit();
      }
    };
    auto out_half = [&](int h, const float* v) {
      const uint32_t ost = sb + (w ? S_D1 : S_D0) * SLOT + wq * 4096 + h * 2048;
#pragma unroll
      for (int j = 0; j < 8; j += 2)
        stsm4(ost + ((moff & 2047) ^ (j << 4)), pack_bf16(v[4 * j], v[4 * j + 1]), pack_bf16(v[4 * j + 2], v[4 * j + 3]),
              pack_bf16(v[4 * j + 4], v[4 * j + 5]), pack_bf16(v[4 * j + 6], v[4 * j + 7]));
      if (OUTV == 3 || (OUTV == 4 && h == 0)) {
        __syncwarp();
        __nv_bfloat16* dst = outp + (size_t)(tb * 128 + warp * 16 + (lane >> 3)) * DM + hg * 128 + h * 64 + (lane & 7) * 8;
#pragma unroll
        for (int i = 0; i < 4; i++) {
          const int r = 4 * i + (lane >> 3);
          const uint4 u4 = lds_u4(ost + r * 128 + (((lane & 7) ^ (r & 7)) << 4));
          asm volatile("st.global.v4.u32 [%0], {%1,%2,%3,%4};" ::"l"(dst + (size_t)i * 4 * DM), "r"(u4.x), "r"(u4.y), "r"(u4.z), "r"(u4.w) : "memory");
        }
        return;
      }
      fence_async_smem();
      __syncwarp();
      if (elect_one()) {
        if (OEF) asm volatile("cp.async.bulk.tensor.2d.global.shared::cta.bulk_group.L2::cache_hint [%0, {%2, %3}], [%1], %4;" ::"l"(&tmOut), "r"(ost), "r"(hg * 128 + h * 64), "r"(tb * 128 + warp * 16), "l"(POL_FIRST) : "memory");
        else asm volatile("cp.async.bulk.tensor.2d.global.shared::cta.bulk_group [%0, {%2, %3}], [%1];" ::"l"(&tmOut), "r"(ost), "r"(hg * 128 + h * 64), "r"(tb * 128 + warp * 16) : "memory");
        if (h) asm volatile("cp.async.bulk.commit_group;\ncp.async.bulk.wait_group.read 0;" ::: "memory");
      }
      __syncwarp();
    };
    bool done = false;
    {
      const uint32_t dO = (d0 + w * 256) | (1u << 16);
      auto step = [&](int i, int r, int p, uint32_t as, uint32_t ws) {
        mbar_wait(BAR(B_FWO + i), 0);
        mbar_wait(BAR(B_VAL + r), p);
        TLS(0, 32 + i);
        const uint32_t da = dO + as * 1024, db = dW + ws * 1024;
        wg_fence();
#pragma unroll
        for (int kk = 0; kk < 4; kk++)
          wgmma_ss_n128<0, 1>(ao, mkdesc(da + (kk >> 1) * 512 + (kk & 1) * 2, HI_SW64), mkdesc(db + (kk >> 1) * 512 + (kk & 1) * 128, HI_SW128));
        wg_commit();
      };
      uint64_t tbl = WO_SLOTS >> (4 * I0);
      int r = 0, p = 0, rp = 0;
#pragma unroll 1
      for (int i = I0; i < 12; i++) {
        step(i, r, p, (A_SLOTS >> (4 * r)) & 15u, (uint32_t)tbl & 15u);
        tbl >>= 4;
#pragma unroll
        for (int c = 0; c < 2; c++)
          if (i == OS3 + c && !early) stx4(mine + 3 * 4096 + c * 32, of[24 + c], of[26 + c], of[28 + c], of[30 + c]);
        wg_wait<1>();
        if (i > I0) release(B_EA + rp);
        rp = r;
        if (++r == NA) { r = 0; p ^= 1; }
        if (i >= 3 && i <= 9) release2(B_EO + i - 3);
      }
      if (SPL && w == 1) {
        float bl[32], bh[32];
        mbar_wait(BAR(B_GO), 0);
        routed();
#pragma unroll
        for (int h = 0; h < 2; h++) {
#pragma unroll
          for (int i = 12; i < 16; i++) {
            const int r_ = (i - I0) % NA;
            if (h == 0) { mbar_wait(BAR(B_FWO + i), 0); mbar_wait(BAR(B_VAL + r_), ((i - I0) / NA) & 1); }
            const uint32_t da = dO + ((A_SLOTS >> (4 * r_)) & 15u) * 1024, db = dW + ((uint32_t)(WO_SLOTS >> (4 * i)) & 15u) * 1024 + h * 256;
            if (h == 0 || i == 12) wg_fence();
#pragma unroll
            for (int kk = 0; kk < 4; kk++) {
              const uint64_t a = mkdesc(da + (kk >> 1) * 512 + (kk & 1) * 2, HI_SW64), bb = mkdesc(db + (kk >> 1) * 512 + (kk & 1) * 128, HI_SW128);
              if (i == 12 && kk == 0) wgmma_sz_n64<0, 1>(h ? bh : bl, a, bb); else wgmma_ss_n64<0, 1>(h ? bh : bl, a, bb);
            }
          }
          wg_commit();
        }
        wg_wait<1>();
        reg_fence(ao); reg_fence(bl);
#pragma unroll
        for (int j = 0; j < 32; j++) bl[j] += ao[j];
        out_half(0, bl);
        wg_wait<0>();
        reg_fence(bh);
#pragma unroll
        for (int j = 0; j < 32; j++) bh[j] += ao[32 + j];
        out_half(1, bh);
        done = true;
      } else
#pragma unroll
      for (int i = 12; i < 16; i++) {
        if (i == 16 - STAG && w == 1) mbar_wait(BAR(B_GO), 0);
        step(i, (i - I0) % NA, ((i - I0) / NA) & 1, (A_SLOTS >> (4 * ((i - I0) % NA))) & 15u, (uint32_t)(WO_SLOTS >> (4 * i)) & 15u);
        if (STAG && i == 15 - GOE && tid == 0) mbar_arrive(BAR(B_GO));
      }
    }
    if (!done) {
      routed();
      wg_wait<0>();
      reg_fence(ao);
      TLS(0, 10);
      out_half(0, ao);
      out_half(1, ao + 32);
    }
    TLS(0, 11);
    TLS(128, 9);
  }
}

typedef CUresult (*EncFn)(CUtensorMap*, CUtensorMapDataType, cuuint32_t, void*, const cuuint64_t*, const cuuint64_t*, const cuuint32_t*,
                          const cuuint32_t*, CUtensorMapInterleave, CUtensorMapSwizzle, CUtensorMapL2promotion, CUtensorMapFloatOOBfill);

void make_map2(EncFn enc, CUtensorMap* m, void* p, uint64_t rows, uint64_t cols, uint32_t brows, CUtensorMapL2promotion promo) {
  cuuint64_t gd[2] = {cols, rows}, gs[1] = {cols * 2};
  cuuint32_t bd[2] = {64, brows}, es[2] = {1, 1};
  enc(m, CU_TENSOR_MAP_DATA_TYPE_BFLOAT16, 2, p, gd, gs, bd, es, CU_TENSOR_MAP_INTERLEAVE_NONE, CU_TENSOR_MAP_SWIZZLE_128B, promo,
      CU_TENSOR_MAP_FLOAT_OOB_FILL_NONE);
}
void make_map3(EncFn enc, CUtensorMap* m, void* p, uint64_t rows, uint64_t cols, uint32_t brows) {
  cuuint64_t gd[3] = {64, rows, cols / 64}, gs[2] = {cols * 2, 128};
  cuuint32_t bd[3] = {64, brows, 2}, es[3] = {1, 1, 1};
  enc(m, CU_TENSOR_MAP_DATA_TYPE_BFLOAT16, 3, p, gd, gs, bd, es, CU_TENSOR_MAP_INTERLEAVE_NONE, CU_TENSOR_MAP_SWIZZLE_128B,
      CU_TENSOR_MAP_L2_PROMOTION_L2_256B, CU_TENSOR_MAP_FLOAT_OOB_FILL_NONE);
}

}

extern "C" void kernel_launch(void* const* d_in, const int* in_sizes, int n_in, void* d_out, int out_size) {
  static EncFn enc = nullptr;
  static int by_sm = 0;
  if (!enc) {
    void* fn = nullptr;
    cudaDriverEntryPointQueryResult qr;
    cudaGetDriverEntryPoint("cuTensorMapEncodeTiled", &fn, cudaEnableDefault, &qr);
    enc = (EncFn)fn;
    int dev = 0, sms = 0;
    cudaGetDevice(&dev);
    cudaDeviceGetAttribute(&sms, cudaDevAttrMultiProcessorCount, dev);
    by_sm = MAP == 2 && sms == NCTA + NSVC;
    cudaFuncSetAttribute(fused_kernel, cudaFuncAttributeMaxDynamicSharedMemorySize, SMEM_BYTES);
  }
  CUtensorMap tmX, tmW, tmWo, tmOut, tmG, tmU, tmD, tmR, tmWp;
  {
    cuuint64_t gd[5] = {64, 2, 128, 4, 16}, gs[4] = {2048, 16384, 4096, 128};
    cuuint32_t bd[5] = {64, 2, 4, 4, 2}, es[5] = {1, 1, 1, 1, 1};
    enc(&tmWp, CU_TENSOR_MAP_DATA_TYPE_BFLOAT16, 5, d_in[2], gd, gs, bd, es, CU_TENSOR_MAP_INTERLEAVE_NONE, CU_TENSOR_MAP_SWIZZLE_128B,
        CU_TENSOR_MAP_L2_PROMOTION_L2_256B, CU_TENSOR_MAP_FLOAT_OOB_FILL_NONE);
  }
  make_map2(enc, &tmR, d_in[0], SEQ, DM, 1, CU_TENSOR_MAP_L2_PROMOTION_L2_128B);
  make_map2(enc, &tmX, d_in[0], SEQ, DM, 128, XPROMO);
  make_map3(enc, &tmW, d_in[1], DM, 3 * DM, 64);
  make_map3(enc, &tmWo, d_in[2], DM, DM, 32);
  if (OUTV) make_map2(enc, &tmOut, d_out, SEQ, DM, 16, CU_TENSOR_MAP_L2_PROMOTION_L2_128B); else make_map3(enc, &tmOut, d_out, SEQ, DM, 64);
  make_map2(enc, &tmG, d_in[5], DM, FF, 64, MPROMO);
  make_map2(enc, &tmU, d_in[6], DM, FF, 64, MPROMO);
  make_map2(enc, &tmD, d_in[7], FF, DM, 64, MPROMO);
  typedef const __nv_bfloat16* P;
  cudaLaunchConfig_t cfg = {};
  cfg.gridDim = dim3(NCTA + NSVC); cfg.blockDim = dim3(512); cfg.dynamicSmemBytes = SMEM_BYTES; cfg.stream = cudaStreamPerThread;
  cudaLaunchAttribute at[1];
  at[0].id = cudaLaunchAttributeClusterDimension;
  at[0].val.clusterDim.x = 2; at[0].val.clusterDim.y = 1; at[0].val.clusterDim.z = 1;
  cfg.attrs = at; cfg.numAttrs = 1;
  cudaLaunchKernelEx(&cfg, fused_kernel, (P)d_in[0], (P)d_in[1], (P)d_in[2], (P)d_in[4], (P)d_in[7], (__nv_bfloat16*)d_out, (P)d_in[5], (P)d_in[6], by_sm, tmX, tmW, tmWo, tmOut, tmG, tmU, tmD, tmR, tmWp);
}
```

```cpp
#include <cuda_runtime.h>
#include <cuda.h>
#include <cuda_bf16.h>
#include <stdint.h>

#define WK 0
#define NOCQ 0
#define NOFOLD 0
#define FOLD(m, c, a) fmaf(m, c, a)
#define OEF 0
namespace {

template <int TA, int TB> __device__ __forceinline__ void wgmma_ss_n128(float (&d)[64], uint64_t da, uint64_t db) {
  asm volatile("wgmma.mma_async.sync.aligned.m64n128k16.f32.bf16.bf16 "
  "{%0,%1,%2,%3,%4,%5,%6,%7,%8,%9,%10,%11,%12,%13,%14,%15,%16,%17,%18,%19,%20,%21,%22,%23,%24,%25,%26,%27,%28,%29,%30,%31,%32,%33,%34,%35,%36,%37,%38,%39,%40,%41,%42,%43,%44,%45,%46,%47,%48,%49,%50,%51,%52,%53,%54,%55,%56,%57,%58,%59,%60,%61,%62,%63}, "
  "%64, %65, 1, 1, 1, %66, %67;"
  : "+f"(d[0]),"+f"(d[1]),"+f"(d[2]),"+f"(d[3]),"+f"(d[4]),"+f"(d[5]),"+f"(d[6]),"+f"(d[7]),"+f"(d[8]),"+f"(d[9]),"+f"(d[10]),"+f"(d[11]),"+f"(d[12]),"+f"(d[13]),"+f"(d[14]),"+f"(d[15]),"+f"(d[16]),"+f"(d[17]),"+f"(d[18]),"+f"(d[19]),"+f"(d[20]),"+f"(d[21]),"+f"(d[22]),"+f"(d[23]),"+f"(d[24]),"+f"(d[25]),"+f"(d[26]),"+f"(d[27]),"+f"(d[28]),"+f"(d[29]),"+f"(d[30]),"+f"(d[31]),"+f"(d[32]),"+f"(d[33]),"+f"(d[34]),"+f"(d[35]),"+f"(d[36]),"+f"(d[37]),"+f"(d[38]),"+f"(d[39]),"+f"(d[40]),"+f"(d[41]),"+f"(d[42]),"+f"(d[43]),"+f"(d[44]),"+f"(d[45]),"+f"(d[46]),"+f"(d[47]),"+f"(d[48]),"+f"(d[49]),"+f"(d[50]),"+f"(d[51]),"+f"(d[52]),"+f"(d[53]),"+f"(d[54]),"+f"(d[55]),"+f"(d[56]),"+f"(d[57]),"+f"(d[58]),"+f"(d[59]),"+f"(d[60]),"+f"(d[61]),"+f"(d[62]),"+f"(d[63])
  : "l"(da), "l"(db), "n"(TA), "n"(TB));
}
template <int TA, int TB> __device__ __forceinline__ void wgmma_ss_n64(float (&d)[32], uint64_t da, uint64_t db) {
  asm volatile("wgmma.mma_async.sync.aligned.m64n64k16.f32.bf16.bf16 "
  "{%0,%1,%2,%3,%4,%5,%6,%7,%8,%9,%10,%11,%12,%13,%14,%15,%16,%17,%18,%19,%20,%21,%22,%23,%24,%25,%26,%27,%28,%29,%30,%31}, "
  "%32, %33, 1, 1, 1, %34, %35;"
  : "+f"(d[0]),"+f"(d[1]),"+f"(d[2]),"+f"(d[3]),"+f"(d[4]),"+f"(d[5]),"+f"(d[6]),"+f"(d[7]),"+f"(d[8]),"+f"(d[9]),"+f"(d[10]),"+f"(d[11]),"+f"(d[12]),"+f"(d[13]),"+f"(d[14]),"+f"(d[15]),"+f"(d[16]),"+f"(d[17]),"+f"(d[18]),"+f"(d[19]),"+f"(d[20]),"+f"(d[21]),"+f"(d[22]),"+f"(d[23]),"+f"(d[24]),"+f"(d[25]),"+f"(d[26]),"+f"(d[27]),"+f"(d[28]),"+f"(d[29]),"+f"(d[30]),"+f"(d[31])
  : "l"(da), "l"(db), "n"(TA), "n"(TB));
}
template <int TA, int TB> __device__ __forceinline__ void wgmma_sz_n64(float (&d)[32], uint64_t da, uint64_t db) {
  asm volatile("wgmma.mma_async.sync.aligned.m64n64k16.f32.bf16.bf16 "
  "{%0,%1,%2,%3,%4,%5,%6,%7,%8,%9,%10,%11,%12,%13,%14,%15,%16,%17,%18,%19,%20,%21,%22,%23,%24,%25,%26,%27,%28,%29,%30,%31}, "
  "%32, %33, 0, 1, 1, %34, %35;"
  : "=f"(d[0]),"=f"(d[1]),"=f"(d[2]),"=f"(d[3]),"=f"(d[4]),"=f"(d[5]),"=f"(d[6]),"=f"(d[7]),"=f"(d[8]),"=f"(d[9]),"=f"(d[10]),"=f"(d[11]),"=f"(d[12]),"=f"(d[13]),"=f"(d[14]),"=f"(d[15]),"=f"(d[16]),"=f"(d[17]),"=f"(d[18]),"=f"(d[19]),"=f"(d[20]),"=f"(d[21]),"=f"(d[22]),"=f"(d[23]),"=f"(d[24]),"=f"(d[25]),"=f"(d[26]),"=f"(d[27]),"=f"(d[28]),"=f"(d[29]),"=f"(d[30]),"=f"(d[31])
  : "l"(da), "l"(db), "n"(TA), "n"(TB));
}
template <int TB> __device__ __forceinline__ void wgmma_rs_n72(float (&d)[36], uint32_t a0, uint32_t a1, uint32_t a2, uint32_t a3, uint64_t db) {
  asm volatile("wgmma.mma_async.sync.aligned.m64n72k16.f32.bf16.bf16 "
  "{%0,%1,%2,%3,%4,%5,%6,%7,%8,%9,%10,%11,%12,%13,%14,%15,%16,%17,%18,%19,%20,%21,%22,%23,%24,%25,%26,%27,%28,%29,%30,%31,%32,%33,%34,%35}, "
  "{%36,%37,%38,%39}, %40, 1, 1, 1, %41;"
  : "+f"(d[0]),"+f"(d[1]),"+f"(d[2]),"+f"(d[3]),"+f"(d[4]),"+f"(d[5]),"+f"(d[6]),"+f"(d[7]),"+f"(d[8]),"+f"(d[9]),"+f"(d[10]),"+f"(d[11]),"+f"(d[12]),"+f"(d[13]),"+f"(d[14]),"+f"(d[15]),"+f"(d[16]),"+f"(d[17]),"+f"(d[18]),"+f"(d[19]),"+f"(d[20]),"+f"(d[21]),"+f"(d[22]),"+f"(d[23]),"+f"(d[24]),"+f"(d[25]),"+f"(d[26]),"+f"(d[27]),"+f"(d[28]),"+f"(d[29]),"+f"(d[30]),"+f"(d[31]),"+f"(d[32]),"+f"(d[33]),"+f"(d[34]),"+f"(d[35])
  : "r"(a0), "r"(a1), "r"(a2), "r"(a3), "l"(db), "n"(TB));
}
template <int TB> __device__ __forceinline__ void wgmma_rz_n72(float (&d)[36], uint32_t a0, uint32_t a1, uint32_t a2, uint32_t a3, uint64_t db) {
  asm volatile("wgmma.mma_async.sync.aligned.m64n72k16.f32.bf16.bf16 "
  "{%0,%1,%2,%3,%4,%5,%6,%7,%8,%9,%10,%11,%12,%13,%14,%15,%16,%17,%18,%19,%20,%21,%22,%23,%24,%25,%26,%27,%28,%29,%30,%31,%32,%33,%34,%35}, "
  "{%36,%37,%38,%39}, %40, 0, 1, 1, %41;"
  : "=f"(d[0]),"=f"(d[1]),"=f"(d[2]),"=f"(d[3]),"=f"(d[4]),"=f"(d[5]),"=f"(d[6]),"=f"(d[7]),"=f"(d[8]),"=f"(d[9]),"=f"(d[10]),"=f"(d[11]),"=f"(d[12]),"=f"(d[13]),"=f"(d[14]),"=f"(d[15]),"=f"(d[16]),"=f"(d[17]),"=f"(d[18]),"=f"(d[19]),"=f"(d[20]),"=f"(d[21]),"=f"(d[22]),"=f"(d[23]),"=f"(d[24]),"=f"(d[25]),"=f"(d[26]),"=f"(d[27]),"=f"(d[28]),"=f"(d[29]),"=f"(d[30]),"=f"(d[31]),"=f"(d[32]),"=f"(d[33]),"=f"(d[34]),"=f"(d[35])
  : "r"(a0), "r"(a1), "r"(a2), "r"(a3), "l"(db), "n"(TB));
}
template <int TB> __device__ __forceinline__ void wgmma_rs_n40(float (&d)[20], uint32_t a0, uint32_t a1, uint32_t a2, uint32_t a3, uint64_t db) {
  asm volatile("wgmma.mma_async.sync.aligned.m64n40k16.f32.bf16.bf16 "
  "{%0,%1,%2,%3,%4,%5,%6,%7,%8,%9,%10,%11,%12,%13,%14,%15,%16,%17,%18,%19}, "
  "{%20,%21,%22,%23}, %24, 1, 1, 1, %25;"
  : "+f"(d[0]),"+f"(d[1]),"+f"(d[2]),"+f"(d[3]),"+f"(d[4]),"+f"(d[5]),"+f"(d[6]),"+f"(d[7]),"+f"(d[8]),"+f"(d[9]),"+f"(d[10]),"+f"(d[11]),"+f"(d[12]),"+f"(d[13]),"+f"(d[14]),"+f"(d[15]),"+f"(d[16]),"+f"(d[17]),"+f"(d[18]),"+f"(d[19])
  : "r"(a0), "r"(a1), "r"(a2), "r"(a3), "l"(db), "n"(TB));
}
template <int TB> __device__ __forceinline__ void wgmma_rz_n40(float (&d)[20], uint32_t a0, uint32_t a1, uint32_t a2, uint32_t a3, uint64_t db) {
  asm volatile("wgmma.mma_async.sync.aligned.m64n40k16.f32.bf16.bf16 "
  "{%0,%1,%2,%3,%4,%5,%6,%7,%8,%9,%10,%11,%12,%13,%14,%15,%16,%17,%18,%19}, "
  "{%20,%21,%22,%23}, %24, 0, 1, 1, %25;"
  : "=f"(d[0]),"=f"(d[1]),"=f"(d[2]),"=f"(d[3]),"=f"(d[4]),"=f"(d[5]),"=f"(d[6]),"=f"(d[7]),"=f"(d[8]),"=f"(d[9]),"=f"(d[10]),"=f"(d[11]),"=f"(d[12]),"=f"(d[13]),"=f"(d[14]),"=f"(d[15]),"=f"(d[16]),"=f"(d[17]),"=f"(d[18]),"=f"(d[19])
  : "r"(a0), "r"(a1), "r"(a2), "r"(a3), "l"(db), "n"(TB));
}
template <int TB> __device__ __forceinline__ void wgmma_rs_n128(float (&d)[64], uint32_t a0, uint32_t a1, uint32_t a2, uint32_t a3, uint64_t db) {
  asm volatile("wgmma.mma_async.sync.aligned.m64n128k16.f32.bf16.bf16 "
  "{%0,%1,%2,%3,%4,%5,%6,%7,%8,%9,%10,%11,%12,%13,%14,%15,%16,%17,%18,%19,%20,%21,%22,%23,%24,%25,%26,%27,%28,%29,%30,%31,%32,%33,%34,%35,%36,%37,%38,%39,%40,%41,%42,%43,%44,%45,%46,%47,%48,%49,%50,%51,%52,%53,%54,%55,%56,%57,%58,%59,%60,%61,%62,%63}, "
  "{%64,%65,%66,%67}, %68, 1, 1, 1, %69;"
  : "+f"(d[0]),"+f"(d[1]),"+f"(d[2]),"+f"(d[3]),"+f"(d[4]),"+f"(d[5]),"+f"(d[6]),"+f"(d[7]),"+f"(d[8]),"+f"(d[9]),"+f"(d[10]),"+f"(d[11]),"+f"(d[12]),"+f"(d[13]),"+f"(d[14]),"+f"(d[15]),"+f"(d[16]),"+f"(d[17]),"+f"(d[18]),"+f"(d[19]),"+f"(d[20]),"+f"(d[21]),"+f"(d[22]),"+f"(d[23]),"+f"(d[24]),"+f"(d[25]),"+f"(d[26]),"+f"(d[27]),"+f"(d[28]),"+f"(d[29]),"+f"(d[30]),"+f"(d[31]),"+f"(d[32]),"+f"(d[33]),"+f"(d[34]),"+f"(d[35]),"+f"(d[36]),"+f"(d[37]),"+f"(d[38]),"+f"(d[39]),"+f"(d[40]),"+f"(d[41]),"+f"(d[42]),"+f"(d[43]),"+f"(d[44]),"+f"(d[45]),"+f"(d[46]),"+f"(d[47]),"+f"(d[48]),"+f"(d[49]),"+f"(d[50]),"+f"(d[51]),"+f"(d[52]),"+f"(d[53]),"+f"(d[54]),"+f"(d[55]),"+f"(d[56]),"+f"(d[57]),"+f"(d[58]),"+f"(d[59]),"+f"(d[60]),"+f"(d[61]),"+f"(d[62]),"+f"(d[63])
  : "r"(a0), "r"(a1), "r"(a2), "r"(a3), "l"(db), "n"(TB));
}
template <int TA, int TB> __device__ __forceinline__ void wgmma_ss_n8(float (&d)[4], uint64_t da, uint64_t db) {
  asm volatile("wgmma.mma_async.sync.aligned.m64n8k16.f32.bf16.bf16 "
  "{%0,%1,%2,%3}, "
  "%4, %5, 1, 1, 1, %6, %7;"
  : "+f"(d[0]),"+f"(d[1]),"+f"(d[2]),"+f"(d[3])
  : "l"(da), "l"(db), "n"(TA), "n"(TB));
}
template <int TA, int TB> __device__ __forceinline__ void wgmma_ss_n16(float (&d)[8], uint64_t da, uint64_t db) {
  asm volatile("wgmma.mma_async.sync.aligned.m64n16k16.f32.bf16.bf16 "
  "{%0,%1,%2,%3,%4,%5,%6,%7}, "
  "%8, %9, 1, 1, 1, %10, %11;"
  : "+f"(d[0]),"+f"(d[1]),"+f"(d[2]),"+f"(d[3]),"+f"(d[4]),"+f"(d[5]),"+f"(d[6]),"+f"(d[7])
  : "l"(da), "l"(db), "n"(TA), "n"(TB));
}

constexpr int SEQ = 2048, DM = 1024, FF = 3584;
constexpr int NCTA = 128, NSVC = 4;
constexpr int NUNIT = 112;
constexpr uint32_t SLOT = 16384;
constexpr uint32_t MISC = 14 * SLOT;
constexpr uint32_t SMEM_BYTES = MISC + 3072;
constexpr uint32_t M_MOE = 0;
constexpr uint32_t M_BAR = 2048;
constexpr uint32_t M_DUM = 2048 + 1020;
constexpr uint32_t M_IDX = 2048 + 768;
constexpr uint32_t M_KEY = 2048 + 960;
#define R5 1
#define NQ (R5 ? 6 : 5)
constexpr int NF = 16 - NQ, NR = (NQ == 5 || R5) ? 4 : 3;
constexpr int B_FXQ = 0, B_FKV = 3, B_AST = 6, B_MOE = 7, B_MF = 8  , B_CQ = 12, B_XS = 13, B_DF = 14, B_ZOK = 15, B_FWO = 21  , B_FQ = B_FWO - NQ,
              B_UP = 37, B_FIN = 38, B_KVB = 39, B_ME = 40  , B_HF = 44, B_AF = 45  , B_AR = 50  , B_GO = 52,
              B_FAUX = 53, B_EAUX = 54, B_T0 = 55, B_DE = 56, B_EA = 57  , B_VAL = 62  ,
              B_E = 67  , B_STG = 70, B_EQ = 71  , B_EO = 76  , NBAR = 83, B_KV4 = 83, B_MS = 84,
              B_FV = 85  , B_EK = 88  , B_GQ = 91, B_GT = 92;
constexpr uint32_t MT = 9216, A_ONES = 12 * SLOT + 3 * MT, A_CS = A_ONES + 2048, A_ST = A_CS + 1536;
constexpr uint32_t A_TL = MISC + 2048 + 808;
constexpr int S_V0 = R5 ? 7 : 11, S_V1 = R5 ? 9 : 7;
constexpr uint32_t K_SLOTS = 0x8697A8u, V_SLOTS = 0x97A869u;
constexpr int C_B = 0, C_DONE = 32, NCNT = 2;
constexpr uint32_t QX_SLOTS = NQ == 5 ? 0x43102u : 0x354021u;
constexpr uint32_t QW_SLOTS = R5 ? 0xA9786Au : 0xB76A98u;
constexpr uint32_t qx(int k) { return (QX_SLOTS >> (4 * k)) & 15u; }
constexpr uint32_t qw(int k) { return (QW_SLOTS >> (4 * k)) & 15u; }
constexpr uint32_t S_KVB = R5 ? 1 : 8, S_D0 = R5 ? 11 : (NQ == 5 ? 5 : 1), S_D1 = R5 ? 2 : (NQ == 5 ? 11 : 2);
constexpr uint32_t S_M3 = R5 ? 11 : 5;
constexpr int WQ0 = NQ == 5 ? 1 : 3;
constexpr uint32_t wo_slot_c(int i) { return i >= 9 ? wo_slot_c(i - 9) : (i == 7 ? S_D0 : (i == 8 ? S_D1 : (((i & 1) || i + WQ0 == 1) ? qx((i + WQ0) >> 1) : qw((i + WQ0) >> 1)))); }
constexpr uint64_t wo_slots() { uint64_t t = 0; for (int i = 0; i < 16; i++) t |= (uint64_t)wo_slot_c(i) << (4 * i); return t; }
constexpr uint64_t WO_SLOTS = wo_slots();
constexpr uint32_t A_SLOTS = 0xDC000u | (S_KVB << 8) | (qw(NQ - 1) << 4) | qx(NQ - 1);
constexpr uint32_t SX14 = qx(NQ - 2), SX15 = qx(NQ - 1), SXQ0 = qx(0);
#define WOD 2
#define PLC 3
#define RS0 0
#define POLLNS 150
#define MPROMO CU_TENSOR_MAP_L2_PROMOTION_L2_128B
#define MW0 0
#define PFILL 0
#define H2W (NQ - 3)
#define SV0 2
#define SV0A 14
#define SV0B 22
#define ASTE 2
#define PFS 1
#define PFTAB 0x0012222220000ull
#define HW 0
#define DPF 1
#define PROBE 0x8
#define OS1 0
#define YW 0
#define NOVAL 0
#define NDIR 1
#define I0 (2 + NDIR)
#define DW 0
#define NA 5
#define STAG 4
#define GOE 0
#define KEY1 0
#define HYB 0
#define FW 0
#define E1E 1
#define GATE 0
#define SVD 0
#define XPROMO CU_TENSOR_MAP_L2_PROMOTION_L2_128B
#define MC0 3
#define MX 0
#define OUTV 1
#define NP 0
#define FINCP 0
#define DNS 0
#define WOK 99
#define WOD1 2
#define MRED 1
#define MRW -1
#define ST 0
#define RW 0
#define SL2 0
#define CQ4 0
#define CQE 0
#define VOL 0
#define FMC 0
#define KO 0
#define QO 0
#define GPF 0
#define GPD 0
#define OH 0
#define R4E 0
#define WOP 3
#define WSP 0
#define SH2 0
#define KS 7
#define SQ 2
#define H2D 200
#define MRC 0
#define H2C 0
#define MRD 300
#define STP 0
#define TPNS 50
#define MFIN 0
#define MFD 300
#define SF 1
#define PH MFIN
#define RSL 0
#define OS3 4
#define PLP 2
#define PFNS2 200
#define MAP 2
#define RSNS 60
#define SVS 6
#define MC 7
#define QE 0
#define TMP 1
#define TMPW 4
#define DS 15
#define RL 0
#define EV 0
#define LQ 0
#define SPL 0
#define PHI2 1
#define E7 1
#define RF 1
#define RK 0
#define LE 1
#define SL7 0
#define XP 3
#define MS 0
constexpr int CON_REGS = 224, MOE_REGS = 40, PROD_REGS = 24;
constexpr uint32_t SPIN_MAX = 2000000;
constexpr uint32_t SENT = 0xFFFFFFFFu;

struct __align__(128) Scratch {
  uint4 o[NCTA * 2048];
  uint4 part[NCTA * 544];
  uint4 fin[8 * 640];
  float2 stats[SEQ];
  uint32_t key[SEQ];
  uint32_t cs[3 * DM];
  uint4 y[NCTA * 128];
  uint32_t h[56 * 256];
  uint32_t top[128];
  uint32_t cnt[NCNT * 32];
};
__device__ Scratch G;
#define TLS(th, i)
#define TLP_(i)
#define TLG(i)
#define TLDUMP()

__device__ __forceinline__ bool elect_one() {
  uint32_t p;
  asm volatile("{\n.reg .pred P;\nelect.sync _|P, 0xffffffff;\nselp.b32 %0, 1, 0, P;\n}" : "=r"(p));
  return p;
}
__device__ __forceinline__ void mbar_init(uint32_t b, uint32_t c) { asm volatile("mbarrier.init.shared::cta.b64 [%0], %1;" ::"r"(b), "r"(c) : "memory"); }
__device__ __forceinline__ void mbar_expect_tx(uint32_t b, uint32_t bytes) { asm volatile("mbarrier.arrive.expect_tx.shared::cta.b64 _, [%0], %1;" ::"r"(b), "r"(bytes) : "memory"); }
__device__ __forceinline__ void mbar_arrive(uint32_t b) { asm volatile("mbarrier.arrive.shared::cta.b64 _, [%0];" ::"r"(b) : "memory"); }
__device__ __forceinline__ void mbar_wait_b(uint32_t b, uint32_t parity) {
  asm volatile(
      "{\n.reg .pred p;\n.reg .u32 cnt;\nmov.u32 cnt, 0;\n"
      "LW:\nmbarrier.try_wait.parity.shared::cta.b64 p, [%0], %1;\n@p bra LD;\n"
      "add.u32 cnt, cnt, 1;\nsetp.lt.u32 p, cnt, 4000000;\n@p bra LW;\ntrap;\nLD:\n}" ::"r"(b), "r"(parity) : "memory");
}
__device__ __forceinline__ void mbar_wait(uint32_t b, uint32_t parity) {
  asm volatile("{\n.reg .pred p;\nLW:\nmbarrier.try_wait.parity.shared::cta.b64 p, [%0], %1;\n@!p bra LW;\n}" ::"r"(b), "r"(parity) : "memory");
}
__device__ __forceinline__ bool mbar_test(uint32_t b, uint32_t parity) {
  uint32_t r;
  asm volatile("{\n.reg .pred p;\nmbarrier.test_wait.parity.shared::cta.b64 p, [%1], %2;\nselp.b32 %0, 1, 0, p;\n}" : "=r"(r) : "r"(b), "r"(parity) : "memory");
  return r;
}
__device__ __forceinline__ uint32_t ev_arrive(uint32_t a) { uint32_t r; asm volatile("atom.shared.add.u32 %0, [%1], 1;" : "=r"(r) : "r"(a) : "memory"); return r; }
__device__ __forceinline__ void tma2d(uint32_t dst, const CUtensorMap* m, int c0, int c1, uint32_t bar) {
  asm volatile("cp.async.bulk.tensor.2d.shared::cluster.global.mbarrier::complete_tx::bytes [%0], [%1, {%3, %4}], [%2];" ::"r"(dst), "l"(m), "r"(bar), "r"(c0), "r"(c1) : "memory");
}
__device__ __forceinline__ void tma3d(uint32_t dst, const CUtensorMap* m, int c1, int c2, uint32_t bar) {
  asm volatile("cp.async.bulk.tensor.3d.shared::cluster.global.mbarrier::complete_tx::bytes [%0], [%1, {%3, %4, %5}], [%2];" ::"r"(dst), "l"(m), "r"(bar), "r"(0), "r"(c1), "r"(c2) : "memory");
}
__device__ __forceinline__ void tma3d_mc(uint32_t dst, const CUtensorMap* m, int c1, int c2, uint32_t bar) {
  asm volatile("cp.async.bulk.tensor.3d.shared::cluster.global.mbarrier::complete_tx::bytes.multicast::cluster [%0], [%1, {%3, %4, %5}], [%2], %6;" ::"r"(dst), "l"(m), "r"(bar), "r"(0), "r"(c1), "r"(c2), "h"((uint16_t)3) : "memory");
}
__device__ __forceinline__ void tma5d(uint32_t dst, const CUtensorMap* m, int c2, int c4, uint32_t bar, bool mc) {
  if (mc) asm volatile("cp.async.bulk.tensor.5d.shared::cluster.global.mbarrier::complete_tx::bytes.multicast::cluster [%0], [%1, {%3, %3, %4, %3, %5}], [%2], %6;" ::"r"(dst), "l"(m), "r"(bar), "r"(0), "r"(c2), "r"(c4), "h"((uint16_t)3) : "memory");
  else asm volatile("cp.async.bulk.tensor.5d.shared::cluster.global.mbarrier::complete_tx::bytes [%0], [%1, {%3, %3, %4, %3, %5}], [%2];" ::"r"(dst), "l"(m), "r"(bar), "r"(0), "r"(c2), "r"(c4) : "memory");
}
__device__ __forceinline__ void mbar_arrive_cta(uint32_t b, uint32_t cta) {
  asm volatile("{\n.reg .b32 ra;\nmapa.shared::cluster.u32 ra, %0, %1;\nmbarrier.arrive.shared::cluster.b64 _, [ra];\n}" ::"r"(b), "r"(cta) : "memory");
}
constexpr uint64_t POL_FIRST = 0x12F0000000000000ull;
__device__ __forceinline__ void tma2d_ef(uint32_t dst, const CUtensorMap* m, int c0, int c1, uint32_t bar) {
  asm volatile("cp.async.bulk.tensor.2d.shared::cluster.global.mbarrier::complete_tx::bytes.L2::cache_hint [%0], [%1, {%3, %4}], [%2], %5;" ::"r"(dst), "l"(m), "r"(bar), "r"(c0), "r"(c1), "l"(POL_FIRST) : "memory");
}
__device__ __forceinline__ void bulk_ld(uint32_t dst, const void* src, uint32_t bytes, uint32_t bar) {
  asm volatile("cp.async.bulk.shared::cluster.global.mbarrier::complete_tx::bytes [%0], [%1], %2, [%3];" ::"r"(dst), "l"(src), "r"(bytes), "r"(bar) : "memory");
}
__device__ __forceinline__ void bulk_ld_mc(uint32_t dst, const void* src, uint32_t bytes, uint32_t bar) {
  asm volatile("cp.async.bulk.shared::cluster.global.mbarrier::complete_tx::bytes.multicast::cluster [%0], [%1], %2, [%3], %4;" ::"r"(dst), "l"(src), "r"(bytes), "r"(bar), "h"((uint16_t)3) : "memory");
}
__device__ __forceinline__ void bulk_pf(const void* src, uint32_t bytes) { asm volatile("cp.async.bulk.prefetch.L2.global [%0], %1;" ::"l"(src), "r"(bytes) : "memory"); }
__device__ __forceinline__ void tma2d_pf(const CUtensorMap* m, int c0, int c1) {
  asm volatile("cp.async.bulk.prefetch.tensor.2d.L2.global [%0, {%1, %2}];" ::"l"(m), "r"(c0), "r"(c1) : "memory");
}
__device__ __forceinline__ void map_pf(const CUtensorMap* m) { asm volatile("prefetch.tensormap [%0];" ::"l"(m) : "memory"); }
__device__ __forceinline__ void line_pf(const void* p) { asm volatile("prefetch.global.L2 [%0];" ::"l"(p)); }
__device__ __forceinline__ void pf128(uint32_t dummy, const void* src) { asm volatile("cp.async.ca.shared.global.L2::128B [%0], [%1], 4;" ::"r"(dummy), "l"(src) : "memory"); }
__device__ __forceinline__ void pf256(uint32_t dummy, const void* src) { asm volatile("cp.async.ca.shared.global.L2::256B [%0], [%1], 4;" ::"r"(dummy), "l"(src) : "memory"); }
__device__ __forceinline__ void cp16x2(uint32_t dst, const void* src) {
  asm volatile("cp.async.cg.shared.global [%0], [%1], 16;\ncp.async.cg.shared.global [%0+4096], [%1+512], 16;" ::"r"(dst), "l"(src) : "memory");
}
constexpr uint32_t HI_SW128 = 0x40000000u | (1024 >> 4), HI_SW64 = 0x80000000u | (512 >> 4), HI_NOSW = 512 >> 4;
__device__ __forceinline__ uint64_t mkdesc(uint32_t lo, uint32_t hi) { uint64_t d; asm("mov.b64 %0, {%1, %2};" : "=l"(d) : "r"(lo), "r"(hi)); return d; }
__device__ __forceinline__ void wg_fence() { asm volatile("wgmma.fence.sync.aligned;" ::: "memory"); }
__device__ __forceinline__ void wg_commit() { asm volatile("wgmma.commit_group.sync.aligned;" ::: "memory"); }
template <int N> __device__ __forceinline__ void wg_wait() { asm volatile("wgmma.wait_group.sync.aligned %0;" ::"n"(N) : "memory"); }
template <int N> __device__ __forceinline__ void reg_fence(float (&a)[N]) {
#pragma unroll
  for (int i = 0; i < N; i++) asm volatile("" : "+f"(a[i])::"memory");
}
template <int ID, int N> __device__ __forceinline__ void bar_sync() { asm volatile("bar.sync %0, %1;" ::"n"(ID), "n"(N) : "memory"); }
__device__ __forceinline__ void fence_async_smem() { asm volatile("fence.proxy.async.shared::cta;" ::: "memory"); }
__device__ __forceinline__ void fence_async_gmem() { asm volatile("fence.proxy.async.global;" ::: "memory"); }
__device__ __forceinline__ uint32_t pack_bf16(float lo, float hi) { uint32_t r; asm("cvt.rn.bf16x2.f32 %0, %1, %2;" : "=r"(r) : "f"(hi), "f"(lo)); return r; }
__device__ __forceinline__ float bf_lo(uint32_t v) { return __uint_as_float(v << 16); }
__device__ __forceinline__ float bf_hi(uint32_t v) { return __uint_as_float(v & 0xFFFF0000u); }
__device__ __forceinline__ float bf_round(float v) { return bf_lo(pack_bf16(v, v)); }
__device__ __forceinline__ uint32_t bf_sub2(uint32_t a, uint32_t b) { uint32_t r; asm("sub.rn.bf16x2 %0, %1, %2;" : "=r"(r) : "r"(a), "r"(b)); return r; }
__device__ __forceinline__ float rcp(float v) { float r; asm("rcp.approx.ftz.f32 %0, %1;" : "=f"(r) : "f"(v)); return r; }
__device__ __forceinline__ float ex2(float v) { float r; asm("ex2.approx.ftz.f32 %0, %1;" : "=f"(r) : "f"(v)); return r; }
__device__ __forceinline__ float sigmoid(float v) { return rcp(1.f + ex2(v * -1.4426950408889634f)); }
__device__ __forceinline__ void stsm4(uint32_t a, uint32_t r0, uint32_t r1, uint32_t r2, uint32_t r3) {
  asm volatile("stmatrix.sync.aligned.m8n8.x4.shared.b16 [%0], {%1,%2,%3,%4};" ::"r"(a), "r"(r0), "r"(r1), "r"(r2), "r"(r3) : "memory");
}
__device__ __forceinline__ void stsm4t(uint32_t a, uint32_t r0, uint32_t r1, uint32_t r2, uint32_t r3) {
  asm volatile("stmatrix.sync.aligned.m8n8.x4.trans.shared.b16 [%0], {%1,%2,%3,%4};" ::"r"(a), "r"(r0), "r"(r1), "r"(r2), "r"(r3) : "memory");
}
__device__ __forceinline__ void ldsm4(uint32_t a, uint32_t& r0, uint32_t& r1, uint32_t& r2, uint32_t& r3) {
  asm volatile("ldmatrix.sync.aligned.m8n8.x4.shared.b16 {%0,%1,%2,%3}, [%4];" : "=r"(r0), "=r"(r1), "=r"(r2), "=r"(r3) : "r"(a) : "memory");
}
__device__ __forceinline__ uint32_t movmat(uint32_t a) { uint32_t d; asm volatile("movmatrix.sync.aligned.m8n8.trans.b16 %0, %1;" : "=r"(d) : "r"(a)); return d; }
__device__ __forceinline__ void sts_h(uint32_t a, float v) { asm volatile("st.shared.u16 [%0], %1;" ::"r"(a), "h"((uint16_t)pack_bf16(v, v)) : "memory"); }
__device__ __forceinline__ float2 lds_f2(uint32_t a) { float2 v; asm volatile("ld.shared.v2.f32 {%0,%1}, [%2];" : "=f"(v.x), "=f"(v.y) : "r"(a)); return v; }
__device__ __forceinline__ float lds_f(uint32_t a) { float v; asm volatile("ld.shared.f32 %0, [%1];" : "=f"(v) : "r"(a)); return v; }
__device__ __forceinline__ float4 lds_f4(uint32_t a) { float4 v; asm volatile("ld.shared.v4.f32 {%0,%1,%2,%3}, [%4];" : "=f"(v.x), "=f"(v.y), "=f"(v.z), "=f"(v.w) : "r"(a)); return v; }
__device__ __forceinline__ uint32_t lds_u(uint32_t a) { uint32_t v; asm volatile("ld.shared.u32 %0, [%1];" : "=r"(v) : "r"(a) : "memory"); return v; }
__device__ __forceinline__ uint4 lds_u4(uint32_t a) { uint4 v; asm volatile("ld.shared.v4.u32 {%0,%1,%2,%3}, [%4];" : "=r"(v.x), "=r"(v.y), "=r"(v.z), "=r"(v.w) : "r"(a) : "memory"); return v; }
__device__ __forceinline__ void sts_u(uint32_t a, uint32_t v) { asm volatile("st.shared.u32 [%0], %1;" ::"r"(a), "r"(v) : "memory"); }
__device__ __forceinline__ void sts_u4(uint32_t a, uint4 v) { asm volatile("st.shared.v4.u32 [%0], {%1,%2,%3,%4};" ::"r"(a), "r"(v.x), "r"(v.y), "r"(v.z), "r"(v.w) : "memory"); }
__device__ __forceinline__ uint4 ldx4(const void* p) { uint4 v; asm volatile("ld.relaxed.gpu.global.v4.u32 {%0,%1,%2,%3}, [%4];" : "=r"(v.x), "=r"(v.y), "=r"(v.z), "=r"(v.w) : "l"(p) : "memory"); return v; }
__device__ __forceinline__ uint2 ldx2(const void* p) { uint2 v; asm volatile("ld.relaxed.gpu.global.v2.u32 {%0,%1}, [%2];" : "=r"(v.x), "=r"(v.y) : "l"(p) : "memory"); return v; }
__device__ __forceinline__ uint32_t ldx1(const void* p) { uint32_t v; asm volatile("ld.relaxed.gpu.global.u32 %0, [%1];" : "=r"(v) : "l"(p) : "memory"); return v; }
__device__ __forceinline__ void stx4(void* p, uint32_t a, uint32_t b, uint32_t c, uint32_t d) {
  asm volatile("st.relaxed.gpu.global.v4.u32 [%0], {%1,%2,%3,%4};" ::"l"(p), "r"(a), "r"(b), "r"(c), "r"(d) : "memory");
}
__device__ __forceinline__ void stx2(void* p, uint32_t a, uint32_t b) { asm volatile("st.relaxed.gpu.global.v2.u32 [%0], {%1,%2};" ::"l"(p), "r"(a), "r"(b) : "memory"); }
__device__ __forceinline__ void stx1(void* p, uint32_t a) { asm volatile("st.relaxed.gpu.global.u32 [%0], %1;" ::"l"(p), "r"(a) : "memory"); }
__device__ __forceinline__ uint32_t umax4(uint4 v) { return max(max(v.x, v.y), max(v.z, v.w)); }
__device__ __forceinline__ uint32_t f2x(float f) { return min(__float_as_uint(f), 0xFFFFFFFEu); }
__device__ __forceinline__ void red4(float* p, float a, float b, float c, float d) { asm volatile("red.relaxed.gpu.global.add.v4.f32 [%0], {%1,%2,%3,%4};" ::"l"(p), "f"(a), "f"(b), "f"(c), "f"(d) : "memory"); }
__device__ __forceinline__ void cnt_arrive(int c) { asm volatile("red.release.gpu.global.add.u32 [%0], 1;" ::"l"(&G.cnt[c]) : "memory"); }
__device__ __forceinline__ void cnt_wait(int c, uint32_t target) {
#pragma unroll 1
  for (uint32_t it = 0; it < SPIN_MAX; it++) {
    uint32_t v;
    asm volatile("ld.acquire.gpu.global.u32 %0, [%1];" : "=r"(v) : "l"(&G.cnt[c]) : "memory");
    if (v >= target) break;
    __nanosleep(POLLNS);
  }
}
__device__ __forceinline__ void spin_cycles(uint32_t n) {
  uint32_t t0, t1;
  asm volatile("mov.u32 %0, %%clock;" : "=r"(t0));
#pragma unroll 1
  do { __nanosleep(20); asm volatile("mov.u32 %0, %%clock;" : "=r"(t1)); } while (t1 - t0 < n);
}
__device__ __forceinline__ void cnt_done() {
  uint32_t t;
  asm volatile("atom.acq_rel.gpu.global.add.u32 %0, [%1], 1;" : "=r"(t) : "l"(&G.cnt[C_DONE]) : "memory");
  if (t == NCTA + NSVC - 1) {
#pragma unroll 1
    for (int i = 0; i < NCNT; i++) G.cnt[i * 32] = 0;
  }
}
__device__ __forceinline__ float phi(float u, float rs, float rl) {
  float a = fmaf(u, rs, 1.000001f), e = ex2(u * rl), r;
  asm("add.sat.f32 %0, %1, 0f358637BD;" : "=f"(e) : "f"(e));
  asm("max.NaN.f32 %0, %1, %2;" : "=f"(r) : "f"(a), "f"(e));
  return r;
}

constexpr float LOG2E = 1.4426950408889634f, LN2 = 0.6931471805599453f;
__device__ __forceinline__ uint32_t phi2l(float u0, float rl0, float u1, float rl1) {
  const float l0 = u0 * rl0, l1 = u1 * rl1;
  float e0, e1;
  asm("{\n.reg .f32 t;\nabs.f32 t, %1;\nneg.f32 t, t;\nex2.approx.ftz.f32 %0, t;\n}" : "=f"(e0) : "f"(l0));
  asm("{\n.reg .f32 t;\nabs.f32 t, %1;\nneg.f32 t, t;\nex2.approx.ftz.f32 %0, t;\n}" : "=f"(e1) : "f"(l1));
  uint32_t e = pack_bf16(e0, e1), r;
  const uint32_t a = pack_bf16(fmaf(l0, LN2, 1.000001f), fmaf(l1, LN2, 1.000001f));
  asm("add.rn.bf16x2 %0, %0, %1;" : "+r"(e) : "r"(0x35863586u));
  asm("max.NaN.bf16x2 %0, %1, %2;" : "=r"(r) : "r"(a), "r"(e));
  return r;
}
template <bool V = false>
__device__ __forceinline__ uint32_t phi2(float u0, float rs0, float rl0, float u1, float rs1, float rl1) {
  float e0, e1;
  if (V) {
    asm volatile("{\n.reg .f32 t;\nabs.f32 t, %1;\nneg.f32 t, t;\nex2.approx.ftz.f32 %0, t;\n}" : "=f"(e0) : "f"(u0 * rl0));
    asm volatile("{\n.reg .f32 t;\nabs.f32 t, %1;\nneg.f32 t, t;\nex2.approx.ftz.f32 %0, t;\n}" : "=f"(e1) : "f"(u1 * rl1));
  } else {
    asm("{\n.reg .f32 t;\nabs.f32 t, %1;\nneg.f32 t, t;\nex2.approx.ftz.f32 %0, t;\n}" : "=f"(e0) : "f"(u0 * rl0));
    asm("{\n.reg .f32 t;\nabs.f32 t, %1;\nneg.f32 t, t;\nex2.approx.ftz.f32 %0, t;\n}" : "=f"(e1) : "f"(u1 * rl1));
  }
  uint32_t e = pack_bf16(e0, e1), r;
  const uint32_t a = pack_bf16(fmaf(u0, rs0, 1.000001f), fmaf(u1, rs1, 1.000001f));
  asm("add.rn.bf16x2 %0, %0, %1;" : "+r"(e) : "r"(0x35863586u));
  asm("max.NaN.bf16x2 %0, %1, %2;" : "=r"(r) : "r"(a), "r"(e));
  return r;
}

__device__ __forceinline__ int kstep1(int e, int hg) { return e < 14 ? (e < 2 * hg ? e : e + 2) : 2 * hg + e - 14; }
__device__ __forceinline__ int slab(int n, int hg) {
  return n + (((n + 7 - hg) * 37) >> 8);
}
__host__ __device__ constexpr uint32_t d_off(int i) { return i < 3 ? 12 * SLOT + (NR == 4 ? i : (i == 2 ? 0 : i + 1)) * MT : (i < 5 ? S_D0 * SLOT + (i - 3) * 8192 : S_D1 * SLOT + (i - 5) * 8192); }
__host__ __device__ constexpr uint32_t h_off(int i) { return i < 3 ? 12 * SLOT + i * MT + 8192 : (i < 5 ? A_ONES + (i - 3) * 1024 : MISC + M_MOE + (i - 5) * 1024); }
__device__ __forceinline__ uint32_t m_off(int r) { return r < 3 ? 12 * SLOT + r * MT : S_M3 * SLOT; }
__device__ __forceinline__ int x_slot(int e, int s) { return NQ == 5 ? (e < 14 ? s : e - 11) : (e < 13 ? s : 3 + s); }
__device__ __forceinline__ uint32_t wo_slot(int i) { return (uint32_t)(WO_SLOTS >> (4 * i)) & 15u; }

__global__ void __launch_bounds__(512, 1)
fused_kernel(const __nv_bfloat16* __restrict__ x, const __nv_bfloat16* __restrict__ wqkv, const __nv_bfloat16* __restrict__ wo,
             const __nv_bfloat16* __restrict__ wr, const __nv_bfloat16* __restrict__ wd, __nv_bfloat16* __restrict__ outp,
             const __nv_bfloat16* __restrict__ wg, const __nv_bfloat16* __restrict__ wu, const int by_sm,
             const __grid_constant__ CUtensorMap tmX, const __grid_constant__ CUtensorMap tmW,
             const __grid_constant__ CUtensorMap tmWo, const __grid_constant__ CUtensorMap tmOut,
             const __grid_constant__ CUtensorMap tmG, const __grid_constant__ CUtensorMap tmU,
             const __grid_constant__ CUtensorMap tmD, const __grid_constant__ CUtensorMap tmR,
             const __grid_constant__ CUtensorMap tmWp) {
  if (TMP && threadIdx.x == 32 * TMPW) { map_pf(&tmX); map_pf(&tmW); }
  extern __shared__ __align__(1024) uint8_t smem_raw[];
  const uint32_t sb = (uint32_t)__cvta_generic_to_shared(smem_raw);
  const uint32_t bars = sb + MISC + M_BAR;
  uint32_t smid;
  asm("mov.u32 %0, %%smid;" : "=r"(smid));
  const int tpc = smid >> 1;
  int cl = tpc + max(((tpc - 25) * 37) >> 8, 0);
  cl = tpc < 60 ? cl : cl - 1;
  cl = tpc < 62 ? cl : (tpc - 58) * 8;
  const int u = by_sm ? 2 * cl + (blockIdx.x & 1) : blockIdx.x;
  const int hg = (u >> 4) & 7, tb = u & 15;
  const int b = tb * 8 + hg;
  const int lane = threadIdx.x & 31;
  const int warp = __shfl_sync(~0u, threadIdx.x >> 5, 0);
  const int ltid = threadIdx.x;
  const int g = lane >> 2, t = lane & 3;
  const uint32_t d0 = (sb & 0x3FFFF) >> 4;
#define BAR(i) (bars + 8 * (i))
  TLS(0, 0);

  const int rank = u & 1;
  auto load_entry = [&](int e, int s) {
    const int k0 = kstep1(e, hg) * 64;
    mbar_expect_tx(BAR(B_FXQ + s), e < NF ? 2 * SLOT : SLOT);
    mbar_expect_tx(BAR(B_FKV + s), R5 ? SLOT : 2 * SLOT);
    if (R5 && e < 11) mbar_expect_tx(BAR(B_FV + s), SLOT);
    const uint32_t vb = R5 ? BAR(B_FV + s) : BAR(B_FKV + s);
    tma2d(sb + x_slot(e, s) * SLOT, &tmX, k0, tb * 128, BAR(B_FXQ + s));
    if (e < MC0 || !(MC & 1)) {
      if (e < NF) tma3d(sb + (3 + s) * SLOT, &tmW, k0, 2 * hg, BAR(B_FXQ + s));
      tma3d(sb + (6 + 2 * s) * SLOT, &tmW, k0, 16 + 2 * hg, BAR(B_FKV + s));
      tma3d(sb + (7 + 2 * s) * SLOT, &tmW, k0, 32 + 2 * hg, vb);
    } else {
      if (e < NF && (e & 1) == rank) tma3d_mc(sb + (3 + s) * SLOT, &tmW, k0, 2 * hg, BAR(B_FXQ + s));
      if (R5 && e >= 11) { if (rank == 0) tma3d_mc(sb + ((K_SLOTS >> (4 * (e - 10))) & 15u) * SLOT, &tmW, k0, 16 + 2 * hg, BAR(B_FKV + s)); }
      else tma3d_mc(sb + (6 + 2 * s + rank) * SLOT, &tmW, k0, 16 + 16 * rank + 2 * hg, rank ? vb : BAR(B_FKV + s));
    }
  };
  if (warp == FW && u < NCTA) {
    if (elect_one()) {
      mbar_init(BAR(B_FXQ), 1); mbar_init(BAR(B_FKV), 1);
      if (R5) mbar_init(BAR(B_FV), 1);
      load_entry(0, 0);
      asm volatile("fence.mbarrier_init.release.cluster;" ::: "memory");
      TLS(FW * 32, 61);
    }
    __syncwarp();
  }
  if (u >= NCTA) {
    const int j = u - NCTA;
    if (warp == 8 && elect_one()) {
#pragma unroll
      for (int i = 0; i < 13; i++) mbar_init(BAR(i), 1);
    }
    if (ltid < 64) sts_u4(sb + MISC + ltid * 16, make_uint4(0x3F803F80u, 0x3F803F80u, 0x3F803F80u, 0x3F803F80u));
    fence_async_smem();
    __syncthreads();
    if (warp < 4) {
      int s = 0, p = 0;
#pragma unroll 1
      for (int pass = 0; pass < 3; pass++) {
        float acc[4][4];
#pragma unroll
        for (int c = 0; c < 4; c++) acc[c][0] = acc[c][1] = acc[c][2] = acc[c][3] = 0.f;
#pragma unroll 1
        for (int k = 0; k < 16; k++) {
          mbar_wait(BAR(s), p);
          wg_fence();
#pragma unroll
          for (int c = 0; c < 4; c++)
#pragma unroll
            for (int kk = 0; kk < 4; kk++)
              wgmma_ss_n8<1, 0>(acc[c], mkdesc((d0 + s * 2048 + c * 512 + kk * 128) | (512u << 16), HI_SW128), mkdesc((d0 + (MISC >> 4)) | (1u << 16), HI_SW128));
          wg_commit();
          wg_wait<0>();
          if (ltid == 0) mbar_arrive(BAR(6 + s));
          if (++s == SVS) { s = 0; p ^= 1; }
        }
        uint32_t* pc = G.cs + (pass < 2 ? DM + pass * DM : 0) + j * 256 + warp * 16 + g;
#pragma unroll
        for (int c = 0; c < 4; c++) {
          reg_fence(acc[c]);
          const uint32_t v = __float_as_uint((t & 1) ? acc[c][2] : acc[c][0]);
          if (t < 2) stx1(pc + c * 64 + t * 8, v ? v : 0x80000000u);
        }
        TLS(0, 1 + pass);
      }
    } else if (warp >= 8 && j == 0) {
      const int wq = warp - 8;
      const uint32_t top = sb + MISC + 1024;
#pragma unroll 1
      for (uint32_t it = 0; it < SPIN_MAX; it++) {
        const uint4 v0 = ldx4(G.key + wq * 256 + lane * 4), v1 = ldx4(G.key + wq * 256 + 128 + lane * 4);
        uint32_t ok;
        asm volatile("{\n.reg .pred p, q;\nsetp.ne.u32 p, %1, 0;\nbar.red.and.pred q, 2, 256, p;\nselp.b32 %0, 1, 0, q;\n}" : "=r"(ok) : "r"((v0.x & v0.y & v0.z & v0.w & v1.x & v1.y & v1.z & v1.w) >> 27) : "memory");
        ok = __any_sync(~0u, ok);
        if (!ok && it) continue;
        TLS(256, 4);
        uint32_t np = 0u - (1u << 28), mine = 0;
#pragma unroll 1
        for (int r = 0; r < 8; r++) {
          const uint32_t m0 = __viaddmax_u32(v0.x, np, v0.y + np), m1 = __viaddmax_u32(v0.z, np, v0.w + np), m2 = __viaddmax_u32(v1.x, np, v1.y + np), m3 = __viaddmax_u32(v1.z, np, v1.w + np);
          np -= __reduce_max_sync(~0u, max(max(m0, m1), max(m2, m3)));
          if (g == r) mine = 0u - np;
        }
        if (t == 0) sts_u(top + (wq * 8 + g) * 4, mine);
        bar_sync<2, 256>();
        TLS(256, 5);
        int rk = 0;
#pragma unroll
        for (int i = 0; i < 4; i++) {
          const uint4 o = lds_u4(top + t * 64 + i * 16);
          rk += (o.x > mine) + (o.y > mine) + (o.z > mine) + (o.w > mine);
        }
        rk += __shfl_xor_sync(~0u, rk, 1);
        rk += __shfl_xor_sync(~0u, rk, 2);
        if (ok) { if (rk < 8) stx1(G.top + t * 32 + rk, mine); break; }
        __nanosleep(2500);
      }
      TLS(256, 7);
    } else if (warp == 4) {
      int s = 0, p = 1;
      if (SVD) __nanosleep(SVD);
#pragma unroll 1
      for (int i = 0; i < 48; i++) {
        mbar_wait(BAR(6 + s), p);
        if (j == 0 && i >= SV0A && i < SV0B) mbar_wait(BAR(s >= SV0 ? s - SV0 : s - SV0 + SVS), s >= SV0 ? p ^ 1 : p);
        if (elect_one()) {
          mbar_expect_tx(BAR(s), 2 * SLOT);
          const int ch = (i < 32 ? 16 + (i & 16) : 0) + j * 4, k0 = (i & 15) * 64;
          tma3d(sb + s * 2 * SLOT, &tmW, k0, ch, BAR(s));
          tma3d(sb + s * 2 * SLOT + SLOT, &tmW, k0, ch + 2, BAR(s));
        }
        if (++s == SVS) { s = 0; p ^= 1; }
      }
    }
    if (ltid == 0) cnt_wait(C_DONE, NCTA);
    __syncthreads();
    const uint4 zero = make_uint4(0, 0, 0, 0);
    if (ltid < 128) reinterpret_cast<uint4*>(G.key)[j * 128 + ltid] = zero;
    else if (ltid < 320) reinterpret_cast<uint4*>(G.cs)[j * 192 + ltid - 128] = zero;
    else if (ltid < 322) reinterpret_cast<uint4*>(G.top)[j * 8 + ltid - 320] = zero;
    if (ltid == 0) { cnt_done(); TLDUMP(); }
    return;
  }

  if (warp == 12) {
    if (elect_one()) {
#pragma unroll
      for (int i = 1; i < 7; i++) if (i != B_FKV) mbar_init(BAR(i), 1);
      if (R5) { mbar_init(BAR(B_FV + 1), 1); mbar_init(BAR(B_FV + 2), 1); }
      if (E1E) load_entry(1, 1);
      if (E1E == 2) {
        load_entry(2, 2);
        mbar_expect_tx(BAR(B_AST), 2 * SLOT + 2048);
        bulk_ld(sb + 12 * SLOT, x + (size_t)b * 16 * DM, 2 * SLOT, BAR(B_AST));
        bulk_ld(sb + MISC + M_MOE, wr, 2048, BAR(B_AST));
      }
      asm volatile("fence.mbarrier_init.release.cluster;" ::: "memory");
    }
  } else if (warp >= 13) {
    if (elect_one()) {
      if (warp == 15) {
#pragma unroll
        for (int i = B_FAUX; i < NBAR; i++) mbar_init(BAR(i), i < B_E || !MC ? 2 : 4);
        mbar_init(BAR(B_KV4), 4); mbar_init(BAR(B_MS), 2); mbar_init(BAR(B_GQ), 1); mbar_init(BAR(B_GT), 1);
        if (R5) { mbar_init(BAR(B_EK), 4); mbar_init(BAR(B_EK + 1), 4); mbar_init(BAR(B_EK + 2), 4); }
      } else {
#pragma unroll
        for (int i = 0; i < 23; i++) mbar_init(BAR((warp == 13 ? 7 : 30) + i), 1);
      }
      asm volatile("fence.mbarrier_init.release.cluster;" ::: "memory");
    }
  }
  __syncthreads();
  if (MC) asm volatile("barrier.cluster.arrive.relaxed.aligned;" ::: "memory");

  const bool unit = u < NUNIT;
  const int dcol = (u & 15) * 64, drow = (u >> 4) * 448;
  if (warp >= 12) {
    asm volatile("setmaxnreg.dec.sync.aligned.u32 %0;" ::"n"(PROD_REGS));
    if (MC && warp != 12) asm volatile("barrier.cluster.wait.aligned;" ::: "memory");
    if (warp == 12) {
      int s = E1E == 2 ? 0 : 1 + E1E, p = E1E == 2 ? 0 : 1, pn = 3;
#pragma unroll 1
      for (int e = 1 + E1E; e < 16; e++) {
        if (MC && e == MC0) asm volatile("barrier.cluster.wait.aligned;" ::: "memory");
        if (e == GATE) mbar_wait(BAR(B_FXQ), 0);
        if (R4E && R5 && e >= 11) mbar_wait(BAR(B_EK + (s == 2 ? 0 : s + 1)), e >= 14);
        else mbar_wait(BAR(B_E + s), p);
        if (elect_one()) {
          load_entry(e, s);
          if (NR == 4 && e == 11) mbar_arrive(BAR(B_ME + 3));
          if (E1E != 2 && e == ASTE) {
            mbar_expect_tx(BAR(B_AST), 2 * SLOT + 2048);
            bulk_ld(sb + 12 * SLOT, x + (size_t)b * 16 * DM, 2 * SLOT, BAR(B_AST));
            bulk_ld(sb + MISC + M_MOE, wr, 2048, BAR(B_AST));
          } else if (e >= 3) {
            if (WSP == 0) { if (e < 6) bulk_pf(wqkv + (size_t)((e - 2) * 256 + 2 * b) * 3 * DM, 2 * 3 * DM * 2); }
            else if (e < 9) bulk_pf(wqkv + (size_t)((e - 1) * 128 + b) * 3 * DM, 3 * DM * 2);
            if (WOP >= 0 && e >= WOP && e < WOP + 4) bulk_pf(wo + (size_t)((e - WOP) * 256 + 2 * b) * DM, 2 * DM * 2);
            if (NUNIT) {
#pragma unroll 1
              for (int i = GPF ? 0 : (PFTAB >> (4 * (e - 3))) & 15; i > 0; i--, pn++) {
                if (pn >= 16) { if (!(MX & 8)) tma2d_pf(&tmD, dcol, drow + (pn - 16) * 64); }
                else if (unit && !(MX & 2)) tma2d_pf(rank ? &tmU : &tmG, (u >> 1) * 64, pn * 64);
              }
            }
          }
        }
        if (R5 && e >= 11) {
          if (R4E) mbar_wait(BAR(B_E + (s == 2 ? 0 : s + 1)), ((e - 2) / 3) & 1);
          else mbar_wait(BAR(B_EK + (s == 2 ? 0 : s + 1)), e >= 14);
          if (elect_one()) {
            mbar_expect_tx(BAR(B_FV + s), SLOT);
            if (rank) tma3d_mc(sb + ((V_SLOTS >> (4 * (e - 10))) & 15u) * SLOT, &tmW, kstep1(e, hg) * 64, 32 + 2 * hg, BAR(B_FV + s));
          }
        }
        if (++s == 3) { s = 0; p ^= 1; }
      }
#pragma unroll 1
      for (int k = 0; k < NQ; k++) {
        if (k == 0) mbar_wait(BAR(B_E + 1), 0);
        if (k == 1) mbar_wait(BAR(B_EK + 2), 1);
        if (k == 2) mbar_wait(BAR(B_EK + 0), 0);
        if (k == 3) mbar_wait(BAR(B_STG), 0);
        if (k == 5) mbar_wait(BAR(B_EQ), 0);
        if (elect_one()) {
          const int k0 = kstep1(NF + k, hg) * 64;
          mbar_expect_tx(BAR(B_FQ + k), SLOT);
          if (!(MC & 2)) tma3d(sb + ((QW_SLOTS >> (4 * k)) & 15u) * SLOT, &tmW, k0, 2 * hg, BAR(B_FQ + k));
          else if ((k & 1) == rank) tma3d_mc(sb + ((QW_SLOTS >> (4 * k)) & 15u) * SLOT, &tmW, k0, 2 * hg, BAR(B_FQ + k));
        }
      }
#pragma unroll 1
      for (int i = 0; i < 16; i++) {
        mbar_wait(i < 7 ? BAR(B_EQ + ((i + WQ0) >> 1)) : (i < 9 ? BAR(B_DE) : BAR(B_EO + i - 9)), 0);
        if (i == WOK) mbar_wait(BAR(B_KVB), 0);
        mbar_wait(BAR(B_FWO + i - (i < WOK ? WOD1 : WOD)), 0);
        if (elect_one()) {
          mbar_expect_tx(BAR(B_FWO + i), SLOT);
#pragma unroll
          for (int hf = 0; hf < ((MC & 4) ? 1 : 2); hf++) {
            const int n = 2 * i + ((MC & 4) ? rank : hf), m = slab(n - 4, hg), hd = n < 4 ? 4 * hg + n : 4 * (m & 7) + (m >> 3);
            if (i < 2 + NDIR) tma5d(sb + wo_slot(i) * SLOT + (n & 1) * 8192, &tmWp, hd * 4, 2 * hg, BAR(B_FWO + i), MC & 4);
            else if (MC & 4) tma3d_mc(sb + wo_slot(i) * SLOT + rank * 8192, &tmWo, hd * 32, 2 * hg, BAR(B_FWO + i));
            else tma3d(sb + wo_slot(i) * SLOT + hf * 8192, &tmWo, hd * 32, 2 * hg, BAR(B_FWO + i));
          }
        }
      }
    } else if (warp == 13) {
      if (elect_one()) {
        map_pf(rank ? &tmU : &tmG); map_pf(&tmR); map_pf(&tmD); map_pf(&tmWo); map_pf(&tmWp); map_pf(&tmOut);
      }
      bar_sync<6, 64>();
      if (elect_one()) {
        cnt_wait(C_B, NCTA);
        fence_async_gmem();
        mbar_expect_tx(BAR(B_FAUX), 1024);
        bulk_ld(sb + A_ST, G.stats + tb * 128, 1024, BAR(B_FAUX));
      }
      __syncwarp();
      TLS(416, 68);
#pragma unroll 1
      for (int m = 1; m < 4; m++) {
        const int part = m == 3 ? 0 : m;
        uint4 c;
#pragma unroll 1
        for (uint32_t it = 0; it < SPIN_MAX; it++) {
          c = ldx4(G.cs + part * DM + hg * 128 + lane * 4);
          if (__all_sync(~0u, min(min(c.x, c.y), min(c.z, c.w)))) break;
          __nanosleep(POLLNS);
        }
        if (CQ4 && part == 0) {
          const uint32_t o = sb + A_CS + (lane >> 2) * 64 + (lane & 1) * 32 + ((lane >> 1) & 1) * 8;
          asm volatile("st.shared.v2.u32 [%0], {%1,%2};\nst.shared.v2.u32 [%0+16], {%3,%4};" ::"r"(o), "r"(c.x), "r"(c.y), "r"(c.z), "r"(c.w) : "memory");
        } else sts_u4(sb + A_CS + part * 512 + lane * 16, c);
        __syncwarp();
        if (m > 1 && lane == 0) mbar_arrive(BAR(m == 2 ? B_FAUX : B_CQ));
        TLS(416, 71 + m);
      }
      mbar_wait(BAR(B_XS), 1);
      if (elect_one()) asm volatile("red.relaxed.gpu.global.add.u32 [%0], 1;" ::"l"(&G.cnt[C_DONE]) : "memory");
    } else if (warp == 14) {
      const uint4 sent = make_uint4(SENT, SENT, SENT, SENT);
      uint4* ro = G.o + (tb * 32 + hg) * 512 + lane;
      uint4* rp = G.part + b * 544 + lane;
      if (RSL) bar_sync<5, 160>(); else mbar_wait(BAR(B_AST), 0);
#pragma unroll 1
      for (int i = RS0; i < 40; i++) {
        uint4* q = i < 32 ? ro + (i >> 3) * 4096 + (i & 7) * 64 : rp + (i - 32) * 64;
        q[0] = sent; q[32] = sent;
        __nanosleep(RSNS);
      }
      rp[512] = sent;
#pragma unroll
      for (int i = 0; i < 4; i++) G.y[u * 128 + i * 32 + lane] = sent;
      if (unit) reinterpret_cast<uint4*>(G.h)[u * 32 + lane] = sent;
      G.fin[hg * 640 + tb * 40 + lane] = sent;
      if (lane < 8) G.fin[hg * 640 + tb * 40 + 32 + lane] = sent;
      if (!RSL) bar_sync<5, 160>();
      __syncwarp();
      TLS(448, 67);
      if (lane == 0) cnt_arrive(C_B);
      __syncwarp();
      TLS(448, 32);
      asm volatile("bar.arrive 6, 64;" ::: "memory");
    } else {
      const uint32_t stg = sb + 12 * SLOT;
      auto load_a = [&](int n, int r) {
        mbar_expect_tx(BAR(B_MF + r), (MX & 2) ? 1024 : MT);
        if (!(MX & 2)) tma2d_ef(sb + m_off(r), rank ? &tmU : &tmG, (u >> 1) * 64, n * 64, BAR(B_MF + r));
      };
      mbar_wait(BAR(B_XS), 0);
      if (unit) {
#pragma unroll 1
        for (int i = 0; i < 3; i++) {
          if (elect_one()) load_a(i, i);
          __nanosleep(PFILL);
        }
      }
      uint32_t key;
#pragma unroll 1
      for (uint32_t it = 0; it < SPIN_MAX; it++) {
        key = ldx1(G.top + ((u >> 1) & 3) * 32 + (lane & 7));
        if (__all_sync(~0u, key)) break;
        __nanosleep(TPNS);
      }
      TLS(480, 66);
      if (lane < 8) sts_u(sb + MISC + M_IDX + lane * 4, key);
      __syncwarp();
      if (lane == 0) mbar_arrive(BAR(B_XS));
      if (unit) {
        int tok[8];
#pragma unroll
        for (int i = 0; i < 8; i++) tok[i] = ~__shfl_sync(~0u, key, i) & 2047;
        int r = 0, p = 0;
#pragma unroll 1
        for (int n = 0; n < 16; n++) {
          if (n >= 3) mbar_wait(BAR(B_ME + r), r == 3 ? p : p ^ 1);
          if (elect_one()) {
            if (n >= 3) load_a(n, r);
#pragma unroll
            for (int i = 0; i < 8; i++) tma2d(sb + m_off(r) + 8192 + i * 128, &tmR, n * 64, tok[i], BAR(B_MF + r));
          }
          if (++r == NR) { r = 0; p ^= 1; }
        }
      }
      if (NUNIT) {
        if (lane == 0) mbar_expect_tx(BAR(B_DF), (MX & 8) ? 0 : 7 * 8192);
#pragma unroll 1
        for (int i = 0; i < 7; i++) {
          if (NR == 4) {
            if (i >= 3) mbar_wait(i < 5 ? BAR(B_ME + 3) : (R5 ? BAR(B_EQ + 1) : BAR(B_STG)), 0);
            else if (unit) mbar_wait(BAR(B_ME + i), 1);
          } else {
            if (i >= 3) mbar_wait(BAR(B_EQ + ((i - 3) >> 1)), 0);
            else if (unit) mbar_wait(BAR(B_ME + (i == 2 ? 0 : i + 1)), i == 2);
          }
          if (!(MX & 8) && elect_one()) tma2d_ef(sb + d_off(i), &tmD, dcol, drow + i * 64, BAR(B_DF));
          if (DNS) __nanosleep(DNS);
        }
      }
    }
    if (warp == 14) {
      if (GPF && unit) {
        const __nv_bfloat16* wsrc = (rank ? wu : wg) + (size_t)lane * FF + (u >> 1) * 64;
        if (GPD) __nanosleep(GPD);
#pragma unroll 1
        for (int pn = 3; pn < 16; pn++) {
          pf128(sb + MISC + M_DUM, wsrc + (size_t)(pn * 64) * FF); pf128(sb + MISC + M_DUM, wsrc + (size_t)(pn * 64 + 32) * FF);
          __nanosleep(GPF);
        }
      }
      if (DPF && NUNIT && !(MX & 8)) {
        mbar_wait(DS ? BAR(B_MS) : (DPF == 1 ? BAR(B_FQ) : BAR(B_T0)), 0);
#pragma unroll 1
        for (int pf = 0; pf < 7; pf++) { pf256(sb + MISC + M_DUM, wd + (size_t)(drow + pf * 64 + rank * 32 + lane) * DM + (dcol & ~127)); __nanosleep(PFNS2); }
      }
      const uint32_t* src = reinterpret_cast<const uint32_t*>(G.part + ((lane >> 3) * 32 + hg) * 544 + 512) + tb * 8 + (lane & 7);
      mbar_wait(BAR(B_EQ + MRW), 0);
      if (MRC) spin_cycles(MRC); else if (MRD) __nanosleep(MRD);
      uint32_t z0, z1, z2, z3;
#pragma unroll 1
      for (uint32_t it = 0; it < SPIN_MAX; it++) {
        z0 = ldx1(src); z1 = ldx1(src + 8 * 2176); z2 = ldx1(src + 16 * 2176); z3 = ldx1(src + 24 * 2176);
        if (!__any_sync(~0u, max(max(z0, z1), max(z2, z3)) == SENT)) break;
      }
      if (MRED == 2 && elect_one()) mbar_arrive(BAR(B_ZOK));
      float zz = (__uint_as_float(z0) + __uint_as_float(z1)) + (__uint_as_float(z2) + __uint_as_float(z3));
      zz += __shfl_xor_sync(~0u, zz, 8);
      zz += __shfl_xor_sync(~0u, zz, 16);
      stx1(reinterpret_cast<uint32_t*>(G.fin + hg * 640) + (tb >> 2) * 640 + 512 + ((tb >> 1) & 1) * 64 + (lane & 1) * 32 + (tb & 1) * 16 + ((lane & 7) >> 1) * 4 + (lane >> 3),
           pack_bf16(zz, zz));
      TLS(448, 12);
    }
    if (!MFIN && (warp == 13 || warp == 14)) {
      mbar_wait(BAR(B_EQ + H2W), 0);
      if (H2C) spin_cycles(H2C); else if (H2D) __nanosleep(H2D);
#pragma unroll 1
      for (uint32_t it = 0; it < SPIN_MAX; it++) {
        if (warp == 14 && elect_one()) {
          mbar_expect_tx(BAR(B_FIN), 10240);
          if (FMC && MC && it == 0) bulk_ld_mc(sb + S_KVB * SLOT + rank * 5120, G.fin + hg * 640 + rank * 320, 5120, BAR(B_FIN));
          else bulk_ld(sb + S_KVB * SLOT, G.fin + hg * 640, 10240, BAR(B_FIN));
        }
        mbar_wait(BAR(B_FIN), it & 1);
        uint32_t m = 0;
#pragma unroll
        for (int i = 0; i < 10; i++) m = max(m, lds_u(sb + S_KVB * SLOT + (i * 64 + ltid - 416) * 16 + (g >> 1) * 4));
        uint32_t bad;
        asm volatile("{\n.reg .pred p, q;\nsetp.eq.u32 p, %1, 0xFFFFFFFF;\nbar.red.or.pred q, 7, 64, p;\nselp.b32 %0, 1, 0, q;\n}" : "=r"(bad) : "r"(m) : "memory");
        if (!__any_sync(~0u, bad)) break;
      }
      if (warp == 14 && elect_one()) mbar_arrive(BAR(B_KVB));
      TLS(448, 14);
    }
    if (PH && (warp == 13 || warp == 14)) {
      bar_sync<3, 192>();
      mbar_wait(BAR(B_STG), 0);
#pragma unroll 1
      for (uint32_t it = 0; NUNIT && it < SPIN_MAX; it++) {
        if (elect_one()) {
          const uint32_t* ph = G.h + (u >> 4) * 7 * 256;
          if (warp == 13) { mbar_expect_tx(BAR(B_HF), 7168); bulk_ld(sb + h_off(3), ph + 768, 2048, BAR(B_HF)); bulk_ld(sb + h_off(5), ph + 1280, 2048, BAR(B_HF)); }
          else { bulk_ld(sb + h_off(0), ph, 1024, BAR(B_HF)); bulk_ld(sb + h_off(1), ph + 256, 1024, BAR(B_HF)); bulk_ld(sb + h_off(2), ph + 512, 1024, BAR(B_HF)); }
        }
        mbar_wait(BAR(B_HF), it & 1);
        uint32_t m = 0;
#pragma unroll
        for (int i = 0; i < 7; i++) m = max(m, lds_u(sb + h_off(i) + (ltid - 416) * 16 + (g >> 1) * 4));
        uint32_t bad;
        asm volatile("{\n.reg .pred p, q;\nsetp.eq.u32 p, %1, 0xFFFFFFFF;\nbar.red.or.pred q, 7, 64, p;\nselp.b32 %0, 1, 0, q;\n}" : "=r"(bad) : "r"(m) : "memory");
        if (!__any_sync(~0u, bad)) break;
        __nanosleep(POLLNS);
      }
      if (warp == 14 && elect_one()) mbar_arrive(BAR(B_KVB));
    }
    __syncwarp();
    if (warp >= 13) {
      const char* og = reinterpret_cast<const char*>(G.o + tb * 16384);
      auto probe = [&](uint32_t m) {
        const char* p = og + m * 8192u + (lane & 15) * 512 + 496;
#pragma unroll 1
        for (uint32_t it = 0; it < SPIN_MAX; it++)
          if (!__any_sync(~0u, ldx1(p) == SENT)) break;
      };
      if (warp == 15) {
        int r = 0, p = 1;
        mbar_wait(BAR(B_EAUX), 0);
#pragma unroll 1
        for (int i = I0; i < 16; i++) {
          const uint32_t dst = sb + ((A_SLOTS >> (4 * r)) & 15u) * SLOT, m0 = slab(2 * i - 4, hg), m1 = slab(2 * i - 3, hg);
          if (i == I0 + 3) mbar_wait(BAR(B_DE), 0);
          mbar_wait(BAR(B_EA + r), p);
          if ((PROBE >> i) & 1) probe(lane < 16 ? m0 : m1);
          if (elect_one()) {
            mbar_expect_tx(BAR(B_AF + r), SLOT);
            bulk_ld(dst, og + m0 * 8192u, 8192, BAR(B_AF + r)); bulk_ld(dst + 8192, og + m1 * 8192u, 8192, BAR(B_AF + r));
          }
          if (++r == NA) { r = 0; p ^= 1; }
        }
      } else {
        const uint32_t lo = lane * 32 + g * 4, hb = sb + (warp - 13) * 8192;
        uint32_t ph = 0;
        int r = 0, p = 0;
#pragma unroll 1
        for (int i = I0; i < 16; i++) {
          const uint32_t mine = hb + ((A_SLOTS >> (4 * r)) & 15u) * SLOT;
          auto bad = [&]() {
            uint32_t v[8];
#pragma unroll
            for (int j = 0; j < 8; j++) v[j] = lds_u(mine + lo + j * 1024);
            return __any_sync(~0u, max(max(max(v[0], v[1]), max(v[2], v[3])), max(max(v[4], v[5]), max(v[6], v[7]))) == SENT);
          };
          mbar_wait(BAR(B_AF + r), p);
          if (!NOVAL && bad()) {
            const uint32_t m = slab(2 * i - 17 + warp, hg);
#pragma unroll 1
            for (uint32_t it = 0; it < 64; it++) {
              probe(m);
              if (elect_one()) { mbar_expect_tx(BAR(B_AR + warp - 13), 8192); bulk_ld(mine, og + m * 8192u, 8192, BAR(B_AR + warp - 13)); }
              mbar_wait(BAR(B_AR + warp - 13), ph);
              ph ^= 1;
              if (!bad()) break;
            }
          }
          if (elect_one()) mbar_arrive(BAR(B_VAL + r));
          if (++r == NA) { r = 0; p ^= 1; }
        }
      }
    }
  } else if (warp >= 8) {
    asm volatile("setmaxnreg.dec.sync.aligned.u32 %0;" ::"n"(MOE_REGS));
    if (MC) asm volatile("barrier.cluster.wait.aligned;" ::: "memory");
    const int aw = warp - 8;
    const uint32_t mbuf = sb + MISC + M_MOE, stg = sb + 12 * SLOT;
    mbar_wait(BAR(B_AST), 0);
    TLS(288, 64);
    {
      float v[16];
#pragma unroll
      for (int r = 0; r < 16; r++) v[r] = 0.f;
      const uint32_t base = stg + aw * 4 * 2048 + lane * 8;
#pragma unroll 1
      for (int c = 0; c < 8; c++) {
        const float2 w2 = lds_f2(mbuf + c * 256 + lane * 8);
        const float w[4] = {bf_lo(__float_as_uint(w2.x)), bf_hi(__float_as_uint(w2.x)), bf_lo(__float_as_uint(w2.y)), bf_hi(__float_as_uint(w2.y))};
        v[12] += (w[0] + w[1]) + (w[2] + w[3]);
#pragma unroll
        for (int r = 0; r < 4; r++) {
          const float2 x2 = lds_f2(base + r * 2048 + c * 256);
#pragma unroll
          for (int e = 0; e < 2; e++) {
            const uint32_t xx = __float_as_uint(e ? x2.y : x2.x);
            const float lo = bf_lo(xx), hi = bf_hi(xx);
            v[r] += lo; v[4 + r] = fmaf(lo, lo, v[4 + r]); v[8 + r] = fmaf(lo, w[2 * e], v[8 + r]);
            v[r] += hi; v[4 + r] = fmaf(hi, hi, v[4 + r]); v[8 + r] = fmaf(hi, w[2 * e + 1], v[8 + r]);
          }
        }
      }
#pragma unroll
      for (int l = 0; l < 4; l++) {
        const int n = 8 >> l;
        const bool up = lane & (2 * n);
#pragma unroll
        for (int r = 0; r < 8; r++) {
          if (r < n) { const float a = v[r], c = v[n + r]; v[r] = (up ? c : a) + __shfl_xor_sync(~0u, up ? a : c, 2 * n); }
        }
      }
      v[0] += __shfl_xor_sync(~0u, v[0], 1);
      const float sx = __shfl_sync(~0u, v[0], 2 * t), sq = __shfl_sync(~0u, v[0], 8 + 2 * t), sw = __shfl_sync(~0u, v[0], 16 + 2 * t), ws = __shfl_sync(~0u, v[0], 24);
      if (lane < 4) {
        const int row = b * 16 + aw * 4 + lane;
        const float mean = sx * (1.f / DM);
        const float var = fmaxf(fmaf(-mean, mean, sq * (1.f / DM)), 0.f);
        float sd;
        asm("sqrt.approx.ftz.f32 %0, %1;" : "=f"(sd) : "f"(bf_round(bf_round(var) + 1e-5f)));
        const float rstd = rcp(bf_round(sd));
        const float mb = bf_round(mean);
        uint32_t rb = pack_bf16(fmaf(-mb, ws, sw) * rstd, 0.f) & 0xFFFFu;
        rb = (rb & 0x8000u) ? (~rb & 0xFFFFu) : (rb | 0x8000u);
        const uint32_t key = (1u << 27) | (rb << 11) | (uint32_t)(2047 - row);
        if (KEY1) sts_u(sb + MISC + M_KEY + (aw * 4 + lane) * 4, key); else stx1(G.key + row, key);
        G.stats[row] = make_float2(mb, SL2 ? rstd * LOG2E : rstd);
      }
    }
    bar_sync<2, 128>();
    if (KEY1 && ltid < 272) stx1(G.key + b * 16 + lane, lds_u(sb + MISC + M_KEY + lane * 4));
    TLS(288, 65);
    sts_u4(sb + A_ONES + (ltid - 256) * 16, make_uint4(0x3F803F80u, 0x3F803F80u, 0x3F803F80u, 0x3F803F80u));
    fence_async_smem();
    asm volatile("bar.arrive 5, 160;" ::: "memory");
    if (ltid == 256) { if (unit && rank == 0) mbar_expect_tx(BAR(B_UP), 2048); mbar_arrive(BAR(B_XS)); }
    bar_sync<2, 128>();
    mbar_wait(BAR(B_XS), 1);
    TLS(288, 70);
    if (NUNIT) {
      if (unit) {
        int r = 0, p = 0;
        uint32_t rel = 0;
        float acc[8];
        uint2 s0, s1;
#pragma unroll
        for (int i = 0; i < 8; i++) acc[i] = 0.f;
        if (MS == 16) mbar_wait(BAR(B_T0), 0); else if (MS) mbar_wait(BAR(B_MS), 0);
#pragma unroll 1
        for (int n = 0; n < 16; n++) {
          if (n == 15) {
            mbar_wait(BAR(B_FAUX), 0);
            s0 = ldx2(G.stats + (~lds_u(sb + MISC + M_IDX + t * 8) & 2047)); s1 = ldx2(G.stats + (~lds_u(sb + MISC + M_IDX + t * 8 + 4) & 2047));
            if (SL2) { s0.y = __float_as_uint(__uint_as_float(s0.y) * LN2); s1.y = __float_as_uint(__uint_as_float(s1.y) * LN2); }
          }
          mbar_wait(BAR(B_MF + r), p);
          if (!(n & 3)) TLS(288, 56 + (n >> 2));
          const uint32_t mo = m_off(r) >> 4, da = (d0 + mo) | (512u << 16), db = (d0 + mo + 512) | (1u << 16);
          const uint32_t hb = 0x40000000u | ((A_ONES >> 4) - 512 - mo);
          wg_fence();
#pragma unroll
          for (int kk = 0; kk < ((MX & 1) ? 1 : 4); kk++) wgmma_ss_n16<1, 0>(acc, mkdesc(da + kk * 128, HI_SW128), mkdesc(db + kk * 2, hb));
          wg_commit();
          wg_wait<1>();
          if (n > 0 && !rel && ltid == 256) mbar_arrive(BAR(B_ME + (r == 0 ? NR - 1 : r - 1)));
          rel = 0;
          const int r0 = r;
          if (++r == NR) { r = 0; p ^= 1; }
        }
        wg_wait<0>();
        reg_fence(acc);
        {
          if (!MW0 && !rel && ltid == 256) mbar_arrive(BAR(B_ME + 15 % NR));
          TLS(288, 71);
          const float v0 = bf_round(fmaf(-__uint_as_float(s0.x), acc[4], acc[0]) * __uint_as_float(s0.y));
          const float v1 = bf_round(fmaf(-__uint_as_float(s1.x), acc[4], acc[1]) * __uint_as_float(s1.y));
          const float v2 = bf_round(fmaf(-__uint_as_float(s0.x), acc[6], acc[2]) * __uint_as_float(s0.y));
          const float v3 = bf_round(fmaf(-__uint_as_float(s1.x), acc[6], acc[3]) * __uint_as_float(s1.y));
          if (rank) {
            asm volatile("{\n.reg .b32 ra, rb;\nmapa.shared::cluster.u32 ra, %0, 0;\nmapa.shared::cluster.u32 rb, %1, 0;\n"
                         "st.async.weak.shared::cluster.mbarrier::complete_tx::bytes.v4.f32 [ra], {%2, %3, %4, %5}, [rb];\n}"
                         ::"r"(mbuf + (ltid - 256) * 16), "r"(BAR(B_UP)), "f"(v0), "f"(v1), "f"(v2), "f"(v3) : "memory");
          } else {
            const float g0 = bf_round(v0 * sigmoid(v0)), g1 = bf_round(v1 * sigmoid(v1)), g2 = bf_round(v2 * sigmoid(v2)), g3 = bf_round(v3 * sigmoid(v3));
            mbar_wait(BAR(B_UP), 0);
            const uint4 uu = lds_u4(mbuf + (ltid - 256) * 16);
            const uint32_t h0 = movmat(pack_bf16(g0 * __uint_as_float(uu.x), g1 * __uint_as_float(uu.y)));
            const uint32_t h1 = movmat(pack_bf16(g2 * __uint_as_float(uu.z), g3 * __uint_as_float(uu.w)));
            uint32_t* ph = G.h + (u >> 1) * 256 + g * 32 + t;
            stx1(ph + ((2 * aw) ^ g) * 4, h0); stx1(ph + ((2 * aw + 1) ^ g) * 4, h1);
          }
          TLS(288, 60);
        }
      }
    }
    if (PH) asm volatile("bar.arrive 3, 192;" ::: "memory");
    {
      const int wd_ = ltid & 63;
      const uint32_t* src = reinterpret_cast<const uint32_t*>(G.part + hg * 544 + (aw >> 1) * 256 + tb * 16) + wd_;
      mbar_wait(MRED == 2 ? BAR(B_ZOK) : BAR(B_EQ + MRW), 0);
      if (MRC) spin_cycles(MRC); else if (MRD) __nanosleep(MRD);
      TLS(256, 48);
      uint32_t v[16];
#pragma unroll 1
      for (uint32_t it = 0; it < SPIN_MAX; it++) {
        uint32_t m = 0;
#pragma unroll
        for (int i = 0; i < 16; i++) v[i] = ldx1(src + i * 8 * 2176);
#pragma unroll
        for (int i = 0; i < 16; i++) m = max(m, v[i]);
        if (!__any_sync(~0u, m == SENT)) break;
      }
      TLS(256, 55);
      float lo[4], hi[4];
#pragma unroll
      for (int i = 0; i < 4; i++) {
        lo[i] = (bf_lo(v[4 * i]) + bf_lo(v[4 * i + 1])) + (bf_lo(v[4 * i + 2]) + bf_lo(v[4 * i + 3]));
        hi[i] = (bf_hi(v[4 * i]) + bf_hi(v[4 * i + 1])) + (bf_hi(v[4 * i + 2]) + bf_hi(v[4 * i + 3]));
      }
      stx1(reinterpret_cast<uint32_t*>(G.fin + hg * 640) + (tb >> 2) * 640 + ((tb >> 1) & 1) * 64 + (tb & 1) * 16 + (aw >> 1) * 32 + ((wd_ >> 2) & 3) * 128 + (wd_ >> 4) * 4 + (wd_ & 3),
           pack_bf16((lo[0] + lo[1]) + (lo[2] + lo[3]), (hi[0] + hi[1]) + (hi[2] + hi[3])));
      TLS(256, 5);
    }
    if (NUNIT) {
      mbar_wait(BAR(B_STG), 0);
      bar_sync<2, 128>();
      if (HW) __nanosleep(HW);
#pragma unroll 1
      for (uint32_t it = 0; it < SPIN_MAX; it++) {
        if (elect_one()) {
          const uint32_t* ph = G.h + (u >> 4) * 7 * 256;
          if (aw == 3) { mbar_expect_tx(BAR(B_HF), 7168); bulk_ld(sb + h_off(3), ph + 768, 2048, BAR(B_HF)); bulk_ld(sb + h_off(5), ph + 1280, 2048, BAR(B_HF)); }
          else bulk_ld(stg + aw * MT + 8192, ph + aw * 256, 1024, BAR(B_HF));
        }
        mbar_wait(BAR(B_HF), it & 1);
        const uint32_t o = (ltid & 63) * 16 + (g >> 1) * 4, o2 = o + (aw >> 1) * 1024;
        const uint32_t m = max(max(lds_u(sb + h_off(0) + (aw >> 1) * MT + o), lds_u(sb + h_off(2) + o)), max(lds_u(sb + h_off(3) + o2), lds_u(sb + h_off(5) + o2)));
        uint32_t bad;
        asm volatile("{\n.reg .pred p, q;\nsetp.eq.u32 p, %1, 0xFFFFFFFF;\nbar.red.or.pred q, 2, 128, p;\nselp.b32 %0, 1, 0, q;\n}" : "=r"(bad) : "r"(m) : "memory");
        if (!__any_sync(~0u, bad)) break;
        __nanosleep(POLLNS);
      }
      TLS(288, 62);
      float acc[4] = {0.f, 0.f, 0.f, 0.f};
      mbar_wait(BAR(B_DF), 0);
      TLS(288, 63);
#pragma unroll 1
      for (int i = 0; i < 7; i++) {
        const uint32_t da = (d0 + (d_off(i) >> 4)) | (512u << 16), db = (d0 + (h_off(i) >> 4)) | (1u << 16);
        wg_fence();
#pragma unroll
        for (int kk = 0; kk < ((MX & 4) ? 1 : 4); kk++) wgmma_ss_n8<1, 0>(acc, mkdesc(da + kk * 128, HI_SW128), mkdesc(db + kk * 2, HI_SW128));
        wg_commit();
      }
      wg_wait<0>();
      reg_fence(acc);
      if (ltid < 258) { if (MC) mbar_arrive_cta(BAR(B_DE), ltid & 1); else mbar_arrive(BAR(B_DE)); }
      {
        uint32_t* py = reinterpret_cast<uint32_t*>(G.y) + u * 512 + t * 128 + aw * 16 + g;
        stx1(py, f2x(acc[0])); stx1(py + 64, f2x(acc[1])); stx1(py + 8, f2x(acc[2])); stx1(py + 72, f2x(acc[3]));
      }
      TLS(288, 69);
      const uint32_t key = lds_u(sb + MISC + M_IDX + (lane & 7) * 4);
      uint32_t rb = (key >> 11) & 0xFFFFu;
      rb = (rb & 0x8000u) ? (rb & 0x7FFFu) : (~rb & 0xFFFFu);
      const float sg = bf_round(sigmoid(__uint_as_float(rb << 16)));
      uint32_t hits = __ballot_sync(~0u, ((~key >> 7) & 15) == tb) & 255u;
      const uint32_t* py = reinterpret_cast<const uint32_t*>(G.y) + (2 * hg + (aw >> 1)) * 512 + (ltid & 63);
      if (hits) {
        sts_u4(mbuf + (ltid - 256) * 16, make_uint4(0, 0, 0, 0));
        bar_sync<2, 128>();
        if (YW >= 0) mbar_wait(BAR(B_EO + YW), 0); else if (YW == -2) mbar_wait(BAR(B_EAUX), 0);
      }
#pragma unroll 1
      while (hits) {
        const int n0 = __ffs(hits) - 1;
        hits &= hits - 1;
        const int n1 = hits ? __ffs(hits) - 1 : n0;
        hits &= hits - 1;
        uint32_t v[16];
#pragma unroll 1
        for (uint32_t it = 0; it < SPIN_MAX; it++) {
          uint32_t m = 0;
#pragma unroll
          for (int i = 0; i < 8; i++) { v[i] = ldx1(py + n0 * 64 + i * 8192); v[8 + i] = ldx1(py + n1 * 64 + i * 8192); }
#pragma unroll
          for (int i = 0; i < 16; i++) m = max(m, v[i]);
          if (!__any_sync(~0u, m == SENT)) break;
          __nanosleep(POLLNS);
        }
#pragma unroll
        for (int e = 0; e < 2; e++) {
          const uint32_t* w8 = v + 8 * e;
          const float y = ((__uint_as_float(w8[0]) + __uint_as_float(w8[1])) + (__uint_as_float(w8[2]) + __uint_as_float(w8[3]))) +
                          ((__uint_as_float(w8[4]) + __uint_as_float(w8[5])) + (__uint_as_float(w8[6]) + __uint_as_float(w8[7])));
          const int n = e ? n1 : n0;
          sts_h(mbuf + (aw >> 1) * 1024 + n * 128 + ((((ltid >> 3) & 7) ^ n) << 4) + (lane & 7) * 2, bf_round(y) * __shfl_sync(~0u, sg, n));
        }
      }
    }
    if (!NUNIT && ltid < 258) mbar_arrive(BAR(B_DE));
    fence_async_smem();
    bar_sync<2, 128>();
    TLS(288, 33);
    if (ltid == 288) mbar_arrive(BAR(B_MOE));
  } else {
    asm volatile("setmaxnreg.inc.sync.aligned.u32 %0;" ::"n"(CON_REGS));
    if (MC) asm volatile("barrier.cluster.wait.aligned;" ::: "memory");
    const int w = warp >> 2, wq = warp & 3, tid = ltid;
    const bool lead = (tid & 127) == 0;
    const uint32_t dA = (d0 + w * 512) | (1u << 16);
    const uint32_t dB = d0 | (512u << 16);
    auto release = [&](int bar) { if (lead) mbar_arrive(BAR(bar)); };
    auto release2 = [&](int bar) {
      if (MC) { if ((tid & 127) < 2) mbar_arrive_cta(BAR(bar), tid & 1); } else release(bar);
    };
    float aq[64], ak[64], av[64];
#pragma unroll
    for (int i = 0; i < 64; i++) aq[i] = ak[i] = av[i] = 0.f;
    auto q_step = [&](uint32_t bar, int p, uint32_t xs, uint32_t qs) {
      mbar_wait_b(bar, p);
      wg_fence();
#pragma unroll
      for (int kk = 0; kk < 4; kk++)
        wgmma_ss_n128<0, 1>(aq, mkdesc(dA + xs * 1024 + kk * 2, HI_SW128), mkdesc(dB + qs * 1024 + kk * 128, HI_SW128));
      wg_commit();
    };
    const uint32_t dT = dB + w * 512, dX = d0 | (1u << 16);
    auto t_step = [&](float (&a)[64], uint32_t ws, uint32_t xs) {
      wg_fence();
#pragma unroll
      for (int kk = 0; kk < 4; kk++)
        wgmma_ss_n128<1, 0>(a, mkdesc(dT + ws * 1024 + kk * 128, HI_SW128), mkdesc(dX + xs * 1024 + kk * 2, HI_SW128));
      wg_commit();
    };
    {
      int s = 0, p = 0, sp = 2;
#pragma unroll 1
      for (int e = 0; e < NF; e++) {
        TLS(0, 16 + e);
        if (((MS && MS < NF) || (DS && DS < NF)) && e == (MS ? MS : DS)) release(B_MS);
        q_step(BAR(B_FXQ + s), p, s, 3 + s);
        wg_wait<1>();
        if (e > 0) release2(B_E + sp);
        mbar_wait(BAR(B_FKV + s), p);
        t_step(ak, 6 + 2 * s, s);
        if (R5) mbar_wait(BAR(B_FV + s), p);
        t_step(av, 7 + 2 * s, s);
        if (R5 && e == NF - 1) { wg_wait<1>(); release2(B_EK + s); }
        sp = s;
        if (++s == 3) { s = 0; p ^= 1; }
      }
#pragma unroll 1
      for (int e = NF; e < 16; e++) {
        TLS(0, 16 + e);
        if (((MS >= NF && MS < 16) || DS >= NF) && e == (MS ? MS : DS)) release(B_MS);
        if (ST && e == 16 - ST && w == 1) mbar_wait(BAR(B_GT), 0);
        mbar_wait(BAR(B_FXQ + s), p);
        mbar_wait(BAR(B_FKV + s), p);
        t_step(ak, R5 ? (K_SLOTS >> (4 * (e - 10))) & 15u : 6 + 2 * s, x_slot(e, s));
        wg_wait<1>();
        release2(B_E + sp);
        if (R5) mbar_wait(BAR(B_FV + s), p);
        t_step(av, R5 ? (V_SLOTS >> (4 * (e - 10))) & 15u : 7 + 2 * s, x_slot(e, s));
        if (ST && e == 15 && tid == 0) mbar_arrive(BAR(B_GT));
        if (R5) { wg_wait<1>(); release2(B_EK + s); }
        sp = s;
        if (++s == 3) { s = 0; p ^= 1; }
      }
    }
    const uint32_t aux = sb;
    mbar_wait(BAR(B_FAUX), 0);
    const int row0 = w * 64 + wq * 16 + g;
    const float ck0 = lds_f(aux + A_CS + 512 + row0 * 4), ck1 = lds_f(aux + A_CS + 512 + (row0 + 8) * 4);
    const float cv0 = lds_f(aux + A_CS + 1024 + row0 * 4), cv1 = lds_f(aux + A_CS + 1024 + (row0 + 8) * 4);
    const uint32_t moff = (uint32_t)(w * 64 + wq * 16 + (lane & 15)) * 128 + (((lane >> 4) ^ (lane & 7)) << 4);
    const uint32_t sta = aux + A_ST + t * 16;
    float kvp[36], ao[64];
    uint32_t xr[32];
    float nm0, nm1, rs0, rs1, rl0, rl1;
    auto row_stats = [&]() {
      const float2 st0 = lds_f2(aux + A_ST + row0 * 8), st1 = lds_f2(aux + A_ST + (row0 + 8) * 8);
      nm0 = -st0.x; nm1 = -st1.x;
      if (SL2) { rl0 = st0.y; rl1 = st1.y; rs0 = rl0 * LN2; rs1 = rl1 * LN2; }
      else { rs0 = st0.y; rs1 = st1.y; rl0 = rs0 * LOG2E; rl1 = rs1 * LOG2E; }
    };
    auto ld_x = [&]() {
#pragma unroll
      for (int j = 0; j < 16; j += 2) ldsm4(sb + (j < 8 ? SX14 : SX15) * SLOT + (moff ^ ((j & 7) << 4)), xr[2 * j], xr[2 * j + 1], xr[2 * j + 2], xr[2 * j + 3]);
    };
    auto resid = [&]() {
      const float c0 = 1.f + rs0, c1 = 1.f + rs1, e0 = nm0 * rs0, e1 = nm1 * rs1;
#pragma unroll
      for (int j = 0; j < 16; j++) {
        ao[4 * j + 0] = fmaf(bf_lo(xr[2 * j]), c0, e0); ao[4 * j + 1] = fmaf(bf_hi(xr[2 * j]), c0, e0);
        ao[4 * j + 2] = fmaf(bf_lo(xr[2 * j + 1]), c1, e1); ao[4 * j + 3] = fmaf(bf_hi(xr[2 * j + 1]), c1, e1);
      }
    };
    {
      uint32_t pa[32];
      float4 st[16];
      auto ld = [&](int j) { st[j] = lds_f4(sta + j * 64); };
      auto k_blk = [&](int c) {
#pragma unroll
        for (int i = 0; i < 2; i++) {
          const float4 u = st[2 * c + i];
          const float l0 = u.y * LOG2E, l1 = u.w * LOG2E;
          const float* a = ak + 8 * c + 4 * i;
          pa[4 * c + 2 * i] = SL2 ? phi2l(FOLD(-u.x, ck0, a[0]), u.y, FOLD(-u.z, ck0, a[1]), u.w) : phi2<(VOL & 1) != 0>(FOLD(-u.x, ck0, a[0]), u.y, l0, FOLD(-u.z, ck0, a[1]), u.w, l1);
          pa[4 * c + 2 * i + 1] = SL2 ? phi2l(FOLD(-u.x, ck1, a[2]), u.y, FOLD(-u.z, ck1, a[3]), u.w) : phi2<(VOL & 1) != 0>(FOLD(-u.x, ck1, a[2]), u.y, l0, FOLD(-u.z, ck1, a[3]), u.w, l1);
        }
      };
      const uint32_t voff = sb + w * 8192 + (uint32_t)(8 * (lane >> 4) + (lane & 7)) * 128 + (((2 * wq + ((lane >> 3) & 1)) ^ (lane & 7)) << 4);
      auto v_blk = [&](int c) {
        uint32_t r[4];
#pragma unroll
        for (int i = 0; i < 2; i++) {
          const float4 u = st[2 * c + i];
          const float* a = av + 8 * c + 4 * i;
          r[2 * i] = pack_bf16(FOLD(-u.x, cv0, a[0]) * u.y, FOLD(-u.z, cv0, a[1]) * u.w);
          r[2 * i + 1] = pack_bf16(FOLD(-u.x, cv1, a[2]) * u.y, FOLD(-u.z, cv1, a[3]) * u.w);
        }
        stsm4t(voff + (c < 4 ? S_V0 : S_V1) * SLOT + (c & 3) * 2048, r[0], r[1], r[2], r[3]);
      };
      auto kv_mma = [&](int c) {
        const uint32_t bo = (c < 4 ? S_V0 : S_V1) * 1024 + w * 512 + (c & 3) * 128;
        const uint64_t bb = mkdesc((d0 + bo) | (((A_ONES >> 4) - bo) << 16), HI_SW128);
        if (c == 0) wgmma_rz_n72<1>(kvp, pa[4 * c], pa[4 * c + 1], pa[4 * c + 2], pa[4 * c + 3], bb);
        else wgmma_rs_n72<1>(kvp, pa[4 * c], pa[4 * c + 1], pa[4 * c + 2], pa[4 * c + 3], bb);
      };
      if (NOFOLD == 2) {
        wg_fence();
        wgmma_rs_n128<0>(ak, __float_as_uint(ck0), __float_as_uint(ck1), 0u, 0u, mkdesc(dX + SX14 * 1024, HI_SW128));
        wgmma_rs_n128<0>(av, __float_as_uint(cv0), __float_as_uint(cv1), 0u, 0u, mkdesc(dX + SX14 * 1024, HI_SW128));
        wg_commit();
      }
      if (SH2 && R5) {
        reg_fence(ak);
        ld(6); ld(7); k_blk(3);
        asm volatile("" : "+r"(pa[12]), "+r"(pa[13]), "+r"(pa[14]), "+r"(pa[15]));
      }
      ld(0); ld(1);
      wg_wait<0>();
      if (!(SH2 && R5)) reg_fence(ak);
      reg_fence(av);
      TLS(0, 2);
      if (!R5) release2(B_E);
      release(B_T0);
      if (LQ) { v_blk(0); ld(2); ld(3); } else { ld(2); ld(3); v_blk(0); }
      ld(4); ld(5); v_blk(1); k_blk(0);
      ld(6); ld(7); v_blk(2); ld(8); ld(9); v_blk(3); k_blk(1);
      ld(10); ld(11); v_blk(4); ld(12); ld(13); v_blk(5); k_blk(2);
      ld(14); ld(15); v_blk(6); v_blk(7); if (!(SH2 && R5)) k_blk(3);
      if (RL) { ld(8); ld(9); }
#pragma unroll
      for (int c = 4; c < KS; c++) k_blk(c);
      TLS(0, 3);
      fence_async_smem();
      asm volatile("bar.sync %0, 128;" ::"r"(3 + w) : "memory");
      if (XP == 0) ld_x();
      wg_fence();
#pragma unroll
      for (int c = 0; c < KS; c++) kv_mma(c);
      wg_commit();
#pragma unroll
      for (int c = KS; c < 8; c++) {
        if (RL && c < 7) { ld(2 * c + 2); ld(2 * c + 3); }
        k_blk(c);
        wg_fence();
        kv_mma(c);
        wg_commit();
      }
      if (XP == 3 && (RK == 0 || RK == 9)) ld_x();
      if (QE) { q_step(BAR(B_FQ), 0, SXQ0, QW_SLOTS & 15u); wg_wait<1>(); } else wg_wait<0>();
      reg_fence(kvp);
      auto hand_back = [&]() { release2(B_STG); __syncwarp(); };
      if (!SF) hand_back();
      TLS(0, 4);
      uint4* pp = G.part + b * 544;
      uint32_t pk[8];
#pragma unroll
      for (int j = 0; j < 8; j++) pk[j] = wq >= 2 ? pack_bf16(kvp[16 + 2 * j], kvp[17 + 2 * j]) : pack_bf16(kvp[2 * j], kvp[2 * j + 1]);
      stx4(pp + tid, pk[0], pk[2], pk[4], pk[6]);
      stx4(pp + 256 + tid, pk[1], pk[3], pk[5], pk[7]);
      if (t == 0) stx2(reinterpret_cast<uint2*>(pp + 512) + (tid >> 2), f2x(kvp[32]), f2x(kvp[34]));
      if (SF == 1) hand_back();
      if (XP == 1) ld_x();
      if (!QE) q_step(BAR(B_FQ), 0, SXQ0, QW_SLOTS & 15u);
      if (XP == 2) ld_x();
      if (SF == 2) hand_back();
      if (RK == 0 || RK == 9) {
        uint32_t chk = 0;
#pragma unroll
        for (int j = 0; j < 8; j++) chk ^= xr[4 * j];
        asm volatile("{\n.reg .pred p;\nsetp.eq.u32 p, %0, 0x7FC17FC3;\n@p st.shared.u32 [%1], %0;\n}" ::"r"(chk), "r"(sb + MISC + M_DUM) : "memory");
      }
      const int wd_ = wq * 16 + (lane & 15);
      const uint32_t* src = reinterpret_cast<const uint32_t*>(G.part + ((lane >> 4) * 64 + hg) * 544 + w * 256 + tb * 16) + wd_;
      uint32_t* fin = reinterpret_cast<uint32_t*>(G.fin + hg * 640) + (tb >> 2) * 640 + ((tb >> 1) & 1) * 64 + (tb & 1) * 16 + w * 32 + ((wd_ >> 2) & 3) * 128 + wq * 4 + (wd_ & 3);
      uint32_t v[8];
      auto part_load = [&]() {
#pragma unroll
        for (int i = 0; i < 8; i++) v[i] = ldx1(src + i * 8 * 2176);
      };
#pragma unroll
      for (int k = 1; k < NQ; k++) {
        if (SQ && k == NQ - SQ && w == 1) mbar_wait(BAR(B_GQ), 0);
        q_step(BAR(B_FQ + k), 0, (QX_SLOTS >> (4 * k)) & 15u, (QW_SLOTS >> (4 * k)) & 15u);
        if (SQ && k == NQ - 1 && tid == 0) mbar_arrive(BAR(B_GQ));
        TLS(0, 48 + k);
        if (!MRED && k == PLP) part_load();
        if (!MRED && k == PLC) {
#pragma unroll 1
          for (uint32_t it = 0; it < SPIN_MAX; it++) {
            if (!__any_sync(~0u, max(max(max(v[0], v[1]), max(v[2], v[3])), max(max(v[4], v[5]), max(v[6], v[7]))) == SENT)) break;
            part_load();
          }
          float lo = ((bf_lo(v[0]) + bf_lo(v[1])) + (bf_lo(v[2]) + bf_lo(v[3]))) + ((bf_lo(v[4]) + bf_lo(v[5])) + (bf_lo(v[6]) + bf_lo(v[7])));
          float hi = ((bf_hi(v[0]) + bf_hi(v[1])) + (bf_hi(v[2]) + bf_hi(v[3]))) + ((bf_hi(v[4]) + bf_hi(v[5])) + (bf_hi(v[6]) + bf_hi(v[7])));
          lo += __shfl_xor_sync(~0u, lo, 16); hi += __shfl_xor_sync(~0u, hi, 16);
          if (lane < 16) stx1(fin, pack_bf16(lo, hi));
          TLS(0, 5);
        }
        wg_wait<1>();
        release2(B_EQ + k - 1);
        if (k == RK) { row_stats(); ld_x(); resid(); reg_fence(ao); }
      }
      TLS(0, 13);
      if (!NOCQ) mbar_wait(BAR(B_CQ), 0);
    }
    float4 cq4[8];
    auto ld_cq = [&](int j) {
      if (CQ4) cq4[j >> 1] = lds_f4(aux + A_CS + (j * 8 + 4 * t) * 4);
      else { const float2 ca = lds_f2(aux + A_CS + (j * 8 + 2 * t) * 4), cb = lds_f2(aux + A_CS + (j * 8 + 8 + 2 * t) * 4); cq4[j >> 1] = make_float4(ca.x, ca.y, cb.x, cb.y); }
    };
    if (CQE) {
      if (RK == 0 || RK == 9) row_stats();
#pragma unroll
      for (int j = 0; j < 16; j += 2) ld_cq(j);
    }
    wg_wait<0>();
    reg_fence(aq);
    TLS(0, 15);
    if (!CQE && (RK == 0 || RK == 9)) row_stats();
    uint32_t pq[32];
    if (!CQE && QO >= 2) { ld_cq(0); if (QO == 3) ld_cq(2); }
#pragma unroll
    for (int jj = 0; jj < 16; jj += 2) {
      const int j = QO == 1 ? 14 - jj : jj;
      if (!CQE) {
        if (QO < 2) ld_cq(j);
        else if (j + 2 * (QO - 1) < 16) ld_cq(j + 2 * (QO - 1));
      }
      const float4 c4 = cq4[j >> 1];
#pragma unroll
      for (int i = 0; i < 2; i++) {
        const float cx = i ? c4.z : c4.x, cy = i ? c4.w : c4.y;
        const float* a = aq + 4 * (j + i);
        pq[2 * (j + i)] = SL2 ? phi2l(fmaf(nm0, cx, a[0]), rl0, fmaf(nm0, cy, a[1]), rl0) : phi2<(VOL & 2) != 0>(fmaf(nm0, cx, a[0]), rs0, rl0, fmaf(nm0, cy, a[1]), rs0, rl0);
        pq[2 * (j + i) + 1] = SL2 ? phi2l(fmaf(nm1, cx, a[2]), rl1, fmaf(nm1, cy, a[3]), rl1) : phi2<(VOL & 2) != 0>(fmaf(nm1, cx, a[2]), rs1, rl1, fmaf(nm1, cy, a[3]), rs1, rl1);
      }
    }
    TLS(0, 6);
    if (RK == 9) { resid(); if (RF) reg_fence(ao); }
    mbar_wait_b(BAR(MFIN ? B_KV4 : B_KVB), 0);
    TLS(0, 7);
    uint32_t of[32];
    uint4* mine = G.o + (tb * 32 + hg) * 512 + warp * 64 + g * 4 + (t ^ (g >> 1));
    const uint32_t dW = d0 | (256u << 16);
    auto o_store = [&](int h) {
#pragma unroll
      for (int c = 0; c < 2; c++) stx4(mine + h * 4096 + c * 32, of[8 * h + c], of[8 * h + 2 + c], of[8 * h + 4 + c], of[8 * h + 6 + c]);
    };
    auto out_step = [&](uint32_t slot, const uint32_t* a) {
      const uint32_t d = dW + slot * 1024;
      wg_fence();
#pragma unroll
      for (int kk = 0; kk < 4; kk++) wgmma_rs_n128<1>(ao, a[4 * kk], a[4 * kk + 1], a[4 * kk + 2], a[4 * kk + 3], mkdesc(d + (kk >> 1) * 512 + (kk & 1) * 128, HI_SW128));
      wg_commit();
    };
    uint4 v[NDIR][4];
    auto ld_o = [&](int k) {
      const uint4* p0 = mine + (slab(2 * k, hg) - hg) * 512;
      const uint4* p1 = mine + (slab(2 * k + 1, hg) - hg) * 512;
      v[k][0] = ldx4(p0); v[k][1] = ldx4(p0 + 32); v[k][2] = ldx4(p1); v[k][3] = ldx4(p1 + 32);
    };
    auto ld_all = [&]() {
#pragma unroll
      for (int k = 0; k < NDIR; k++) ld_o(k);
    };
    {
      float oa[4][20];
      const uint32_t dK = (d0 + S_KVB * 1024) | (8u << 16);
      auto o_mma = [&](int h) {
        wgmma_rz_n40<1>(oa[h], pq[8 * h], pq[8 * h + 1], pq[8 * h + 2], pq[8 * h + 3], mkdesc(dK + h * 160, HI_NOSW));
        wgmma_rs_n40<1>(oa[h], pq[8 * h + 4], pq[8 * h + 5], pq[8 * h + 6], pq[8 * h + 7], mkdesc(dK + h * 160 + 16, HI_NOSW));
      };
      wg_fence();
      o_mma(0);
      wg_commit();
      if (OH == 0) { o_mma(1); o_mma(2); o_mma(3); wg_commit(); }
      if (OH == 2) { o_mma(1); wg_commit(); }
      auto norm = [&](int h) {
        const float r0 = SL2 ? rcp(fmaf(oa[h][16], LOG2E, 1e-6f * LOG2E)) : rcp(oa[h][16] + 1e-6f);
        const float r1 = SL2 ? rcp(fmaf(oa[h][18], LOG2E, 1e-6f * LOG2E)) : rcp(oa[h][18] + 1e-6f);
#pragma unroll
        for (int j = 0; j < 4; j++) {
          of[8 * h + 2 * j] = pack_bf16(oa[h][4 * j] * r0, oa[h][4 * j + 1] * r0);
          of[8 * h + 2 * j + 1] = pack_bf16(oa[h][4 * j + 2] * r1, oa[h][4 * j + 3] * r1);
        }
      };
      if (OH == 1) wg_wait<0>(); else wg_wait<1>();
      reg_fence(oa[0]);
      norm(0);
      if (LE == 4) ld_all();
      o_store(0);
      if (LE == 3) ld_all();
      TLS(0, 8);
      if (OH == 1) { wg_fence(); o_mma(1); o_mma(2); o_mma(3); wg_commit(); }
      if (OH == 2) { wg_fence(); o_mma(2); o_mma(3); wg_commit(); }
      wg_wait<0>();
      reg_fence(oa[1]); reg_fence(oa[2]); reg_fence(oa[3]);
      TLP_(0);
      release(B_EAUX);
      norm(1);
      if (OS1 == 3) o_store(1);
      if (E7 && NP == 0 && SL7 && hg == 7) o_store(1);
      if (NP == 0) { norm(2); norm(3); }
      if (E7 && NP == 0 && SL7 && hg == 7) { o_store(2); o_store(3); }
      TLP_(1);
      mbar_wait_b(BAR(B_FWO), 0);
      TLP_(2);
      if (RK == 0) resid();
      if (LE == 2) ld_all();
      TLP_(3);
      out_step(WO_SLOTS & 15u, of);
      TLP_(4);
      if (NP == 1) { norm(2); norm(3); }
      if (LE == 1) ld_all();
      if (LE == 5) ld_o(0);
    }
    if (OS1 == 0) o_store(1);
    mbar_wait(BAR(B_FWO + 1), 0);
    TLP_(5);
    out_step((WO_SLOTS >> 4) & 15u, of + 16);
    TLP_(6);
    const bool early = SL7 && hg == 7;
    if (OS1 == 1 && !(E7 && early)) o_store(1);
    TLP_(7);
    if (early && !E7) { o_store(2); o_store(3); }
    {
      if (DW) __nanosleep(DW);
      if (LE == 0) ld_all();
      if (LE == 5 && NDIR > 1) ld_o(NDIR - 1);
      if (OS1 == 2 && !(E7 && early)) o_store(1);
#pragma unroll
      for (int k = 0; k < NDIR; k++) {
#pragma unroll 1
        for (uint32_t it = 0; it < SPIN_MAX; it++) {
          if (!__any_sync(~0u, max(max(v[k][0].x, v[k][1].x), max(v[k][2].x, v[k][3].x)) == SENT)) break;
#pragma unroll
          for (int j = k; j < (LE == 5 ? k + 1 : NDIR); j++) ld_o(j);
        }
        TLP_(8);
        const uint32_t a[16] = {v[k][0].x, v[k][1].x, v[k][0].y, v[k][1].y, v[k][0].z, v[k][1].z, v[k][0].w, v[k][1].w,
                                v[k][2].x, v[k][3].x, v[k][2].y, v[k][3].y, v[k][2].z, v[k][3].z, v[k][2].w, v[k][3].w};
        mbar_wait(BAR(B_FWO + 2 + k), 0);
        TLS(0, 34 + k);
        out_step((WO_SLOTS >> (8 + 4 * k)) & 15u, a);
        TLP_(9);
        if (k) { wg_wait<1>(); release2(B_EO); }
      }
      if (!early) o_store(2);
    }
    auto routed = [&]() {
      mbar_wait(BAR(B_MOE), 0);
      const float2 kk = lds_f2(sb + MISC + M_IDX + t * 8);
      const int k0 = (int)(~__float_as_uint(kk.x) & 2047u) - tb * 128, k1 = (int)(~__float_as_uint(kk.y) & 2047u) - tb * 128;
      if (NUNIT && __any_sync(~0u, (k0 >> 6) == w || (k1 >> 6) == w)) {
        const uint32_t a0 = (k0 == row0 ? 0x3F80u : 0u) | (k1 == row0 ? 0x3F800000u : 0u);
        const uint32_t a1 = (k0 == row0 + 8 ? 0x3F80u : 0u) | (k1 == row0 + 8 ? 0x3F800000u : 0u);
        wg_fence();
        wgmma_rs_n128<1>(ao, a0, a1, 0u, 0u, mkdesc((d0 + ((MISC + M_MOE) >> 4)) | (64u << 16), 0x40000000u));
        wg_commit();
      }
    };
    auto out_half = [&](int h, const float* v) {
      const uint32_t ost = sb + (w ? S_D1 : S_D0) * SLOT + wq * 4096 + h * 2048;
#pragma unroll
      for (int j = 0; j < 8; j += 2)
        stsm4(ost + ((moff & 2047) ^ (j << 4)), pack_bf16(v[4 * j], v[4 * j + 1]), pack_bf16(v[4 * j + 2], v[4 * j + 3]),
              pack_bf16(v[4 * j + 4], v[4 * j + 5]), pack_bf16(v[4 * j + 6], v[4 * j + 7]));
      if (OUTV == 3 || (OUTV == 4 && h == 0)) {
        __syncwarp();
        __nv_bfloat16* dst = outp + (size_t)(tb * 128 + warp * 16 + (lane >> 3)) * DM + hg * 128 + h * 64 + (lane & 7) * 8;
#pragma unroll
        for (int i = 0; i < 4; i++) {
          const int r = 4 * i + (lane >> 3);
          const uint4 u4 = lds_u4(ost + r * 128 + (((lane & 7) ^ (r & 7)) << 4));
          asm volatile("st.global.v4.u32 [%0], {%1,%2,%3,%4};" ::"l"(dst + (size_t)i * 4 * DM), "r"(u4.x), "r"(u4.y), "r"(u4.z), "r"(u4.w) : "memory");
        }
        return;
      }
      fence_async_smem();
      __syncwarp();
      if (elect_one()) {
        if (OEF) asm volatile("cp.async.bulk.tensor.2d.global.shared::cta.bulk_group.L2::cache_hint [%0, {%2, %3}], [%1], %4;" ::"l"(&tmOut), "r"(ost), "r"(hg * 128 + h * 64), "r"(tb * 128 + warp * 16), "l"(POL_FIRST) : "memory");
        else asm volatile("cp.async.bulk.tensor.2d.global.shared::cta.bulk_group [%0, {%2, %3}], [%1];" ::"l"(&tmOut), "r"(ost), "r"(hg * 128 + h * 64), "r"(tb * 128 + warp * 16) : "memory");
        if (h) asm volatile("cp.async.bulk.commit_group;\ncp.async.bulk.wait_group.read 0;" ::: "memory");
      }
      __syncwarp();
    };
    bool done = false;
    {
      const uint32_t dO = (d0 + w * 256) | (1u << 16);
      auto step = [&](int i, int r, int p, uint32_t as, uint32_t ws) {
        mbar_wait(BAR(B_FWO + i), 0);
        mbar_wait(BAR(B_VAL + r), p);
        TLS(0, 32 + i);
        const uint32_t da = dO + as * 1024, db = dW + ws * 1024;
        wg_fence();
#pragma unroll
        for (int kk = 0; kk < 4; kk++)
          wgmma_ss_n128<0, 1>(ao, mkdesc(da + (kk >> 1) * 512 + (kk & 1) * 2, HI_SW64), mkdesc(db + (kk >> 1) * 512 + (kk & 1) * 128, HI_SW128));
        wg_commit();
      };
      uint64_t tbl = WO_SLOTS >> (4 * I0);
      int r = 0, p = 0, rp = 0;
#pragma unroll 1
      for (int i = I0; i < 12; i++) {
        step(i, r, p, (A_SLOTS >> (4 * r)) & 15u, (uint32_t)tbl & 15u);
        tbl >>= 4;
#pragma unroll
        for (int c = 0; c < 2; c++)
          if (i == OS3 + c && !early) stx4(mine + 3 * 4096 + c * 32, of[24 + c], of[26 + c], of[28 + c], of[30 + c]);
        wg_wait<1>();
        if (i > I0) release(B_EA + rp);
        rp = r;
        if (++r == NA) { r = 0; p ^= 1; }
        if (i >= 3 && i <= 9) release2(B_EO + i - 3);
      }
      if (SPL && w == 1) {
        float bl[32], bh[32];
        mbar_wait(BAR(B_GO), 0);
        routed();
#pragma unroll
        for (int h = 0; h < 2; h++) {
#pragma unroll
          for (int i = 12; i < 16; i++) {
            const int r_ = (i - I0) % NA;
            if (h == 0) { mbar_wait(BAR(B_FWO + i), 0); mbar_wait(BAR(B_VAL + r_), ((i - I0) / NA) & 1); }
            const uint32_t da = dO + ((A_SLOTS >> (4 * r_)) & 15u) * 1024, db = dW + ((uint32_t)(WO_SLOTS >> (4 * i)) & 15u) * 1024 + h * 256;
            if (h == 0 || i == 12) wg_fence();
#pragma unroll
            for (int kk = 0; kk < 4; kk++) {
              const uint64_t a = mkdesc(da + (kk >> 1) * 512 + (kk & 1) * 2, HI_SW64), bb = mkdesc(db + (kk >> 1) * 512 + (kk & 1) * 128, HI_SW128);
              if (i == 12 && kk == 0) wgmma_sz_n64<0, 1>(h ? bh : bl, a, bb); else wgmma_ss_n64<0, 1>(h ? bh : bl, a, bb);
            }
          }
          wg_commit();
        }
        wg_wait<1>();
        reg_fence(ao); reg_fence(bl);
#pragma unroll
        for (int j = 0; j < 32; j++) bl[j] += ao[j];
        out_half(0, bl);
        wg_wait<0>();
        reg_fence(bh);
#pragma unroll
        for (int j = 0; j < 32; j++) bh[j] += ao[32 + j];
        out_half(1, bh);
        done = true;
      } else
#pragma unroll
      for (int i = 12; i < 16; i++) {
        if (i == 16 - STAG && w == 1) mbar_wait(BAR(B_GO), 0);
        step(i, (i - I0) % NA, ((i - I0) / NA) & 1, (A_SLOTS >> (4 * ((i - I0) % NA))) & 15u, (uint32_t)(WO_SLOTS >> (4 * i)) & 15u);
        if (STAG && i == 15 - GOE && tid == 0) mbar_arrive(BAR(B_GO));
      }
    }
    if (!done) {
      routed();
      wg_wait<0>();
      reg_fence(ao);
      TLS(0, 10);
      out_half(0, ao);
      out_half(1, ao + 32);
    }
    TLS(0, 11);
    TLS(128, 9);
  }
}

typedef CUresult (*EncFn)(CUtensorMap*, CUtensorMapDataType, cuuint32_t, void*, const cuuint64_t*, const cuuint64_t*, const cuuint32_t*,
                          const cuuint32_t*, CUtensorMapInterleave, CUtensorMapSwizzle, CUtensorMapL2promotion, CUtensorMapFloatOOBfill);

void make_map2(EncFn enc, CUtensorMap* m, void* p, uint64_t rows, uint64_t cols, uint32_t brows, CUtensorMapL2promotion promo) {
  cuuint64_t gd[2] = {cols, rows}, gs[1] = {cols * 2};
  cuuint32_t bd[2] = {64, brows}, es[2] = {1, 1};
  enc(m, CU_TENSOR_MAP_DATA_TYPE_BFLOAT16, 2, p, gd, gs, bd, es, CU_TENSOR_MAP_INTERLEAVE_NONE, CU_TENSOR_MAP_SWIZZLE_128B, promo,
      CU_TENSOR_MAP_FLOAT_OOB_FILL_NONE);
}
void make_map3(EncFn enc, CUtensorMap* m, void* p, uint64_t rows, uint64_t cols, uint32_t brows) {
  cuuint64_t gd[3] = {64, rows, cols / 64}, gs[2] = {cols * 2, 128};
  cuuint32_t bd[3] = {64, brows, 2}, es[3] = {1, 1, 1};
  enc(m, CU_TENSOR_MAP_DATA_TYPE_BFLOAT16, 3, p, gd, gs, bd, es, CU_TENSOR_MAP_INTERLEAVE_NONE, CU_TENSOR_MAP_SWIZZLE_128B,
      CU_TENSOR_MAP_L2_PROMOTION_L2_256B, CU_TENSOR_MAP_FLOAT_OOB_FILL_NONE);
}

}

extern "C" void kernel_launch(void* const* d_in, const int* in_sizes, int n_in, void* d_out, int out_size) {
  static EncFn enc = nullptr;
  static int by_sm = 0;
  if (!enc) {
    void* fn = nullptr;
    cudaDriverEntryPointQueryResult qr;
    cudaGetDriverEntryPoint("cuTensorMapEncodeTiled", &fn, cudaEnableDefault, &qr);
    enc = (EncFn)fn;
    int dev = 0, sms = 0;
    cudaGetDevice(&dev);
    cudaDeviceGetAttribute(&sms, cudaDevAttrMultiProcessorCount, dev);
    by_sm = MAP == 2 && sms == NCTA + NSVC;
    cudaFuncSetAttribute(fused_kernel, cudaFuncAttributeMaxDynamicSharedMemorySize, SMEM_BYTES);
  }
  CUtensorMap tmX, tmW, tmWo, tmOut, tmG, tmU, tmD, tmR, tmWp;
  {
    cuuint64_t gd[5] = {64, 2, 128, 4, 16}, gs[4] = {2048, 16384, 4096, 128};
    cuuint32_t bd[5] = {64, 2, 4, 4, 2}, es[5] = {1, 1, 1, 1, 1};
    enc(&tmWp, CU_TENSOR_MAP_DATA_TYPE_BFLOAT16, 5, d_in[2], gd, gs, bd, es, CU_TENSOR_MAP_INTERLEAVE_NONE, CU_TENSOR_MAP_SWIZZLE_128B,
        CU_TENSOR_MAP_L2_PROMOTION_L2_256B, CU_TENSOR_MAP_FLOAT_OOB_FILL_NONE);
  }
  make_map2(enc, &tmR, d_in[0], SEQ, DM, 1, CU_TENSOR_MAP_L2_PROMOTION_L2_128B);
  make_map2(enc, &tmX, d_in[0], SEQ, DM, 128, XPROMO);
  make_map3(enc, &tmW, d_in[1], DM, 3 * DM, 64);
  make_map3(enc, &tmWo, d_in[2], DM, DM, 32);
  if (OUTV) make_map2(enc, &tmOut, d_out, SEQ, DM, 16, CU_TENSOR_MAP_L2_PROMOTION_L2_128B); else make_map3(enc, &tmOut, d_out, SEQ, DM, 64);
  make_map2(enc, &tmG, d_in[5], DM, FF, 64, MPROMO);
  make_map2(enc, &tmU, d_in[6], DM, FF, 64, MPROMO);
  make_map2(enc, &tmD, d_in[7], FF, DM, 64, MPROMO);
  typedef const __nv_bfloat16* P;
  cudaLaunchConfig_t cfg = {};
  cfg.gridDim = dim3(NCTA + NSVC); cfg.blockDim = dim3(512); cfg.dynamicSmemBytes = SMEM_BYTES; cfg.stream = cudaStreamPerThread;
  cudaLaunchAttribute at[1];
  at[0].id = cudaLaunchAttributeClusterDimension;
  at[0].val.clusterDim.x = 2; at[0].val.clusterDim.y = 1; at[0].val.clusterDim.z = 1;
  cfg.attrs = at; cfg.numAttrs = 1;
  cudaLaunchKernelEx(&cfg, fused_kernel, (P)d_in[0], (P)d_in[1], (P)d_in[2], (P)d_in[4], (P)d_in[7], (__nv_bfloat16*)d_out, (P)d_in[5], (P)d_in[6], by_sm, tmX, tmW, tmWo, tmOut, tmG, tmU, tmD, tmR, tmWp);
}
```
